```python
import torch

def _softmax(x, axis=-1):
    return torch.softmax(x, dim=axis)
def _gelu(x):
    return torch.nn.functional.gelu(x, approximate="tanh")
def _silu(x):
    return torch.nn.functional.silu(x)
def _sigmoid(x):
    return torch.sigmoid(x)
def _layernorm(x, axis=-1, eps=1e-5):
    m = x.mean(dim=axis, keepdim=True)
    v = x.var(dim=axis, keepdim=True, unbiased=False)
    return (x - m) / torch.sqrt(v + eps)
def _scatter_add(tgt, idx, src, axis=0):
    return tgt.clone().index_add_(axis, idx, src)
def _segment_sum(src, seg, n):
    out = torch.zeros((n,) + src.shape[1:], dtype=src.dtype)
    return out.index_add_(0, seg, src)
def _pad(x, pw):
    flat = tuple(v for pair in reversed(pw) for v in pair)
    return torch.nn.functional.pad(x, flat)

kernel_name = 'interleave_layers__linear_kernel_hedgehog__dense_activation_squared_relu__prompt'

def setup_inputs():

    _w = (lambda a: (lambda t: t.to(torch.bfloat16) if t.is_floating_point() else t)(torch.as_tensor(a)))
    def _A_setup():
        B, S, D, H = 1, 2048, 448, 16
        Dh = D // H
        return {
            "x": _w((lambda *s: torch.randn(*s, dtype=torch.bfloat16) * 0.05)(B, S, D)),
            "wqkv": _w((lambda *s: torch.randn(*s, dtype=torch.bfloat16) * 0.2)(D, 3 * D)),
            "w_phi": _w((lambda *s: torch.randn(*s, dtype=torch.bfloat16) * 0.2)(H, Dh, Dh) * (Dh ** -0.5)),
            "wo": _w((lambda *s: torch.randn(*s, dtype=torch.bfloat16) * 0.05)(D, D)),
        }
    _A_in = _A_setup()

    def _B_setup():
        B, S, D, F = 1, 2048, 448, 1792
        return {
            "x": _w((lambda *s: torch.randn(*s, dtype=torch.bfloat16) * 0.05)(B, S, D)),
            "w1": _w((lambda *s: torch.randn(*s, dtype=torch.bfloat16) * 0.05)(D, F)),
            "b1": _w((lambda *s: torch.randn(*s, dtype=torch.bfloat16) * 0.2)(F)),
            "w2": _w((lambda *s: torch.randn(*s, dtype=torch.bfloat16) * 0.05)(F, D)),
            "b2": _w((lambda *s: torch.randn(*s, dtype=torch.bfloat16) * 0.4)(D)),
        }
    _B_in = _B_setup()

    return {
        "A_x": _A_in["x"],
        "A_wqkv": _A_in["wqkv"],
        "A_w_phi": _A_in["w_phi"],
        "A_wo": _A_in["wo"],
        "B_x": _B_in["x"],
        "B_w1": _B_in["w1"],
        "B_b1": _B_in["b1"],
        "B_w2": _B_in["w2"],
        "B_b2": _B_in["b2"],
    }

def reference(A_x, A_wqkv, A_w_phi, A_wo, B_x, B_w1, B_b1, B_w2, B_b2):
    def _A_ref(x, wqkv, w_phi, wo):
        B, S, D = x.shape
        H = 16; Dh = D // H
        qkv = (lambda x, *d: x.permute(*d))((x @ wqkv).reshape(B, S, 3, H, Dh), 2, 0, 3, 1, 4)
        q, k, v = qkv[0], qkv[1], qkv[2]
        pq = torch.einsum("bhsd,hdf->bhsf", q, w_phi)
        pk = torch.einsum("bhsd,hdf->bhsf", k, w_phi)
        phi_q = torch.concatenate([_softmax(pq, axis=-1), _softmax(-pq, axis=-1)], axis=-1)
        phi_k = torch.concatenate([_softmax(pk, axis=-1), _softmax(-pk, axis=-1)], axis=-1)
        kv = torch.einsum("bhsf,bhsd->bhfd", phi_k, v)
        z  = torch.einsum("bhsf->bhf", phi_k)
        num = torch.einsum("bhqf,bhfd->bhqd", phi_q, kv)
        den = torch.einsum("bhqf,bhf->bhq", phi_q, z)[..., None] + 1e-6
        o = num / den
        return (lambda x, *d: x.permute(*d))(o, 0, 2, 1, 3).reshape(B, S, D) @ wo

    def _B_ref(x, w1, b1, w2, b2):
        h = torch.einsum("bsd,df->bsf", x, w1) + b1
        zero = torch.zeros_like(h)
        r = torch.where(h > zero, h, zero)
        h = r * r
        out = torch.einsum("bsf,fd->bsd", h, w2) + b2
        return out

    x = A_x
    x = x + _A_ref(_layernorm(x, axis=-1), A_wqkv, A_w_phi, A_wo)
    x = x + _B_ref(_layernorm(x, axis=-1), B_w1, B_b1, B_w2, B_b2)
    x = x + _A_ref(_layernorm(x, axis=-1), A_wqkv, A_w_phi, A_wo)
    x = x + _B_ref(_layernorm(x, axis=-1), B_w1, B_b1, B_w2, B_b2)
    return x
```

```cpp
#include <cuda_runtime.h>
#include <cuda_bf16.h>
#include <cuda.h>
#include <stdint.h>

constexpr int NST = 6, STAGE = 28672;
constexpr int OFF_PHIK = NST * STAGE;
constexpr int OFF_V = OFF_PHIK + 32768;
constexpr int OFF_WPHI = OFF_V + 16384;
constexpr int OFF_CB = OFF_WPHI + 8192;
constexpr int OFF_LN = OFF_CB + 1792;
constexpr int OFF_BAR = OFF_LN + 896;
constexpr int SMEM_BYTES = OFF_BAR + 16 * NST;
constexpr int FR = 16 * 8 * 28 * 32;
constexpr int SPIN = 1 << 18;

__device__ uint4 g_XN[FR], g_XR[FR], g_O[FR], g_X1[FR];
__device__ uint4 g_P[8 * FR];
__device__ uint4 g_ST[16 * 8 * 8 * 8];
__device__ uint4 g_KVP[8 * 16 * 1024];
__device__ uint2 g_KVR[8 * 1024];
__device__ uint4 g_CS[448];
#define MARK(i)

__device__ __forceinline__ uint32_t s2u(const void* p) { return (uint32_t)__cvta_generic_to_shared(p); }
__device__ __forceinline__ void mbar_init(uint32_t b, uint32_t c) { asm volatile("mbarrier.init.shared::cta.b64 [%0], %1;" ::"r"(b), "r"(c)); }
__device__ __forceinline__ void mbar_expect(uint32_t b, uint32_t tx) { asm volatile("mbarrier.arrive.expect_tx.shared::cta.b64 _, [%0], %1;" ::"r"(b), "r"(tx) : "memory"); }
__device__ __forceinline__ void mbar_arrive(uint32_t b) { asm volatile("mbarrier.arrive.shared::cta.b64 _, [%0];" ::"r"(b) : "memory"); }
__device__ __forceinline__ void mbar_wait(uint32_t b, uint32_t ph) {
  uint32_t ok = 0;
  for (int it = 0; it < SPIN && !ok; it++)
    asm volatile("{.reg .pred p; mbarrier.try_wait.parity.shared::cta.b64 p,[%1],%2; selp.u32 %0,1,0,p;}" : "=r"(ok) : "r"(b), "r"(ph) : "memory");
}
__device__ __forceinline__ void tma2d(uint32_t dst, const CUtensorMap* m, int c0, int c1, uint32_t bar) {
  asm volatile("cp.async.bulk.tensor.2d.shared::cluster.global.mbarrier::complete_tx::bytes [%0], [%1, {%3, %4}], [%2];"
               ::"r"(dst), "l"(m), "r"(bar), "r"(c0), "r"(c1) : "memory");
}
__device__ __forceinline__ void tma3d(uint32_t dst, const CUtensorMap* m, int c0, int c1, int c2, uint32_t bar) {
  asm volatile("cp.async.bulk.tensor.3d.shared::cluster.global.mbarrier::complete_tx::bytes [%0], [%1, {%3, %4, %5}], [%2];"
               ::"r"(dst), "l"(m), "r"(bar), "r"(c0), "r"(c1), "r"(c2) : "memory");
}
__device__ __forceinline__ void l2pf(const void* p, uint32_t bytes) { asm volatile("cp.async.bulk.prefetch.L2.global [%0], %1;" ::"l"(p), "r"(bytes) : "memory"); }
__device__ __forceinline__ void wg_fence() { asm volatile("wgmma.fence.sync.aligned;" ::: "memory"); }
__device__ __forceinline__ void wg_commit() { asm volatile("wgmma.commit_group.sync.aligned;" ::: "memory"); }
template <int N> __device__ __forceinline__ void wg_wait() { asm volatile("wgmma.wait_group.sync.aligned %0;" ::"n"(N) : "memory"); }
template <int N> __device__ __forceinline__ void regfence(float (&d)[N]) {
#pragma unroll
  for (int i = 0; i < N; i++) asm volatile("" : "+f"(d[i])::"memory");
}
__device__ __forceinline__ void bar_cons() { asm volatile("bar.sync 1, 256;" ::: "memory"); }
__device__ __forceinline__ void bar_ln() { asm volatile("bar.sync 2, 224;" ::: "memory"); }
__device__ __forceinline__ void fence_async() { asm volatile("fence.proxy.async.shared::cta;" ::: "memory"); }
__device__ __forceinline__ uint64_t mkdesc(uint32_t addr, uint32_t lbo, uint32_t sbo, uint32_t swz) {
  return (uint64_t)((addr & 0x3FFFF) >> 4) | ((uint64_t)(lbo >> 4) << 16) | ((uint64_t)(sbo >> 4) << 32) | ((uint64_t)swz << 62);
}
__device__ __forceinline__ uint4 ldll(const uint4* p) {
  uint4 v; asm volatile("ld.relaxed.gpu.global.v4.u32 {%0,%1,%2,%3}, [%4];" : "=r"(v.x), "=r"(v.y), "=r"(v.z), "=r"(v.w) : "l"(p) : "memory"); return v;
}
__device__ __forceinline__ uint2 ldll2(const uint2* p) {
  uint2 v; asm volatile("ld.relaxed.gpu.global.v2.u32 {%0,%1}, [%2];" : "=r"(v.x), "=r"(v.y) : "l"(p) : "memory"); return v;
}
__device__ __forceinline__ void stll(uint4* p, uint32_t x, uint32_t y, uint32_t z, uint32_t w) {
  asm volatile("st.relaxed.gpu.global.v4.u32 [%0], {%1,%2,%3,%4};" ::"l"(p), "r"(x), "r"(y), "r"(z), "r"(w) : "memory");
}
__device__ __forceinline__ void stll2(void* p, uint32_t x, uint32_t y) {
  asm volatile("st.relaxed.gpu.global.v2.u32 [%0], {%1,%2};" ::"l"(p), "r"(x), "r"(y) : "memory");
}
__device__ __forceinline__ uint32_t tg(uint32_t w, uint32_t tag) { return (w & ~1u) | tag; }
__device__ __forceinline__ uint32_t pack(float lo, float hi) {
  uint32_t r; asm("cvt.rn.bf16x2.f32 %0, %1, %2;" : "=r"(r) : "f"(hi), "f"(lo)); return r;
}
__device__ __forceinline__ float blo(uint32_t w) { return __uint_as_float(w << 16); }
__device__ __forceinline__ float bhi(uint32_t w) { return __uint_as_float(w & 0xffff0000u); }
__device__ __forceinline__ float ex2(float x) { float r; asm("ex2.approx.ftz.f32 %0, %1;" : "=f"(r) : "f"(x)); return r; }
__device__ __forceinline__ float rcp(float x) { float r; asm("rcp.approx.ftz.f32 %0, %1;" : "=f"(r) : "f"(x)); return r; }
__device__ __forceinline__ float qsum(float v) { v += __shfl_xor_sync(~0u, v, 1); v += __shfl_xor_sync(~0u, v, 2); return v; }
__device__ __forceinline__ void sts32(uint32_t a, uint32_t v) { asm volatile("st.shared.u32 [%0], %1;" ::"r"(a), "r"(v) : "memory"); }
__device__ __forceinline__ void sts16(uint32_t a, uint32_t v) { asm volatile("st.shared.u16 [%0], %1;" ::"r"(a), "h"((uint16_t)v) : "memory"); }
__device__ __forceinline__ void sts128(uint32_t a, uint32_t x, uint32_t y, uint32_t z, uint32_t w) {
  asm volatile("st.shared.v4.u32 [%0], {%1,%2,%3,%4};" ::"r"(a), "r"(x), "r"(y), "r"(z), "r"(w) : "memory");
}
__device__ __forceinline__ uint32_t sw128(int row, int col) { return row * 128 + ((((col >> 3) ^ row) & 7) << 4) + (col & 7) * 2; }

__device__ __forceinline__ void wgmma_rs56(float (&d)[28], const uint32_t a0, const uint32_t a1, const uint32_t a2, const uint32_t a3, uint64_t db, int sd) {
  asm volatile("{.reg .pred p; setp.ne.b32 p, %33, 0;\n wgmma.mma_async.sync.aligned.m64n56k16.f32.bf16.bf16 {%0,%1,%2,%3,%4,%5,%6,%7,%8,%9,%10,%11,%12,%13,%14,%15,%16,%17,%18,%19,%20,%21,%22,%23,%24,%25,%26,%27}, {%28,%29,%30,%31}, %32, p, 1, 1, 1;}"
   : "+f"(d[0]),"+f"(d[1]),"+f"(d[2]),"+f"(d[3]),"+f"(d[4]),"+f"(d[5]),"+f"(d[6]),"+f"(d[7]),"+f"(d[8]),"+f"(d[9]),"+f"(d[10]),"+f"(d[11]),"+f"(d[12]),"+f"(d[13]),"+f"(d[14]),"+f"(d[15]),"+f"(d[16]),"+f"(d[17]),"+f"(d[18]),"+f"(d[19]),"+f"(d[20]),"+f"(d[21]),"+f"(d[22]),"+f"(d[23]),"+f"(d[24]),"+f"(d[25]),"+f"(d[26]),"+f"(d[27])
   : "r"(a0),"r"(a1),"r"(a2),"r"(a3),"l"(db),"r"(sd));
}
__device__ __forceinline__ void wgmma_rs64(float (&d)[32], const uint32_t a0, const uint32_t a1, const uint32_t a2, const uint32_t a3, uint64_t db, int sd) {
  asm volatile("{.reg .pred p; setp.ne.b32 p, %37, 0;\n wgmma.mma_async.sync.aligned.m64n64k16.f32.bf16.bf16 {%0,%1,%2,%3,%4,%5,%6,%7,%8,%9,%10,%11,%12,%13,%14,%15,%16,%17,%18,%19,%20,%21,%22,%23,%24,%25,%26,%27,%28,%29,%30,%31}, {%32,%33,%34,%35}, %36, p, 1, 1, 1;}"
   : "+f"(d[0]),"+f"(d[1]),"+f"(d[2]),"+f"(d[3]),"+f"(d[4]),"+f"(d[5]),"+f"(d[6]),"+f"(d[7]),"+f"(d[8]),"+f"(d[9]),"+f"(d[10]),"+f"(d[11]),"+f"(d[12]),"+f"(d[13]),"+f"(d[14]),"+f"(d[15]),"+f"(d[16]),"+f"(d[17]),"+f"(d[18]),"+f"(d[19]),"+f"(d[20]),"+f"(d[21]),"+f"(d[22]),"+f"(d[23]),"+f"(d[24]),"+f"(d[25]),"+f"(d[26]),"+f"(d[27]),"+f"(d[28]),"+f"(d[29]),"+f"(d[30]),"+f"(d[31])
   : "r"(a0),"r"(a1),"r"(a2),"r"(a3),"l"(db),"r"(sd));
}
__device__ __forceinline__ void wgmma_rs224(float (&d)[112], const uint32_t a0, const uint32_t a1, const uint32_t a2, const uint32_t a3, uint64_t db, int sd) {
  asm volatile("{.reg .pred p; setp.ne.b32 p, %117, 0;\n wgmma.mma_async.sync.aligned.m64n224k16.f32.bf16.bf16 {%0,%1,%2,%3,%4,%5,%6,%7,%8,%9,%10,%11,%12,%13,%14,%15,%16,%17,%18,%19,%20,%21,%22,%23,%24,%25,%26,%27,%28,%29,%30,%31,%32,%33,%34,%35,%36,%37,%38,%39,%40,%41,%42,%43,%44,%45,%46,%47,%48,%49,%50,%51,%52,%53,%54,%55,%56,%57,%58,%59,%60,%61,%62,%63,%64,%65,%66,%67,%68,%69,%70,%71,%72,%73,%74,%75,%76,%77,%78,%79,%80,%81,%82,%83,%84,%85,%86,%87,%88,%89,%90,%91,%92,%93,%94,%95,%96,%97,%98,%99,%100,%101,%102,%103,%104,%105,%106,%107,%108,%109,%110,%111}, {%112,%113,%114,%115}, %116, p, 1, 1, 1;}"
   : "+f"(d[0]),"+f"(d[1]),"+f"(d[2]),"+f"(d[3]),"+f"(d[4]),"+f"(d[5]),"+f"(d[6]),"+f"(d[7]),"+f"(d[8]),"+f"(d[9]),"+f"(d[10]),"+f"(d[11]),"+f"(d[12]),"+f"(d[13]),"+f"(d[14]),"+f"(d[15]),"+f"(d[16]),"+f"(d[17]),"+f"(d[18]),"+f"(d[19]),"+f"(d[20]),"+f"(d[21]),"+f"(d[22]),"+f"(d[23]),"+f"(d[24]),"+f"(d[25]),"+f"(d[26]),"+f"(d[27]),"+f"(d[28]),"+f"(d[29]),"+f"(d[30]),"+f"(d[31]),"+f"(d[32]),"+f"(d[33]),"+f"(d[34]),"+f"(d[35]),"+f"(d[36]),"+f"(d[37]),"+f"(d[38]),"+f"(d[39]),"+f"(d[40]),"+f"(d[41]),"+f"(d[42]),"+f"(d[43]),"+f"(d[44]),"+f"(d[45]),"+f"(d[46]),"+f"(d[47]),"+f"(d[48]),"+f"(d[49]),"+f"(d[50]),"+f"(d[51]),"+f"(d[52]),"+f"(d[53]),"+f"(d[54]),"+f"(d[55]),"+f"(d[56]),"+f"(d[57]),"+f"(d[58]),"+f"(d[59]),"+f"(d[60]),"+f"(d[61]),"+f"(d[62]),"+f"(d[63]),"+f"(d[64]),"+f"(d[65]),"+f"(d[66]),"+f"(d[67]),"+f"(d[68]),"+f"(d[69]),"+f"(d[70]),"+f"(d[71]),"+f"(d[72]),"+f"(d[73]),"+f"(d[74]),"+f"(d[75]),"+f"(d[76]),"+f"(d[77]),"+f"(d[78]),"+f"(d[79]),"+f"(d[80]),"+f"(d[81]),"+f"(d[82]),"+f"(d[83]),"+f"(d[84]),"+f"(d[85]),"+f"(d[86]),"+f"(d[87]),"+f"(d[88]),"+f"(d[89]),"+f"(d[90]),"+f"(d[91]),"+f"(d[92]),"+f"(d[93]),"+f"(d[94]),"+f"(d[95]),"+f"(d[96]),"+f"(d[97]),"+f"(d[98]),"+f"(d[99]),"+f"(d[100]),"+f"(d[101]),"+f"(d[102]),"+f"(d[103]),"+f"(d[104]),"+f"(d[105]),"+f"(d[106]),"+f"(d[107]),"+f"(d[108]),"+f"(d[109]),"+f"(d[110]),"+f"(d[111])
   : "r"(a0),"r"(a1),"r"(a2),"r"(a3),"l"(db),"r"(sd));
}
__device__ __forceinline__ void wgmma_ss64(float (&d)[32], uint64_t da, uint64_t db, int sd) {
  asm volatile("{.reg .pred p; setp.ne.b32 p, %34, 0;\n wgmma.mma_async.sync.aligned.m64n64k16.f32.bf16.bf16 {%0,%1,%2,%3,%4,%5,%6,%7,%8,%9,%10,%11,%12,%13,%14,%15,%16,%17,%18,%19,%20,%21,%22,%23,%24,%25,%26,%27,%28,%29,%30,%31}, %32, %33, p, 1, 1, 1, 1;}"
   : "+f"(d[0]),"+f"(d[1]),"+f"(d[2]),"+f"(d[3]),"+f"(d[4]),"+f"(d[5]),"+f"(d[6]),"+f"(d[7]),"+f"(d[8]),"+f"(d[9]),"+f"(d[10]),"+f"(d[11]),"+f"(d[12]),"+f"(d[13]),"+f"(d[14]),"+f"(d[15]),"+f"(d[16]),"+f"(d[17]),"+f"(d[18]),"+f"(d[19]),"+f"(d[20]),"+f"(d[21]),"+f"(d[22]),"+f"(d[23]),"+f"(d[24]),"+f"(d[25]),"+f"(d[26]),"+f"(d[27]),"+f"(d[28]),"+f"(d[29]),"+f"(d[30]),"+f"(d[31])
   : "l"(da),"l"(db),"r"(sd));
}

template <int S, int N, int T> __device__ __forceinline__ void ll_issue(uint4 (&v)[T], const uint4* p, int stride) {
#pragma unroll
  for (int i = S; i < S + N; i++) v[i] = ldll(p + i * stride);
}
template <int S, int N, bool TWO, int T> __device__ __forceinline__ void ll_check(uint4 (&v)[T], const uint4* p, int stride, uint32_t tag) {
  for (int it = 0; it < SPIN; it++) {
    uint32_t bad = 0;
#pragma unroll
    for (int i = S; i < S + N; i++) bad |= (v[i].x ^ tag) | (TWO ? (v[i].z ^ tag) : 0u);
    if (!__any_sync(~0u, bad & 1)) break;
    ll_issue<S, N>(v, p, stride);
  }
}
template <class F> __device__ __forceinline__ void hedgehog(const float (&d)[28], F sink) {
  const float L2E = 1.4426950408889634f;
#pragma unroll
  for (int r = 0; r < 2; r++)
#pragma unroll
    for (int h = 0; h < 2; h++) {
      float x[7];
#pragma unroll
      for (int p = 0; p < 6; p++) x[p] = d[h * 16 + (p >> 1) * 4 + (p & 1) + 2 * r] * L2E;
      x[6] = d[12 + h + 2 * r] * L2E;
      float mx = x[0], mn = x[0];
#pragma unroll
      for (int p = 1; p < 7; p++) { mx = fmaxf(mx, x[p]); mn = fminf(mn, x[p]); }
      mx = fmaxf(mx, __shfl_xor_sync(~0u, mx, 1)); mn = fminf(mn, __shfl_xor_sync(~0u, mn, 1));
      mx = fmaxf(mx, __shfl_xor_sync(~0u, mx, 2)); mn = fminf(mn, __shfl_xor_sync(~0u, mn, 2));
      float ep[7], en[7], sp = 0.f, sn = 0.f;
#pragma unroll
      for (int p = 0; p < 7; p++) { ep[p] = ex2(x[p] - mx); en[p] = ex2(mn - x[p]); sp += ep[p]; sn += en[p]; }
      sp = rcp(qsum(sp)); sn = rcp(qsum(sn));
#pragma unroll
      for (int p = 0; p < 7; p++) sink(r, h, p, pack(ep[p] * sp, en[p] * sn));
    }
}
__device__ __forceinline__ void phi_gemm(const float (&x)[28], float (&y)[28], uint32_t wphi) {
  uint32_t f[14];
#pragma unroll
  for (int j = 0; j < 14; j++) f[j] = pack(x[2 * j], x[2 * j + 1]);
  wg_fence();
#pragma unroll
  for (int ks = 0; ks < 3; ks++) wgmma_rs56(y, f[4 * ks], f[4 * ks + 1], f[4 * ks + 2], f[4 * ks + 3], mkdesc(wphi + ks * 2048, 1024, 1024, 1), ks);
  wgmma_rs56(y, f[12], f[13], 0u, 0u, mkdesc(wphi + 3 * 2048, 1024, 1024, 1), 1);
  wg_commit();
}
__device__ __forceinline__ void ln_publish(uint32_t (&xw)[4][4], float* sLN, int warp, int lane, int fbase, uint32_t tag) {
  const int g = lane >> 2;
  float s0 = 0.f, s1 = 0.f;
#pragma unroll
  for (int u = 0; u < 4; u++) {
    stll(g_XR + fbase + u * 32, tg(xw[u][0], tag), xw[u][1], tg(xw[u][2], tag), xw[u][3]);
    s0 += blo(xw[u][0]) + bhi(xw[u][0]) + blo(xw[u][2]) + bhi(xw[u][2]);
    s1 += blo(xw[u][1]) + bhi(xw[u][1]) + blo(xw[u][3]) + bhi(xw[u][3]);
  }
  s0 = qsum(s0) * (1.f / 64); s1 = qsum(s1) * (1.f / 64);
  float v0 = 0.f, v1 = 0.f;
#pragma unroll
  for (int u = 0; u < 4; u++)
#pragma unroll
    for (int k = 0; k < 4; k += 2) {
      float a = blo(xw[u][k]) - s0, b = bhi(xw[u][k]) - s0, c2 = blo(xw[u][k + 1]) - s1, d2 = bhi(xw[u][k + 1]) - s1;
      v0 += a * a + b * b; v1 += c2 * c2 + d2 * d2;
    }
  v0 = qsum(v0); v1 = qsum(v1);
  if ((lane & 3) == 0) { sLN[warp * 16 + g] = s0; sLN[warp * 16 + g + 8] = s1; sLN[112 + warp * 16 + g] = v0; sLN[112 + warp * 16 + g + 8] = v1; }
  bar_ln();
  float m0 = 0.f, m1 = 0.f; v0 = 0.f; v1 = 0.f;
#pragma unroll
  for (int w = 0; w < 7; w++) { m0 += sLN[w * 16 + g]; m1 += sLN[w * 16 + g + 8]; }
  m0 *= (1.f / 7); m1 *= (1.f / 7);
#pragma unroll
  for (int w = 0; w < 7; w++) {
    float a = sLN[w * 16 + g] - m0, b = sLN[w * 16 + g + 8] - m1;
    v0 += sLN[112 + w * 16 + g] + 64.f * a * a; v1 += sLN[112 + w * 16 + g + 8] + 64.f * b * b;
  }
  const float r0 = rsqrtf(v0 * (1.f / 448) + 1e-5f), r1 = rsqrtf(v1 * (1.f / 448) + 1e-5f);
#pragma unroll
  for (int u = 0; u < 4; u++)
    stll(g_XN + fbase + u * 32, tg(pack((blo(xw[u][0]) - m0) * r0, (bhi(xw[u][0]) - m0) * r0), tag), pack((blo(xw[u][1]) - m1) * r1, (bhi(xw[u][1]) - m1) * r1),
         pack((blo(xw[u][2]) - m0) * r0, (bhi(xw[u][2]) - m0) * r0), pack((blo(xw[u][3]) - m1) * r1, (bhi(xw[u][3]) - m1) * r1));
}

__global__ void __launch_bounds__(384, 1)
fused_kernel(const __grid_constant__ CUtensorMap mQKV, const __grid_constant__ CUtensorMap mWO, const __grid_constant__ CUtensorMap mW1,
             const __grid_constant__ CUtensorMap mW2, const __nv_bfloat16* __restrict__ x, const __nv_bfloat16* __restrict__ wphi,
             const __nv_bfloat16* __restrict__ wo, const __nv_bfloat16* __restrict__ w1, const __nv_bfloat16* __restrict__ b1,
             const __nv_bfloat16* __restrict__ w2, const __nv_bfloat16* __restrict__ b2, __nv_bfloat16* __restrict__ out) {
  extern __shared__ __align__(1024) uint8_t sm[];
  const uint32_t sb = s2u(sm);
  const int tid = threadIdx.x, warp = tid >> 5, lane = tid & 31, t = blockIdx.x >> 3, c = blockIdx.x & 7;
  const uint32_t bfull = sb + OFF_BAR, bempty = bfull + 8 * NST;

  if (tid == 256) {
    for (int s = 0; s < NST; s++) { mbar_init(bfull + 8 * s, 1); mbar_init(bempty + 8 * s, 8); }
    asm volatile("fence.mbarrier_init.release.cluster;" ::: "memory");
    fence_async();
  }
  __syncthreads();
  if (warp >= 8) {
    asm volatile("setmaxnreg.dec.sync.aligned.u32 24;");
    auto issue = [&](int i, int s) {
      const uint32_t dst = sb + s * STAGE, bar = bfull + 8 * s;
      mbar_expect(bar, STAGE);
      if (i < 4) {
        tma2d(dst, &mQKV, 448 + 56 * c, 112 * i, bar); tma2d(dst + 7168, &mQKV, 480 + 56 * c, 112 * i, bar);
        tma2d(dst + 14336, &mQKV, 896 + 56 * c, 112 * i, bar); tma2d(dst + 21504, &mQKV, 928 + 56 * c, 112 * i, bar);
      } else if (i >= 8 && i < 15) {
        tma3d(dst, &mW1, 0, 64 * (i - 8), 7 * c, bar);
      } else {
        const CUtensorMap* m = i < 6 ? &mQKV : (i < 8 ? &mWO : &mW2);
        const int n0 = i < 8 ? 56 * c : 64 * (i - 15), k0 = i < 8 ? 224 * (i & 1) : 224 * c;
        tma2d(dst, m, n0, k0, bar); tma2d(dst + 7168, m, n0, k0 + 112, bar);
        tma2d(dst + 14336, m, n0 + 32, k0, bar); tma2d(dst + 21504, m, n0 + 32, k0 + 112, bar);
      }
    };
    if (tid == 256) {
      int s = 0; uint32_t ph = 1;
      for (int n = 0; n < 44; n++) {
        mbar_wait(bempty + 8 * s, ph);
        issue(n >= 22 ? n - 22 : n, s);
        if (++s == NST) { s = 0; ph ^= 1; }
      }
    } else if (tid == 288) {
      l2pf((const uint8_t*)wo + blockIdx.x * 3136, 3136);
      l2pf((const uint8_t*)w1 + blockIdx.x * 12544, 12544);
      l2pf((const uint8_t*)w2 + blockIdx.x * 12544, 12544);
    }
  } else {
  asm volatile("setmaxnreg.inc.sync.aligned.u32 240;");

  const int wg = warp >> 2, g = lane >> 2, q = lane & 3, t128 = tid & 127;
  const int row0 = warp * 16 + g;
  const int fmine = ((t * 8 + warp) * 28) * 32 + lane;
  const int fred = ((t * 8 + c) * 28 + 4 * warp) * 32 + lane;
  float* sLN = (float*)(sm + OFF_LN);
  const uint32_t sPK = sb + OFF_PHIK, sV = sb + OFF_V, sW = sb + OFF_WPHI;
  MARK(0);
  {
    uint32_t xw[4][4];
    uint4 cw[28];
    if (warp < 7) {
      const uint32_t* xp = (const uint32_t*)(x + (size_t)(t * 128 + c * 16 + g) * 448 + warp * 64 + 2 * q);
#pragma unroll
      for (int u = 0; u < 4; u++) { xw[u][0] = __ldg(xp + u * 8); xw[u][1] = __ldg(xp + u * 8 + 1792); xw[u][2] = __ldg(xp + u * 8 + 4); xw[u][3] = __ldg(xp + u * 8 + 1796); }
    } else if (blockIdx.x < 112) {
      const uint4* wp = (const uint4*)(w1 + (size_t)(lane >> 1) * 1792 + blockIdx.x * 16 + (lane & 1) * 8);
#pragma unroll
      for (int i = 0; i < 28; i++) cw[i] = __ldg(wp + i * 16 * 224);
    }
#pragma unroll
    for (int i = 0; i < 8; i++) {
      const int e = tid + i * 256, k = e >> 5, n = (e & 31) * 2;
      uint32_t v = 0;
      if (k < 56 && n < 56) {
        const int hk = k >= 28, d = k - 28 * hk;
        const unsigned short* wp = (const unsigned short*)wphi + ((2 * c + hk) * 28 + d) * 28;
        if (n >= 24 && n < 32) { const uint32_t w = __ldg(wp + 24 + ((n - 24) >> 1)); v = hk ? (w << 16) : w; }
        else if ((n >= 32) == hk) v = __ldg((const uint32_t*)(wp + (n & 31)));
      }
      sts32(sW + sw128(k, n), v);
    }
    sts128(sPK + sw128(tid, 56), 0, 0, 0, 0);
    fence_async();
    if (warp < 7) ln_publish(xw, sLN, warp, lane, fred, 1u);
    else if (blockIdx.x < 112) {
      float s[8] = {0, 0, 0, 0, 0, 0, 0, 0};
#pragma unroll
      for (int i = 0; i < 28; i++) {
        s[0] += blo(cw[i].x); s[1] += bhi(cw[i].x); s[2] += blo(cw[i].y); s[3] += bhi(cw[i].y);
        s[4] += blo(cw[i].z); s[5] += bhi(cw[i].z); s[6] += blo(cw[i].w); s[7] += bhi(cw[i].w);
      }
#pragma unroll
      for (int i = 0; i < 8; i++)
#pragma unroll
        for (int o = 2; o < 32; o <<= 1) s[i] += __shfl_xor_sync(~0u, s[i], o);
      if (lane < 2) {
        stll(g_CS + blockIdx.x * 4 + lane * 2, tg(__float_as_uint(s[0]), 1), __float_as_uint(s[1]), __float_as_uint(s[2]), __float_as_uint(s[3]));
        stll(g_CS + blockIdx.x * 4 + lane * 2 + 1, tg(__float_as_uint(s[4]), 1), __float_as_uint(s[5]), __float_as_uint(s[6]), __float_as_uint(s[7]));
      }
    }
  }
  bar_cons();
  MARK(1);

  int cs = 0, rs = 0; uint32_t cph = 0;
  auto acquire = [&]() -> uint32_t { mbar_wait(bfull + 8 * cs, cph); const uint32_t a = sb + cs * STAGE; if (++cs == NST) { cs = 0; cph ^= 1; } return a; };
  auto release = [&]() { if (lane == 0) mbar_arrive(bempty + 8 * rs); if (++rs == NST) rs = 0; };

#pragma unroll 1
  for (int L = 0; L < 2; L++) {
    const uint32_t tag = 1 - L;
    uint32_t phq[2][2][7];
    {
      uint4 a[28];
      const uint4* pa = g_XN + fmine;
      ll_issue<0, 1>(a, pa, 32); ll_check<0, 1, false>(a, pa, 32, tag); ll_issue<1, 27>(a, pa, 32);
      MARK(2 + L * 19);
      float ak[28], av[28], aq[28], pp[28];
#define KVSTAGE(i) { ll_check<7 * i, 7, false>(a, pa, 32, tag); const uint32_t st = acquire(); wg_fence(); \
      _Pragma("unroll") for (int ks = 0; ks < 7; ks++) { const uint4 f = a[7 * i + ks]; \
        wgmma_rs56(ak, f.x, f.y, f.z, f.w, mkdesc(st + ks * 1024, 7168, 512, 2), i | ks); \
        wgmma_rs56(av, f.x, f.y, f.z, f.w, mkdesc(st + 14336 + ks * 1024, 7168, 512, 2), i | ks); } \
      wg_commit(); if (i > 0) { wg_wait<1>(); release(); } }
      KVSTAGE(0) KVSTAGE(1) KVSTAGE(2) KVSTAGE(3)
      wg_wait<0>(); release(); regfence(ak); regfence(av);
      MARK(3 + L * 19);
      phi_gemm(ak, pp, sW);
#pragma unroll
      for (int j = 0; j < 7; j++) {
        const int n = 8 * j + 2 * q, n2 = n < 28 ? n : n + 4;
        sts32(sV + sw128(row0, n2), pack(av[4 * j], av[4 * j + 1])); sts32(sV + sw128(row0 + 8, n2), pack(av[4 * j + 2], av[4 * j + 3]));
      }
      { const int n2 = 28 + 2 * (q & 1) + 32 * (q >> 1); const uint32_t v = (q & 1) ? 0u : 0x3F80u; sts32(sV + sw128(row0, n2), v); sts32(sV + sw128(row0 + 8, n2), v); }
#pragma unroll
      for (int i = 0; i < 2; i++) {
        const uint32_t st = acquire(); wg_fence();
#pragma unroll
        for (int ks = 0; ks < 14; ks++) { const uint4 f = a[14 * i + ks]; wgmma_rs56(aq, f.x, f.y, f.z, f.w, mkdesc(st + ks * 1024, 14336, 512, 2), i | ks); }
        wg_commit();
      }
      wg_wait<2>(); regfence(pp);
      hedgehog(pp, [&](int r, int h, int p, uint32_t v) { sts32(sPK + h * 16384 + sw128(row0 + 8 * r, 8 * p + 2 * q), v); });
      fence_async();
      wg_wait<0>(); release(); release(); regfence(aq);
      bar_cons();
      MARK(4 + L * 19);
      float kv[32];
      wg_fence();
#pragma unroll
      for (int ks = 0; ks < 8; ks++) wgmma_ss64(kv, mkdesc(sPK + wg * 16384 + ks * 2048, 1024, 1024, 1), mkdesc(sV + ks * 2048, 1024, 1024, 1), ks);
      wg_commit();
      phi_gemm(aq, pp, sW);
      wg_wait<1>(); regfence(kv);
#pragma unroll
      for (int u = 0; u < 4; u++) {
        float e[4];
#pragma unroll
        for (int i = 0; i < 4; i++) e[i] = wg ? kv[16 + 4 * u + i] : kv[4 * u + i];
        stll(g_KVP + (c * 16 + t) * 1024 + wg * 512 + u * 128 + t128, tg(__float_as_uint(e[0]), tag), __float_as_uint(e[1]), __float_as_uint(e[2]), __float_as_uint(e[3]));
      }
      MARK(5 + L * 19);
      bar_cons();
#pragma unroll
      for (int i = 0; i < 4; i++) sts128(sV + (tid + i * 256) * 16, 0, 0, 0, 0);
      wg_wait<0>(); regfence(pp);
      hedgehog(pp, [&](int r, int h, int p, uint32_t v) { phq[r][h][p] = v; });
    }
    MARK(6 + L * 19);
    {
      uint4 k4[4];
      const uint4* pk = g_KVP + (c * 16 + 4 * q) * 1024 + 64 * t + (tid >> 2);
      ll_issue<0, 4>(k4, pk, 1024); ll_check<0, 4, false>(k4, pk, 1024, tag);
      float s0 = 0, s1 = 0, s2 = 0, s3 = 0;
#pragma unroll
      for (int i = 0; i < 4; i++) { s0 += __uint_as_float(k4[i].x); s1 += __uint_as_float(k4[i].y); s2 += __uint_as_float(k4[i].z); s3 += __uint_as_float(k4[i].w); }
      s0 = qsum(s0); s1 = qsum(s1); s2 = qsum(s2); s3 = qsum(s3);
      if (q == 0) stll2(g_KVR + c * 1024 + 64 * t + (tid >> 2), tg(pack(s0, s1), tag), pack(s2, s3));
      MARK(7 + L * 19);
      if (L == 0 && tid < 128) {
        const int e = tid < 112 ? tid : 0, n = 224 * c + 2 * e;
        uint4 cv[1];
        ll_issue<0, 1>(cv, g_CS + (n >> 2), 0); ll_check<0, 1, false>(cv, g_CS + (n >> 2), 0, 1u);
        const uint32_t bb = __ldg((const uint32_t*)(b1 + n));
        if (tid < 112) sts128(sb + OFF_CB + e * 16, (e & 1) ? cv[0].z : cv[0].x, (e & 1) ? cv[0].w : cv[0].y, bb << 16, bb & 0xffff0000u);
      }
      bar_cons();
      uint2 r[4];
      const uint2* pr = g_KVR + c * 1024 + wg * 512 + t128;
      for (int it = 0; it < SPIN; it++) {
        uint32_t bad = 0;
#pragma unroll
        for (int u = 0; u < 4; u++) { r[u] = ldll2(pr + u * 128); bad |= r[u].x ^ tag; }
        if (!__any_sync(~0u, bad & 1)) break;
      }
#pragma unroll
      for (int u = 0; u < 4; u++) {
        const int d = 8 * u + 2 * q;
        if (d < 28) { sts32(sV + sw128(row0, 28 * wg + d), r[u].x); sts32(sV + sw128(row0 + 8, 28 * wg + d), r[u].y); }
        else if (d == 28) {
#pragma unroll
          for (int j = 0; j < 4; j++) { sts16(sV + sw128(row0, 56 + 2 * j + wg), r[u].x); sts16(sV + sw128(row0 + 8, 56 + 2 * j + wg), r[u].y); }
        }
      }
      fence_async();
      bar_cons();
      MARK(8 + L * 19);
      float o[32];
      wg_fence();
#pragma unroll
      for (int ks = 0; ks < 8; ks++) {
        const int h = ks >> 2, p = 2 * (ks & 3);
        wgmma_rs64(o, phq[0][h][p], phq[1][h][p], p < 6 ? phq[0][h][p < 6 ? p + 1 : 0] : 0u, p < 6 ? phq[1][h][p < 6 ? p + 1 : 0] : 0u, mkdesc(sV + ks * 2048, 1024, 1024, 1), ks);
      }
      wg_commit(); wg_wait<0>(); regfence(o);
      const float iA0 = rcp(o[28] + 1e-6f), iB0 = rcp(o[29] + 1e-6f), iA1 = rcp(o[30] + 1e-6f), iB1 = rcp(o[31] + 1e-6f);
#pragma unroll
      for (int j = 0; j < 7; j++) {
        const bool hb = 8 * j + 2 * q >= 28; const float i0 = hb ? iB0 : iA0, i1 = hb ? iB1 : iA1; const int J = 7 * c + j;
        stll2((uint2*)(g_O + fmine + (J >> 1) * 32) + (J & 1), tg(pack(o[4 * j] * i0, o[4 * j + 1] * i0), tag), pack(o[4 * j + 2] * i1, o[4 * j + 3] * i1));
      }
    }
    MARK(9 + L * 19);
    {
      uint2 xr[7];
      for (int it = 0; it < SPIN; it++) {
        uint32_t bad = 0;
#pragma unroll
        for (int j = 0; j < 7; j++) { const int J = 7 * c + j; xr[j] = ldll2((const uint2*)(g_XR + fmine + (J >> 1) * 32) + (J & 1)); bad |= xr[j].x ^ tag; }
        if (!__any_sync(~0u, bad & 1)) break;
      }
      uint4 a[28];
      const uint4* pa = g_O + fmine;
      ll_issue<0, 28>(a, pa, 32);
      float y[28];
      uint32_t st;
#define WOSTEP(i) { ll_check<7 * i, 7, true>(a, pa, 32, tag); if (!(i & 1)) st = acquire(); wg_fence(); \
      _Pragma("unroll") for (int ks = 0; ks < 7; ks++) { const uint4 f = a[7 * i + ks]; \
        wgmma_rs56(y, f.x, f.y, f.z, f.w, mkdesc(st + ((i & 1) * 7 + ks) * 1024, 14336, 512, 2), i | ks); } wg_commit(); }
      WOSTEP(0) MARK(10 + L * 19); WOSTEP(1) WOSTEP(2) WOSTEP(3)
      wg_wait<0>(); release(); release(); regfence(y);
      MARK(11 + L * 19);
      float s0 = 0.f, s1 = 0.f;
#pragma unroll
      for (int j = 0; j < 7; j++) {
        const int J = 7 * c + j;
        const uint32_t w0 = tg(pack(blo(xr[j].x) + y[4 * j], bhi(xr[j].x) + y[4 * j + 1]), tag), w1_ = pack(blo(xr[j].y) + y[4 * j + 2], bhi(xr[j].y) + y[4 * j + 3]);
        stll2((uint2*)(g_X1 + fmine + (J >> 1) * 32) + (J & 1), w0, w1_);
        y[4 * j] = blo(w0); y[4 * j + 1] = bhi(w0); y[4 * j + 2] = blo(w1_); y[4 * j + 3] = bhi(w1_);
        s0 += y[4 * j] + y[4 * j + 1]; s1 += y[4 * j + 2] + y[4 * j + 3];
      }
      s0 = qsum(s0) * (1.f / 56); s1 = qsum(s1) * (1.f / 56);
      float v0 = 0.f, v1 = 0.f;
#pragma unroll
      for (int j = 0; j < 7; j++) {
        const float d0 = y[4 * j] - s0, d1 = y[4 * j + 1] - s0, d2 = y[4 * j + 2] - s1, d3 = y[4 * j + 3] - s1;
        v0 += d0 * d0 + d1 * d1; v1 += d2 * d2 + d3 * d3;
      }
      v0 = qsum(v0); v1 = qsum(v1);
      if (q == 0) stll(g_ST + ((t * 8 + warp) * 8 + c) * 8 + g, tg(__float_as_uint(s0), tag), __float_as_uint(v0), __float_as_uint(s1), __float_as_uint(v1));
    }
    MARK(12 + L * 19);
    uint32_t hf[56];
    {
      uint4 a[28];
      const uint4* pa = g_X1 + fmine;
      ll_issue<0, 16>(a, pa, 32);
      float y[112];
#define F1STAGE(i) { ll_check<4 * i, 4, true>(a, pa, 32, tag); const uint32_t st = acquire(); wg_fence(); \
      _Pragma("unroll") for (int ks = 0; ks < 4; ks++) { const uint4 f = a[4 * i + ks]; \
        wgmma_rs224(y, f.x, f.y, f.z, f.w, mkdesc(st + ks * 1024, 4096, 512, 2), i | ks); } \
      wg_commit(); if (i > 0) { wg_wait<1>(); release(); if (i < 4) ll_issue<(i < 4 ? 4 * i + 12 : 0), 4>(a, pa, 32); } }
      F1STAGE(0) MARK(13 + L * 19); F1STAGE(1) F1STAGE(2) F1STAGE(3) F1STAGE(4) F1STAGE(5)
      uint4 sv[2];
      const uint4* ps = g_ST + ((t * 8 + warp) * 8 + 2 * q) * 8 + g;
      ll_issue<0, 2>(sv, ps, 8);
      F1STAGE(6)
      ll_check<0, 2, false>(sv, ps, 8, tag);
      const float ma = __uint_as_float(sv[0].x), mb = __uint_as_float(sv[1].x), mc = __uint_as_float(sv[0].z), md = __uint_as_float(sv[1].z);
      const float m0 = qsum(ma + mb) * 0.125f, m1 = qsum(mc + md) * 0.125f;
      const float v0 = qsum(__uint_as_float(sv[0].y) + __uint_as_float(sv[1].y) + 56.f * ((ma - m0) * (ma - m0) + (mb - m0) * (mb - m0)));
      const float v1 = qsum(__uint_as_float(sv[0].w) + __uint_as_float(sv[1].w) + 56.f * ((mc - m1) * (mc - m1) + (md - m1) * (md - m1)));
      const float r0 = rsqrtf(v0 * (1.f / 448) + 1e-5f), r1 = rsqrtf(v1 * (1.f / 448) + 1e-5f);
      const float n0 = -m0 * r0, n1 = -m1 * r1;
      wg_wait<0>(); release(); regfence(y);
      MARK(14 + L * 19);
#pragma unroll
      for (int j = 0; j < 28; j++) {
        const float4 cb = *(const float4*)(sm + OFF_CB + (j * 4 + q) * 16);
        const float h0 = fmaxf(fmaf(y[4 * j], r0, fmaf(n0, cb.x, cb.z)), 0.f), h1 = fmaxf(fmaf(y[4 * j + 1], r0, fmaf(n0, cb.y, cb.w)), 0.f);
        const float h2 = fmaxf(fmaf(y[4 * j + 2], r1, fmaf(n1, cb.x, cb.z)), 0.f), h3 = fmaxf(fmaf(y[4 * j + 3], r1, fmaf(n1, cb.y, cb.w)), 0.f);
        hf[2 * j] = pack(h0 * h0, h1 * h1); hf[2 * j + 1] = pack(h2 * h2, h3 * h3);
      }
    }
    MARK(15 + L * 19);
    {
      float ya[32], yb[32];
      uint4* pp = g_P + ((t * 8 + warp) * 8 + c) * 28 * 32 + lane;
#define F2STORE(j, Y) { regfence(Y); _Pragma("unroll") for (int u = 0; u < 4; u++) \
      stll(pp + (4 * (j) + u) * 32, tg(pack(Y[8 * u], Y[8 * u + 1]), tag), pack(Y[8 * u + 2], Y[8 * u + 3]), pack(Y[8 * u + 4], Y[8 * u + 5]), pack(Y[8 * u + 6], Y[8 * u + 7])); }
#define F2PASS(j, Y, Z) { const uint32_t st = acquire(); wg_fence(); \
      _Pragma("unroll") for (int ks = 0; ks < 14; ks++) wgmma_rs64(Y, hf[4 * ks], hf[4 * ks + 1], hf[4 * ks + 2], hf[4 * ks + 3], mkdesc(st + ks * 1024, 14336, 512, 2), ks); \
      wg_commit(); if (j > 0) { wg_wait<1>(); release(); F2STORE(j - 1, Z) } }
      F2PASS(0, ya, yb) F2PASS(1, yb, ya) F2PASS(2, ya, yb) F2PASS(3, yb, ya) F2PASS(4, ya, yb) F2PASS(5, yb, ya) F2PASS(6, ya, yb)
      wg_wait<0>(); release(); F2STORE(6, ya)
    }
    MARK(16 + L * 19);
    if (warp < 7) {
      uint4 x1[4], p[32];
      uint32_t bw[8];
      ll_issue<0, 4>(x1, g_X1 + fred, 32);
#pragma unroll
      for (int i = 0; i < 8; i++) bw[i] = __ldg((const uint32_t*)(b2 + warp * 64 + i * 8 + 2 * q));
      const uint4* pp = g_P + ((t * 8 + c) * 8 * 28 + 4 * warp) * 32 + lane;
      ll_issue<0, 8>(p, pp + 96, 896); ll_check<0, 8, false>(p, pp + 96, 896, tag);
      ll_issue<8, 8>(p, pp + 64 - 8 * 896, 896); ll_issue<16, 8>(p, pp + 32 - 16 * 896, 896); ll_issue<24, 8>(p, pp - 24 * 896, 896);
      MARK(17 + L * 19);
      uint32_t xw[4][4];
#define REDU(u, S) { if (S > 0) ll_check<S, 8, false>(p, pp + u * 32 - S * 896, 896, tag); \
      float e[8] = {blo(x1[u].x) + blo(bw[2 * u]), bhi(x1[u].x) + bhi(bw[2 * u]), blo(x1[u].y) + blo(bw[2 * u]), bhi(x1[u].y) + bhi(bw[2 * u]), \
                    blo(x1[u].z) + blo(bw[2 * u + 1]), bhi(x1[u].z) + bhi(bw[2 * u + 1]), blo(x1[u].w) + blo(bw[2 * u + 1]), bhi(x1[u].w) + bhi(bw[2 * u + 1])}; \
      _Pragma("unroll") for (int i = S; i < S + 8; i++) { e[0] += blo(p[i].x); e[1] += bhi(p[i].x); e[2] += blo(p[i].y); e[3] += bhi(p[i].y); \
        e[4] += blo(p[i].z); e[5] += bhi(p[i].z); e[6] += blo(p[i].w); e[7] += bhi(p[i].w); } \
      xw[u][0] = pack(e[0], e[1]); xw[u][1] = pack(e[2], e[3]); xw[u][2] = pack(e[4], e[5]); xw[u][3] = pack(e[6], e[7]); }
      REDU(3, 0) REDU(2, 8) REDU(1, 16) REDU(0, 24)
      MARK(18 + L * 19);
      if (L == 0) ln_publish(xw, sLN, warp, lane, fred, 0u);
      else {
        uint32_t* op = (uint32_t*)(out + (size_t)(t * 128 + c * 16 + g) * 448 + warp * 64 + 2 * q);
#pragma unroll
        for (int u = 0; u < 4; u++) { op[u * 8] = xw[u][0]; op[u * 8 + 1792] = xw[u][1]; op[u * 8 + 4] = xw[u][2]; op[u * 8 + 1796] = xw[u][3]; }
      }
    } else if (L == 1 && blockIdx.x < 112 && lane < 4) stll(g_CS + blockIdx.x * 4 + lane, 0, 0, 0, 0);
    MARK(19 + L * 19);
  }
  }
}

typedef CUresult (*EncFn)(CUtensorMap*, CUtensorMapDataType, cuuint32_t, void*, const cuuint64_t*, const cuuint64_t*, const cuuint32_t*, const cuuint32_t*,
                          CUtensorMapInterleave, CUtensorMapSwizzle, CUtensorMapL2promotion, CUtensorMapFloatOOBfill);

extern "C" void kernel_launch(void* const* d_in, const int* in_sizes, int n_in, void* d_out, int out_size) {
  static EncFn enc = nullptr;
  if (!enc) {
    void* fn = nullptr; cudaDriverEntryPointQueryResult qr;
    cudaGetDriverEntryPoint("cuTensorMapEncodeTiled", &fn, cudaEnableDefault, &qr);
    enc = (EncFn)fn;
    cudaFuncSetAttribute(fused_kernel, cudaFuncAttributeMaxDynamicSharedMemorySize, SMEM_BYTES);
  }
  CUtensorMap mQKV, mWO, mW1, mW2;
  const cuuint32_t es[3] = {1, 1, 1};
  auto enc2 = [&](CUtensorMap* m, void* p, cuuint64_t cols, cuuint64_t rows) {
    const cuuint64_t dims[2] = {cols, rows}, str[1] = {cols * 2}; const cuuint32_t box[2] = {32, 112};
    enc(m, CU_TENSOR_MAP_DATA_TYPE_BFLOAT16, 2, p, dims, str, box, es, CU_TENSOR_MAP_INTERLEAVE_NONE, CU_TENSOR_MAP_SWIZZLE_64B,
        CU_TENSOR_MAP_L2_PROMOTION_L2_128B, CU_TENSOR_MAP_FLOAT_OOB_FILL_NONE);
  };
  enc2(&mQKV, d_in[1], 1344, 448); enc2(&mWO, d_in[3], 448, 448); enc2(&mW2, d_in[7], 448, 1792);
  {
    const cuuint64_t dims[3] = {32, 448, 56}, str[2] = {3584, 64}; const cuuint32_t box[3] = {32, 64, 7};
    enc(&mW1, CU_TENSOR_MAP_DATA_TYPE_BFLOAT16, 3, d_in[5], dims, str, box, es, CU_TENSOR_MAP_INTERLEAVE_NONE, CU_TENSOR_MAP_SWIZZLE_64B,
        CU_TENSOR_MAP_L2_PROMOTION_L2_128B, CU_TENSOR_MAP_FLOAT_OOB_FILL_NONE);
  }
  typedef const __nv_bfloat16* BP;
  fused_kernel<<<128, 384, SMEM_BYTES>>>(mQKV, mWO, mW1, mW2, (BP)d_in[0], (BP)d_in[2], (BP)d_in[3], (BP)d_in[5], (BP)d_in[6], (BP)d_in[7], (BP)d_in[8],
                                         (__nv_bfloat16*)d_out);
}
```

```cpp
#include <cuda_runtime.h>
#include <cuda_bf16.h>
#include <cuda.h>
#include <stdint.h>

constexpr int NST = 6, STAGE = 28672;
constexpr int OFF_PHIK = NST * STAGE;
constexpr int OFF_V = OFF_PHIK + 32768;
constexpr int OFF_WPHI = OFF_V + 16384;
constexpr int OFF_CB = OFF_WPHI + 8192;
constexpr int OFF_LN = OFF_CB + 1792;
constexpr int OFF_BAR = OFF_LN + 896;
constexpr int SMEM_BYTES = OFF_BAR + 16 * NST;
constexpr int FR = 16 * 8 * 28 * 32;
constexpr int SPIN = 1 << 18;

__device__ uint4 g_F[4 * FR];
constexpr int XN = 0, XR = FR, OO = 2 * FR, X1 = 3 * FR;
__device__ uint4 g_P[8 * FR];
__device__ uint4 g_ST[16 * 8 * 8 * 8];
__device__ uint4 g_KVP[8 * 16 * 1024];
__device__ uint2 g_KVR[8 * 1024];
__device__ uint4 g_CS[448];
#define MARK(i)

__device__ __forceinline__ uint32_t s2u(const void* p) { return (uint32_t)__cvta_generic_to_shared(p); }
__device__ __forceinline__ void mbar_init(uint32_t b, uint32_t c) { asm volatile("mbarrier.init.shared::cta.b64 [%0], %1;" ::"r"(b), "r"(c)); }
__device__ __forceinline__ void mbar_expect(uint32_t b, uint32_t tx) { asm volatile("mbarrier.arrive.expect_tx.shared::cta.b64 _, [%0], %1;" ::"r"(b), "r"(tx) : "memory"); }
__device__ __forceinline__ void mbar_arrive(uint32_t b) { asm volatile("mbarrier.arrive.shared::cta.b64 _, [%0];" ::"r"(b) : "memory"); }
__device__ __forceinline__ void mbar_wait(uint32_t b, uint32_t ph) {
  uint32_t ok = 0;
#pragma unroll 1
  for (int it = 0; it < SPIN && !ok; it++)
    asm volatile("{.reg .pred p; mbarrier.try_wait.parity.shared::cta.b64 p,[%1],%2; selp.u32 %0,1,0,p;}" : "=r"(ok) : "r"(b), "r"(ph) : "memory");
}
__device__ __forceinline__ void tma2d(uint32_t dst, const CUtensorMap* m, int c0, int c1, uint32_t bar) {
  asm volatile("cp.async.bulk.tensor.2d.shared::cluster.global.mbarrier::complete_tx::bytes [%0], [%1, {%3, %4}], [%2];"
               ::"r"(dst), "l"(m), "r"(bar), "r"(c0), "r"(c1) : "memory");
}
__device__ __forceinline__ void tma3d(uint32_t dst, const CUtensorMap* m, int c0, int c1, int c2, uint32_t bar) {
  asm volatile("cp.async.bulk.tensor.3d.shared::cluster.global.mbarrier::complete_tx::bytes [%0], [%1, {%3, %4, %5}], [%2];"
               ::"r"(dst), "l"(m), "r"(bar), "r"(c0), "r"(c1), "r"(c2) : "memory");
}
__device__ __forceinline__ void l2pf(const void* p, uint32_t bytes) { asm volatile("cp.async.bulk.prefetch.L2.global [%0], %1;" ::"l"(p), "r"(bytes) : "memory"); }
__device__ __forceinline__ void wg_fence() { asm volatile("wgmma.fence.sync.aligned;" ::: "memory"); }
__device__ __forceinline__ void wg_commit() { asm volatile("wgmma.commit_group.sync.aligned;" ::: "memory"); }
template <int N> __device__ __forceinline__ void wg_wait() { asm volatile("wgmma.wait_group.sync.aligned %0;" ::"n"(N) : "memory"); }
template <int N> __device__ __forceinline__ void regfence(float (&d)[N]) {
#pragma unroll
  for (int i = 0; i < N; i++) asm volatile("" : "+f"(d[i])::"memory");
}
__device__ __forceinline__ void bar_cons() { asm volatile("bar.sync 1, 256;" ::: "memory"); }
__device__ __forceinline__ void bar_ln() { asm volatile("bar.sync 2, 224;" ::: "memory"); }
__device__ __forceinline__ void fence_async() { asm volatile("fence.proxy.async.shared::cta;" ::: "memory"); }
struct Desc { uint32_t lo, hi; };
__device__ __forceinline__ Desc mkdesc(uint32_t base16, uint32_t off, uint32_t lbo, uint32_t sbo, uint32_t swz) {
  return Desc{base16 + ((off >> 4) | ((lbo >> 4) << 16)), (sbo >> 4) | (swz << 30)};
}
__device__ __forceinline__ uint4 ldll(const uint4* p) {
  uint4 v; asm volatile("ld.relaxed.gpu.global.v4.u32 {%0,%1,%2,%3}, [%4];" : "=r"(v.x), "=r"(v.y), "=r"(v.z), "=r"(v.w) : "l"(p) : "memory"); return v;
}
__device__ __forceinline__ uint2 ldll2(const uint2* p) {
  uint2 v; asm volatile("ld.relaxed.gpu.global.v2.u32 {%0,%1}, [%2];" : "=r"(v.x), "=r"(v.y) : "l"(p) : "memory"); return v;
}
__device__ __forceinline__ void stll(uint4* p, uint32_t x, uint32_t y, uint32_t z, uint32_t w) {
  asm volatile("st.relaxed.gpu.global.v4.u32 [%0], {%1,%2,%3,%4};" ::"l"(p), "r"(x), "r"(y), "r"(z), "r"(w) : "memory");
}
__device__ __forceinline__ void stll2(void* p, uint32_t x, uint32_t y) {
  asm volatile("st.relaxed.gpu.global.v2.u32 [%0], {%1,%2};" ::"l"(p), "r"(x), "r"(y) : "memory");
}
__device__ __forceinline__ uint32_t tg(uint32_t w, uint32_t tag) { return (w & ~1u) | tag; }
__device__ __forceinline__ uint32_t pack(float lo, float hi) {
  uint32_t r; asm("cvt.rn.bf16x2.f32 %0, %1, %2;" : "=r"(r) : "f"(hi), "f"(lo)); return r;
}
__device__ __forceinline__ float blo(uint32_t w) { return __uint_as_float(w << 16); }
__device__ __forceinline__ float bhi(uint32_t w) { return __uint_as_float(w & 0xffff0000u); }
__device__ __forceinline__ float ex2(float x) { float r; asm("ex2.approx.ftz.f32 %0, %1;" : "=f"(r) : "f"(x)); return r; }
__device__ __forceinline__ float rcp(float x) { float r; asm("rcp.approx.ftz.f32 %0, %1;" : "=f"(r) : "f"(x)); return r; }
__device__ __forceinline__ float qsum(float v) { v += __shfl_xor_sync(~0u, v, 1); v += __shfl_xor_sync(~0u, v, 2); return v; }
__device__ __forceinline__ void sts32(uint32_t a, uint32_t v) { asm volatile("st.shared.u32 [%0], %1;" ::"r"(a), "r"(v) : "memory"); }
__device__ __forceinline__ void sts16(uint32_t a, uint32_t v) { asm volatile("st.shared.u16 [%0], %1;" ::"r"(a), "h"((uint16_t)v) : "memory"); }
__device__ __forceinline__ void sts128(uint32_t a, uint32_t x, uint32_t y, uint32_t z, uint32_t w) {
  asm volatile("st.shared.v4.u32 [%0], {%1,%2,%3,%4};" ::"r"(a), "r"(x), "r"(y), "r"(z), "r"(w) : "memory");
}
__device__ __forceinline__ uint32_t sw128(int row, int col) { return row * 128 + ((((col >> 3) ^ row) & 7) << 4) + (col & 7) * 2; }

__device__ __forceinline__ void wgmma_rs56(float (&d)[28], const uint32_t a0, const uint32_t a1, const uint32_t a2, const uint32_t a3, Desc db, int sd) {
  asm volatile("{.reg .pred p; .reg .b64 da, db; setp.ne.b32 p, %33, 0; mov.b64 db, {%32, %34};\n wgmma.mma_async.sync.aligned.m64n56k16.f32.bf16.bf16 {%0,%1,%2,%3,%4,%5,%6,%7,%8,%9,%10,%11,%12,%13,%14,%15,%16,%17,%18,%19,%20,%21,%22,%23,%24,%25,%26,%27}, {%28,%29,%30,%31}, db, p, 1, 1, 1;}"
   : "+f"(d[0]),"+f"(d[1]),"+f"(d[2]),"+f"(d[3]),"+f"(d[4]),"+f"(d[5]),"+f"(d[6]),"+f"(d[7]),"+f"(d[8]),"+f"(d[9]),"+f"(d[10]),"+f"(d[11]),"+f"(d[12]),"+f"(d[13]),"+f"(d[14]),"+f"(d[15]),"+f"(d[16]),"+f"(d[17]),"+f"(d[18]),"+f"(d[19]),"+f"(d[20]),"+f"(d[21]),"+f"(d[22]),"+f"(d[23]),"+f"(d[24]),"+f"(d[25]),"+f"(d[26]),"+f"(d[27])
   : "r"(a0),"r"(a1),"r"(a2),"r"(a3),"r"(db.lo),"r"(sd),"r"(db.hi));
}
__device__ __forceinline__ void wgmma_rs64(float (&d)[32], const uint32_t a0, const uint32_t a1, const uint32_t a2, const uint32_t a3, Desc db, int sd) {
  asm volatile("{.reg .pred p; .reg .b64 da, db; setp.ne.b32 p, %37, 0; mov.b64 db, {%36, %38};\n wgmma.mma_async.sync.aligned.m64n64k16.f32.bf16.bf16 {%0,%1,%2,%3,%4,%5,%6,%7,%8,%9,%10,%11,%12,%13,%14,%15,%16,%17,%18,%19,%20,%21,%22,%23,%24,%25,%26,%27,%28,%29,%30,%31}, {%32,%33,%34,%35}, db, p, 1, 1, 1;}"
   : "+f"(d[0]),"+f"(d[1]),"+f"(d[2]),"+f"(d[3]),"+f"(d[4]),"+f"(d[5]),"+f"(d[6]),"+f"(d[7]),"+f"(d[8]),"+f"(d[9]),"+f"(d[10]),"+f"(d[11]),"+f"(d[12]),"+f"(d[13]),"+f"(d[14]),"+f"(d[15]),"+f"(d[16]),"+f"(d[17]),"+f"(d[18]),"+f"(d[19]),"+f"(d[20]),"+f"(d[21]),"+f"(d[22]),"+f"(d[23]),"+f"(d[24]),"+f"(d[25]),"+f"(d[26]),"+f"(d[27]),"+f"(d[28]),"+f"(d[29]),"+f"(d[30]),"+f"(d[31])
   : "r"(a0),"r"(a1),"r"(a2),"r"(a3),"r"(db.lo),"r"(sd),"r"(db.hi));
}
__device__ __forceinline__ void wgmma_rs224(float (&d)[112], const uint32_t a0, const uint32_t a1, const uint32_t a2, const uint32_t a3, Desc db, int sd) {
  asm volatile("{.reg .pred p; .reg .b64 da, db; setp.ne.b32 p, %117, 0; mov.b64 db, {%116, %118};\n wgmma.mma_async.sync.aligned.m64n224k16.f32.bf16.bf16 {%0,%1,%2,%3,%4,%5,%6,%7,%8,%9,%10,%11,%12,%13,%14,%15,%16,%17,%18,%19,%20,%21,%22,%23,%24,%25,%26,%27,%28,%29,%30,%31,%32,%33,%34,%35,%36,%37,%38,%39,%40,%41,%42,%43,%44,%45,%46,%47,%48,%49,%50,%51,%52,%53,%54,%55,%56,%57,%58,%59,%60,%61,%62,%63,%64,%65,%66,%67,%68,%69,%70,%71,%72,%73,%74,%75,%76,%77,%78,%79,%80,%81,%82,%83,%84,%85,%86,%87,%88,%89,%90,%91,%92,%93,%94,%95,%96,%97,%98,%99,%100,%101,%102,%103,%104,%105,%106,%107,%108,%109,%110,%111}, {%112,%113,%114,%115}, db, p, 1, 1, 1;}"
   : "+f"(d[0]),"+f"(d[1]),"+f"(d[2]),"+f"(d[3]),"+f"(d[4]),"+f"(d[5]),"+f"(d[6]),"+f"(d[7]),"+f"(d[8]),"+f"(d[9]),"+f"(d[10]),"+f"(d[11]),"+f"(d[12]),"+f"(d[13]),"+f"(d[14]),"+f"(d[15]),"+f"(d[16]),"+f"(d[17]),"+f"(d[18]),"+f"(d[19]),"+f"(d[20]),"+f"(d[21]),"+f"(d[22]),"+f"(d[23]),"+f"(d[24]),"+f"(d[25]),"+f"(d[26]),"+f"(d[27]),"+f"(d[28]),"+f"(d[29]),"+f"(d[30]),"+f"(d[31]),"+f"(d[32]),"+f"(d[33]),"+f"(d[34]),"+f"(d[35]),"+f"(d[36]),"+f"(d[37]),"+f"(d[38]),"+f"(d[39]),"+f"(d[40]),"+f"(d[41]),"+f"(d[42]),"+f"(d[43]),"+f"(d[44]),"+f"(d[45]),"+f"(d[46]),"+f"(d[47]),"+f"(d[48]),"+f"(d[49]),"+f"(d[50]),"+f"(d[51]),"+f"(d[52]),"+f"(d[53]),"+f"(d[54]),"+f"(d[55]),"+f"(d[56]),"+f"(d[57]),"+f"(d[58]),"+f"(d[59]),"+f"(d[60]),"+f"(d[61]),"+f"(d[62]),"+f"(d[63]),"+f"(d[64]),"+f"(d[65]),"+f"(d[66]),"+f"(d[67]),"+f"(d[68]),"+f"(d[69]),"+f"(d[70]),"+f"(d[71]),"+f"(d[72]),"+f"(d[73]),"+f"(d[74]),"+f"(d[75]),"+f"(d[76]),"+f"(d[77]),"+f"(d[78]),"+f"(d[79]),"+f"(d[80]),"+f"(d[81]),"+f"(d[82]),"+f"(d[83]),"+f"(d[84]),"+f"(d[85]),"+f"(d[86]),"+f"(d[87]),"+f"(d[88]),"+f"(d[89]),"+f"(d[90]),"+f"(d[91]),"+f"(d[92]),"+f"(d[93]),"+f"(d[94]),"+f"(d[95]),"+f"(d[96]),"+f"(d[97]),"+f"(d[98]),"+f"(d[99]),"+f"(d[100]),"+f"(d[101]),"+f"(d[102]),"+f"(d[103]),"+f"(d[104]),"+f"(d[105]),"+f"(d[106]),"+f"(d[107]),"+f"(d[108]),"+f"(d[109]),"+f"(d[110]),"+f"(d[111])
   : "r"(a0),"r"(a1),"r"(a2),"r"(a3),"r"(db.lo),"r"(sd),"r"(db.hi));
}
__device__ __forceinline__ void wgmma_ss64(float (&d)[32], Desc da, Desc db, int sd) {
  asm volatile("{.reg .pred p; .reg .b64 da, db; setp.ne.b32 p, %34, 0; mov.b64 da, {%32, %35}; mov.b64 db, {%33, %35};\n wgmma.mma_async.sync.aligned.m64n64k16.f32.bf16.bf16 {%0,%1,%2,%3,%4,%5,%6,%7,%8,%9,%10,%11,%12,%13,%14,%15,%16,%17,%18,%19,%20,%21,%22,%23,%24,%25,%26,%27,%28,%29,%30,%31}, da, db, p, 1, 1, 1, 1;}"
   : "+f"(d[0]),"+f"(d[1]),"+f"(d[2]),"+f"(d[3]),"+f"(d[4]),"+f"(d[5]),"+f"(d[6]),"+f"(d[7]),"+f"(d[8]),"+f"(d[9]),"+f"(d[10]),"+f"(d[11]),"+f"(d[12]),"+f"(d[13]),"+f"(d[14]),"+f"(d[15]),"+f"(d[16]),"+f"(d[17]),"+f"(d[18]),"+f"(d[19]),"+f"(d[20]),"+f"(d[21]),"+f"(d[22]),"+f"(d[23]),"+f"(d[24]),"+f"(d[25]),"+f"(d[26]),"+f"(d[27]),"+f"(d[28]),"+f"(d[29]),"+f"(d[30]),"+f"(d[31])
   : "r"(da.lo),"r"(db.lo),"r"(sd),"r"(db.hi));
}

template <int S, int N, int T> __device__ __forceinline__ void ll_issue(uint4 (&v)[T], const uint4* p, int stride) {
#pragma unroll
  for (int i = S; i < S + N; i++) v[i] = ldll(p + i * stride);
}
template <int S, int N, bool TWO, int T> __device__ __forceinline__ void ll_check(uint4 (&v)[T], const uint4* p, int stride, uint32_t tag) {
#pragma unroll 1
  for (int it = 0; it < SPIN; it++) {
    uint32_t bad = 0;
#pragma unroll
    for (int i = S; i < S + N; i++) bad |= (v[i].x ^ tag) | (TWO ? (v[i].z ^ tag) : 0u);
    if (!__any_sync(~0u, bad & 1)) break;
    ll_issue<S, N>(v, p, stride);
  }
}
template <class F> __device__ __forceinline__ void hedgehog(const float (&d)[28], F sink) {
  const float L2E = 1.4426950408889634f;
#pragma unroll
  for (int r = 0; r < 2; r++)
#pragma unroll
    for (int h = 0; h < 2; h++) {
      float x[7];
#pragma unroll
      for (int p = 0; p < 6; p++) x[p] = d[h * 16 + (p >> 1) * 4 + (p & 1) + 2 * r] * L2E;
      x[6] = d[12 + h + 2 * r] * L2E;
      float mx = x[0], mn = x[0];
#pragma unroll
      for (int p = 1; p < 7; p++) { mx = fmaxf(mx, x[p]); mn = fminf(mn, x[p]); }
      mx = fmaxf(mx, __shfl_xor_sync(~0u, mx, 1)); mn = fminf(mn, __shfl_xor_sync(~0u, mn, 1));
      mx = fmaxf(mx, __shfl_xor_sync(~0u, mx, 2)); mn = fminf(mn, __shfl_xor_sync(~0u, mn, 2));
      float ep[7], en[7], sp = 0.f, sn = 0.f;
#pragma unroll
      for (int p = 0; p < 7; p++) { ep[p] = ex2(x[p] - mx); en[p] = ex2(mn - x[p]); sp += ep[p]; sn += en[p]; }
      sp = rcp(qsum(sp)); sn = rcp(qsum(sn));
#pragma unroll
      for (int p = 0; p < 7; p++) sink(r, h, p, pack(ep[p] * sp, en[p] * sn));
    }
}
__device__ __forceinline__ void phi_gemm(const float (&x)[28], float (&y)[28], uint32_t wphi) {
  uint32_t f[14];
#pragma unroll
  for (int j = 0; j < 14; j++) f[j] = pack(x[2 * j], x[2 * j + 1]);
  wg_fence();
#pragma unroll
  for (int ks = 0; ks < 3; ks++) wgmma_rs56(y, f[4 * ks], f[4 * ks + 1], f[4 * ks + 2], f[4 * ks + 3], mkdesc(wphi >> 4, ks * 2048, 1024, 1024, 1), ks);
  wgmma_rs56(y, f[12], f[13], 0u, 0u, mkdesc(wphi >> 4, 3 * 2048, 1024, 1024, 1), 1);
  wg_commit();
}
__device__ __forceinline__ void ln_publish(uint32_t (&xw)[4][4], float* sLN, int warp, int lane, uint4* fb, uint32_t tag) {
  const int g = lane >> 2;
  float s0 = 0.f, s1 = 0.f;
#pragma unroll
  for (int u = 0; u < 4; u++) {
    stll(fb + XR + u * 32, tg(xw[u][0], tag), xw[u][1], tg(xw[u][2], tag), xw[u][3]);
    s0 += blo(xw[u][0]) + bhi(xw[u][0]) + blo(xw[u][2]) + bhi(xw[u][2]);
    s1 += blo(xw[u][1]) + bhi(xw[u][1]) + blo(xw[u][3]) + bhi(xw[u][3]);
  }
  s0 = qsum(s0) * (1.f / 64); s1 = qsum(s1) * (1.f / 64);
  float v0 = 0.f, v1 = 0.f;
#pragma unroll
  for (int u = 0; u < 4; u++)
#pragma unroll
    for (int k = 0; k < 4; k += 2) {
      float a = blo(xw[u][k]) - s0, b = bhi(xw[u][k]) - s0, c2 = blo(xw[u][k + 1]) - s1, d2 = bhi(xw[u][k + 1]) - s1;
      v0 += a * a + b * b; v1 += c2 * c2 + d2 * d2;
    }
  v0 = qsum(v0); v1 = qsum(v1);
  if ((lane & 3) == 0) { sLN[warp * 16 + g] = s0; sLN[warp * 16 + g + 8] = s1; sLN[112 + warp * 16 + g] = v0; sLN[112 + warp * 16 + g + 8] = v1; }
  bar_ln();
  float m0 = 0.f, m1 = 0.f; v0 = 0.f; v1 = 0.f;
#pragma unroll
  for (int w = 0; w < 7; w++) { m0 += sLN[w * 16 + g]; m1 += sLN[w * 16 + g + 8]; }
  m0 *= (1.f / 7); m1 *= (1.f / 7);
#pragma unroll
  for (int w = 0; w < 7; w++) {
    float a = sLN[w * 16 + g] - m0, b = sLN[w * 16 + g + 8] - m1;
    v0 += sLN[112 + w * 16 + g] + 64.f * a * a; v1 += sLN[112 + w * 16 + g + 8] + 64.f * b * b;
  }
  const float r0 = rsqrtf(v0 * (1.f / 448) + 1e-5f), r1 = rsqrtf(v1 * (1.f / 448) + 1e-5f);
#pragma unroll
  for (int u = 0; u < 4; u++)
    stll(fb + XN + u * 32, tg(pack((blo(xw[u][0]) - m0) * r0, (bhi(xw[u][0]) - m0) * r0), tag), pack((blo(xw[u][1]) - m1) * r1, (bhi(xw[u][1]) - m1) * r1),
         pack((blo(xw[u][2]) - m0) * r0, (bhi(xw[u][2]) - m0) * r0), pack((blo(xw[u][3]) - m1) * r1, (bhi(xw[u][3]) - m1) * r1));
}

__global__ void __launch_bounds__(384, 1)
fused_kernel(const __grid_constant__ CUtensorMap mQKV, const __grid_constant__ CUtensorMap mWO, const __grid_constant__ CUtensorMap mW1,
             const __grid_constant__ CUtensorMap mW2, const __nv_bfloat16* __restrict__ x, const __nv_bfloat16* __restrict__ wphi,
             const __nv_bfloat16* __restrict__ wo, const __nv_bfloat16* __restrict__ w1, const __nv_bfloat16* __restrict__ b1,
             const __nv_bfloat16* __restrict__ w2, const __nv_bfloat16* __restrict__ b2, __nv_bfloat16* __restrict__ out) {
  extern __shared__ __align__(1024) uint8_t sm[];
  const uint32_t sb = s2u(sm);
  const int tid = threadIdx.x, warp = __shfl_sync(~0u, tid >> 5, 0), lane = tid & 31, t = blockIdx.x >> 3, c = blockIdx.x & 7;
  const uint32_t bfull = sb + OFF_BAR, bempty = bfull + 8 * NST;

  if (tid == 256) {
    for (int s = 0; s < NST; s++) { mbar_init(bfull + 8 * s, 1); mbar_init(bempty + 8 * s, 8); }
    asm volatile("fence.mbarrier_init.release.cluster;" ::: "memory");
    fence_async();
  }
  __syncthreads();
  if (warp >= 8) {
    asm volatile("setmaxnreg.dec.sync.aligned.u32 40;");
    auto issue = [&](int i, int s) {
      const uint32_t dst = sb + s * STAGE, bar = bfull + 8 * s;
      mbar_expect(bar, STAGE);
      if (i < 4) {
        tma2d(dst, &mQKV, 448 + 56 * c, 112 * i, bar); tma2d(dst + 7168, &mQKV, 480 + 56 * c, 112 * i, bar);
        tma2d(dst + 14336, &mQKV, 896 + 56 * c, 112 * i, bar); tma2d(dst + 21504, &mQKV, 928 + 56 * c, 112 * i, bar);
      } else if (i >= 8 && i < 15) {
        tma3d(dst, &mW1, 0, 64 * (i - 8), 7 * c, bar);
      } else {
        const CUtensorMap* m = i < 6 ? &mQKV : (i < 8 ? &mWO : &mW2);
        const int n0 = i < 8 ? 56 * c : 64 * (i - 15), k0 = i < 8 ? 224 * (i & 1) : 224 * c;
        tma2d(dst, m, n0, k0, bar); tma2d(dst + 7168, m, n0, k0 + 112, bar);
        tma2d(dst + 14336, m, n0 + 32, k0, bar); tma2d(dst + 21504, m, n0 + 32, k0 + 112, bar);
      }
    };
    if (tid == 256) {
      int s = 0; uint32_t ph = 1;
      for (int n = 0; n < 44; n++) {
        mbar_wait(bempty + 8 * s, ph);
        issue(n >= 22 ? n - 22 : n, s);
        if (++s == NST) { s = 0; ph ^= 1; }
      }
    } else if (warp == 9) {
      if (lane == 0) {
        l2pf((const uint8_t*)wo + blockIdx.x * 3136, 3136);
        l2pf((const uint8_t*)w1 + blockIdx.x * 12544, 12544);
        l2pf((const uint8_t*)w2 + blockIdx.x * 12544, 12544);
      }
      if (blockIdx.x < 112) {
        const uint2* wp = (const uint2*)(w1 + (size_t)(lane >> 2) * 1792 + blockIdx.x * 16 + (lane & 3) * 4);
        float s0 = 0.f, s1 = 0.f, s2 = 0.f, s3 = 0.f;
#pragma unroll 8
        for (int i = 0; i < 56; i++) { const uint2 v = __ldg(wp + i * 8 * 448); s0 += blo(v.x); s1 += bhi(v.x); s2 += blo(v.y); s3 += bhi(v.y); }
#pragma unroll 1
        for (int o = 4; o < 32; o <<= 1) { s0 += __shfl_xor_sync(~0u, s0, o); s1 += __shfl_xor_sync(~0u, s1, o); s2 += __shfl_xor_sync(~0u, s2, o); s3 += __shfl_xor_sync(~0u, s3, o); }
        if (lane < 4) stll(g_CS + blockIdx.x * 4 + lane, tg(__float_as_uint(s0), 1), __float_as_uint(s1), __float_as_uint(s2), __float_as_uint(s3));
      }
#pragma unroll 1
      for (int i = 0; i < 2; i++) {
        const int e = lane < 28 ? lane + 28 * i : 0;
        uint4 cv[1];
        ll_issue<0, 1>(cv, g_CS + 56 * c + e, 0); ll_check<0, 1, false>(cv, g_CS + 56 * c + e, 0, 1u);
        const uint2 bb = __ldg((const uint2*)(b1 + 224 * c + 4 * e));
        sts128(sb + OFF_CB + e * 32, cv[0].x, cv[0].y, bb.x << 16, bb.x & 0xffff0000u);
        sts128(sb + OFF_CB + e * 32 + 16, cv[0].z, cv[0].w, bb.y << 16, bb.y & 0xffff0000u);
      }
      asm volatile("bar.arrive 4, 288;" ::: "memory");
    } else if (warp >= 10) {
      const int h = warp - 10;
      uint32_t wv[13];
#pragma unroll
      for (int i = 0; i < 13; i++) { const int e = lane + 32 * i; wv[i] = e < 392 ? __ldg((const uint32_t*)wphi + (2 * c + h) * 392 + e) : 0u; }
#pragma unroll 1
      for (int i = 0; i < 8; i++) sts128(sb + OFF_WPHI + (h * 256 + i * 32 + lane) * 16, 0, 0, 0, 0);
#pragma unroll 1
      for (int i = 0; i < 4; i++) sts128(sb + OFF_PHIK + sw128(h * 128 + i * 32 + lane, 56), 0, 0, 0, 0);
      asm volatile("bar.sync 5, 64;" ::: "memory");
#pragma unroll
      for (int i = 0; i < 13; i++) {
        const int e = lane + 32 * i, d = e / 14, f2 = 2 * (e - 14 * d), k = 28 * h + d;
        if (e < 392) {
          if (f2 < 24) sts32(sb + OFF_WPHI + sw128(k, 32 * h + f2), wv[i]);
          else { sts16(sb + OFF_WPHI + sw128(k, 2 * f2 - 24 + h), wv[i]); sts16(sb + OFF_WPHI + sw128(k, 2 * f2 - 22 + h), wv[i] >> 16); }
        }
      }
      fence_async();
      asm volatile("bar.arrive 3, 320;" ::: "memory");
    }
  } else {
  asm volatile("setmaxnreg.inc.sync.aligned.u32 232;");

  const int wg = warp >> 2, g = lane >> 2, q = lane & 3, t128 = tid & 127;
  const int row0 = warp * 16 + g;
  uint4* const fm = g_F + ((t * 8 + warp) * 28) * 32 + lane;
  uint4* const fr = g_F + ((t * 8 + c) * 28 + 4 * warp) * 32 + lane;
  uint2* const fe = (uint2*)(fm + ((7 * c) >> 1) * 32) + (c & 1);
  uint2* const fo = (uint2*)(fm + ((7 * c + 1) >> 1) * 32) + ((c + 1) & 1);
#define SL(j, B) (((j) & 1 ? fo : fe) + ((j) >> 1) * 64 + 2 * (B))
  float* sLN = (float*)(sm + OFF_LN);
  const uint32_t sPK = sb + OFF_PHIK, sV = sb + OFF_V, sW = sb + OFF_WPHI;
  const size_t xoff = (size_t)(t * 128 + c * 16 + g) * 448 + warp * 64 + 2 * q;
  MARK(0);
  uint32_t xw[4][4];
  if (warp < 7) {
    const uint32_t* xp = (const uint32_t*)(x + xoff);
#pragma unroll
    for (int u = 0; u < 4; u++) { xw[u][0] = __ldg(xp + u * 8); xw[u][1] = __ldg(xp + u * 8 + 1792); xw[u][2] = __ldg(xp + u * 8 + 4); xw[u][3] = __ldg(xp + u * 8 + 1796); }
  }
  int cs = 0, rs = 0; uint32_t cph = 0;
  auto acquire = [&]() -> uint32_t { mbar_wait(bfull + 8 * cs, cph); const uint32_t a = (sb >> 4) + cs * (STAGE >> 4); if (++cs == NST) { cs = 0; cph ^= 1; } return a; };
  auto release = [&]() { if (lane == 0) mbar_arrive(bempty + 8 * rs); if (++rs == NST) rs = 0; };

#pragma unroll 1
  for (int L = 0; L < 2; L++) {
    const uint32_t tag = 1 - L;
    uint32_t phq[2][2][7];
    if (warp < 7) ln_publish(xw, sLN, warp, lane, fr, tag);
    MARK(1 + L * 19);
    {
      uint4 a[28];
      const uint4* pa = fm + XN;
      ll_issue<0, 1>(a, pa, 32); ll_check<0, 1, false>(a, pa, 32, tag); ll_issue<1, 27>(a, pa, 32);
      MARK(2 + L * 19);
      float ak[28], av[28], aq[28], pp[28];
#define KVSTAGE(i) { ll_check<7 * i, 7, false>(a, pa, 32, tag); const uint32_t st = acquire(); wg_fence(); \
      _Pragma("unroll") for (int ks = 0; ks < 7; ks++) { const uint4 f = a[7 * i + ks]; \
        wgmma_rs56(ak, f.x, f.y, f.z, f.w, mkdesc(st, ks * 1024, 7168, 512, 2), i | ks); \
        wgmma_rs56(av, f.x, f.y, f.z, f.w, mkdesc(st, 14336 + ks * 1024, 7168, 512, 2), i | ks); } \
      wg_commit(); if (i > 0) { wg_wait<1>(); release(); } }
      KVSTAGE(0) KVSTAGE(1) KVSTAGE(2) KVSTAGE(3)
      wg_wait<0>(); release(); regfence(ak); regfence(av);
      MARK(3 + L * 19);
      if (L == 0) asm volatile("bar.sync 3, 320;" ::: "memory");
      phi_gemm(ak, pp, sW);
#pragma unroll
      for (int j = 0; j < 7; j++) {
        const int n = 8 * j + 2 * q, n2 = n < 28 ? n : n + 4;
        sts32(sV + sw128(row0, n2), pack(av[4 * j], av[4 * j + 1])); sts32(sV + sw128(row0 + 8, n2), pack(av[4 * j + 2], av[4 * j + 3]));
      }
      { const int n2 = 28 + 2 * (q & 1) + 32 * (q >> 1); const uint32_t v = (q & 1) ? 0u : 0x3F80u; sts32(sV + sw128(row0, n2), v); sts32(sV + sw128(row0 + 8, n2), v); }
#pragma unroll
      for (int i = 0; i < 2; i++) {
        const uint32_t st = acquire(); wg_fence();
#pragma unroll
        for (int ks = 0; ks < 14; ks++) { const uint4 f = a[14 * i + ks]; wgmma_rs56(aq, f.x, f.y, f.z, f.w, mkdesc(st, ks * 1024, 14336, 512, 2), i | ks); }
        wg_commit();
      }
      wg_wait<2>(); regfence(pp);
      hedgehog(pp, [&](int r, int h, int p, uint32_t v) { sts32(sPK + h * 16384 + sw128(row0 + 8 * r, 8 * p + 2 * q), v); });
      fence_async();
      wg_wait<0>(); release(); release(); regfence(aq);
      bar_cons();
      MARK(4 + L * 19);
      float kv[32];
      wg_fence();
#pragma unroll
      for (int ks = 0; ks < 8; ks++) wgmma_ss64(kv, mkdesc((sPK + wg * 16384) >> 4, ks * 2048, 1024, 1024, 1), mkdesc(sV >> 4, ks * 2048, 1024, 1024, 1), ks);
      wg_commit();
      phi_gemm(aq, pp, sW);
      wg_wait<1>(); regfence(kv);
#pragma unroll
      for (int u = 0; u < 4; u++) {
        float e[4];
#pragma unroll
        for (int i = 0; i < 4; i++) e[i] = wg ? kv[16 + 4 * u + i] : kv[4 * u + i];
        stll(g_KVP + (c * 16 + t) * 1024 + wg * 512 + u * 128 + t128, tg(__float_as_uint(e[0]), tag), __float_as_uint(e[1]), __float_as_uint(e[2]), __float_as_uint(e[3]));
      }
      MARK(5 + L * 19);
      bar_cons();
#pragma unroll
      for (int i = 0; i < 4; i++) sts128(sV + (tid + i * 256) * 16, 0, 0, 0, 0);
      wg_wait<0>(); regfence(pp);
      hedgehog(pp, [&](int r, int h, int p, uint32_t v) { phq[r][h][p] = v; });
    }
    MARK(6 + L * 19);
    {
      uint4 k4[4];
      const uint4* pk = g_KVP + (c * 16 + 4 * q) * 1024 + 64 * t + (tid >> 2);
      ll_issue<0, 4>(k4, pk, 1024); ll_check<0, 4, false>(k4, pk, 1024, tag);
      float s0 = 0, s1 = 0, s2 = 0, s3 = 0;
#pragma unroll
      for (int i = 0; i < 4; i++) { s0 += __uint_as_float(k4[i].x); s1 += __uint_as_float(k4[i].y); s2 += __uint_as_float(k4[i].z); s3 += __uint_as_float(k4[i].w); }
      s0 = qsum(s0); s1 = qsum(s1); s2 = qsum(s2); s3 = qsum(s3);
      if (q == 0) stll2(g_KVR + c * 1024 + 64 * t + (tid >> 2), tg(pack(s0, s1), tag), pack(s2, s3));
      MARK(7 + L * 19);
      bar_cons();
      uint2 r[4];
      const uint2* pr = g_KVR + c * 1024 + wg * 512 + t128;
#pragma unroll 1
      for (int it = 0; it < SPIN; it++) {
        uint32_t bad = 0;
#pragma unroll
        for (int u = 0; u < 4; u++) { r[u] = ldll2(pr + u * 128); bad |= r[u].x ^ tag; }
        if (!__any_sync(~0u, bad & 1)) break;
      }
#pragma unroll
      for (int u = 0; u < 4; u++) {
        const int d = 8 * u + 2 * q;
        if (d < 28) { sts32(sV + sw128(row0, 28 * wg + d), r[u].x); sts32(sV + sw128(row0 + 8, 28 * wg + d), r[u].y); }
        else if (d == 28) {
#pragma unroll
          for (int j = 0; j < 4; j++) { sts16(sV + sw128(row0, 56 + 2 * j + wg), r[u].x); sts16(sV + sw128(row0 + 8, 56 + 2 * j + wg), r[u].y); }
        }
      }
      fence_async();
      bar_cons();
      MARK(8 + L * 19);
      float o[32];
      wg_fence();
#pragma unroll
      for (int ks = 0; ks < 8; ks++) {
        const int h = ks >> 2, p = 2 * (ks & 3);
        wgmma_rs64(o, phq[0][h][p], phq[1][h][p], p < 6 ? phq[0][h][p < 6 ? p + 1 : 0] : 0u, p < 6 ? phq[1][h][p < 6 ? p + 1 : 0] : 0u, mkdesc(sV >> 4, ks * 2048, 1024, 1024, 1), ks);
      }
      wg_commit(); wg_wait<0>(); regfence(o);
      const float iA0 = rcp(o[28] + 1e-6f), iB0 = rcp(o[29] + 1e-6f), iA1 = rcp(o[30] + 1e-6f), iB1 = rcp(o[31] + 1e-6f);
#pragma unroll
      for (int j = 0; j < 7; j++) {
        const bool hb = 8 * j + 2 * q >= 28; const float i0 = hb ? iB0 : iA0, i1 = hb ? iB1 : iA1;
        stll2(SL(j, OO), tg(pack(o[4 * j] * i0, o[4 * j + 1] * i0), tag), pack(o[4 * j + 2] * i1, o[4 * j + 3] * i1));
      }
    }
    MARK(9 + L * 19);
    {
      uint2 xr[7];
#pragma unroll 1
      for (int it = 0; it < SPIN; it++) {
        uint32_t bad = 0;
#pragma unroll
        for (int j = 0; j < 7; j++) { xr[j] = ldll2(SL(j, XR)); bad |= xr[j].x ^ tag; }
        if (!__any_sync(~0u, bad & 1)) break;
      }
      uint4 a[28];
      const uint4* pa = fm + OO;
      ll_issue<0, 28>(a, pa, 32);
      float y[28];
      uint32_t st;
#define WOSTEP(i) { ll_check<7 * i, 7, true>(a, pa, 32, tag); if (!(i & 1)) st = acquire(); wg_fence(); \
      _Pragma("unroll") for (int ks = 0; ks < 7; ks++) { const uint4 f = a[7 * i + ks]; \
        wgmma_rs56(y, f.x, f.y, f.z, f.w, mkdesc(st, ((i & 1) * 7 + ks) * 1024, 14336, 512, 2), i | ks); } wg_commit(); }
      WOSTEP(0) MARK(10 + L * 19); WOSTEP(1) WOSTEP(2) WOSTEP(3)
      wg_wait<0>(); release(); release(); regfence(y);
      MARK(11 + L * 19);
      float s0 = 0.f, s1 = 0.f;
#pragma unroll
      for (int j = 0; j < 7; j++) {
        const uint32_t w0 = tg(pack(blo(xr[j].x) + y[4 * j], bhi(xr[j].x) + y[4 * j + 1]), tag), w1_ = pack(blo(xr[j].y) + y[4 * j + 2], bhi(xr[j].y) + y[4 * j + 3]);
        stll2(SL(j, X1), w0, w1_);
        y[4 * j] = blo(w0); y[4 * j + 1] = bhi(w0); y[4 * j + 2] = blo(w1_); y[4 * j + 3] = bhi(w1_);
        s0 += y[4 * j] + y[4 * j + 1]; s1 += y[4 * j + 2] + y[4 * j + 3];
      }
      s0 = qsum(s0) * (1.f / 56); s1 = qsum(s1) * (1.f / 56);
      float v0 = 0.f, v1 = 0.f;
#pragma unroll
      for (int j = 0; j < 7; j++) {
        const float d0 = y[4 * j] - s0, d1 = y[4 * j + 1] - s0, d2 = y[4 * j + 2] - s1, d3 = y[4 * j + 3] - s1;
        v0 += d0 * d0 + d1 * d1; v1 += d2 * d2 + d3 * d3;
      }
      v0 = qsum(v0); v1 = qsum(v1);
      if (q == 0) stll(g_ST + ((t * 8 + warp) * 8 + c) * 8 + g, tg(__float_as_uint(s0), tag), __float_as_uint(v0), __float_as_uint(s1), __float_as_uint(v1));
    }
    MARK(12 + L * 19);
    uint32_t hf[56];
    {
      uint4 a[28];
      const uint4* pa = fm + X1;
      ll_issue<0, 16>(a, pa, 32);
      float y[112];
#define F1STAGE(i) { ll_check<4 * i, 4, true>(a, pa, 32, tag); const uint32_t st = acquire(); wg_fence(); \
      _Pragma("unroll") for (int ks = 0; ks < 4; ks++) { const uint4 f = a[4 * i + ks]; \
        wgmma_rs224(y, f.x, f.y, f.z, f.w, mkdesc(st, ks * 1024, 4096, 512, 2), i | ks); } \
      wg_commit(); if (i > 0) { wg_wait<1>(); release(); if (i < 4) ll_issue<(i < 4 ? 4 * i + 12 : 0), 4>(a, pa, 32); } }
      F1STAGE(0) MARK(13 + L * 19); F1STAGE(1) F1STAGE(2) F1STAGE(3) F1STAGE(4) F1STAGE(5)
      uint4 sv[2];
      const uint4* ps = g_ST + ((t * 8 + warp) * 8 + 2 * q) * 8 + g;
      ll_issue<0, 2>(sv, ps, 8);
      F1STAGE(6)
      ll_check<0, 2, false>(sv, ps, 8, tag);
      const float ma = __uint_as_float(sv[0].x), mb = __uint_as_float(sv[1].x), mc = __uint_as_float(sv[0].z), md = __uint_as_float(sv[1].z);
      const float m0 = qsum(ma + mb) * 0.125f, m1 = qsum(mc + md) * 0.125f;
      const float v0 = qsum(__uint_as_float(sv[0].y) + __uint_as_float(sv[1].y) + 56.f * ((ma - m0) * (ma - m0) + (mb - m0) * (mb - m0)));
      const float v1 = qsum(__uint_as_float(sv[0].w) + __uint_as_float(sv[1].w) + 56.f * ((mc - m1) * (mc - m1) + (md - m1) * (md - m1)));
      const float r0 = rsqrtf(v0 * (1.f / 448) + 1e-5f), r1 = rsqrtf(v1 * (1.f / 448) + 1e-5f);
      const float n0 = -m0 * r0, n1 = -m1 * r1;
      if (L == 0) asm volatile("bar.sync 4, 288;" ::: "memory");
      wg_wait<0>(); release(); regfence(y);
      MARK(14 + L * 19);
#pragma unroll
      for (int j = 0; j < 28; j++) {
        const float4 cb = *(const float4*)(sm + OFF_CB + (j * 4 + q) * 16);
        const float h0 = fmaxf(fmaf(y[4 * j], r0, fmaf(n0, cb.x, cb.z)), 0.f), h1 = fmaxf(fmaf(y[4 * j + 1], r0, fmaf(n0, cb.y, cb.w)), 0.f);
        const float h2 = fmaxf(fmaf(y[4 * j + 2], r1, fmaf(n1, cb.x, cb.z)), 0.f), h3 = fmaxf(fmaf(y[4 * j + 3], r1, fmaf(n1, cb.y, cb.w)), 0.f);
        hf[2 * j] = pack(h0 * h0, h1 * h1); hf[2 * j + 1] = pack(h2 * h2, h3 * h3);
      }
    }
    MARK(15 + L * 19);
    {
      float ya[32], yb[32];
      uint4* pp = g_P + ((t * 8 + warp) * 8 + c) * 28 * 32 + lane;
#define F2STORE(j, Y) { regfence(Y); _Pragma("unroll") for (int u = 0; u < 4; u++) \
      stll(pp + (4 * (j) + u) * 32, tg(pack(Y[8 * u], Y[8 * u + 1]), tag), pack(Y[8 * u + 2], Y[8 * u + 3]), pack(Y[8 * u + 4], Y[8 * u + 5]), pack(Y[8 * u + 6], Y[8 * u + 7])); }
#define F2PASS(j, Y, Z) { const uint32_t st = acquire(); wg_fence(); \
      _Pragma("unroll") for (int ks = 0; ks < 14; ks++) wgmma_rs64(Y, hf[4 * ks], hf[4 * ks + 1], hf[4 * ks + 2], hf[4 * ks + 3], mkdesc(st, ks * 1024, 14336, 512, 2), ks); \
      wg_commit(); if (j > 0) { wg_wait<1>(); release(); F2STORE(j - 1, Z) } }
      F2PASS(0, ya, yb)
#pragma unroll 1
      for (int j = 0; j < 3; j++) { F2PASS(1, yb, ya) F2PASS(2, ya, yb) pp += 256; }
      wg_wait<0>(); release(); F2STORE(0, ya)
    }
    MARK(16 + L * 19);
    if (warp < 7) {
      uint4 x1[4], p[32];
      uint32_t bw[8];
      ll_issue<0, 4>(x1, fr + X1, 32);
#pragma unroll
      for (int i = 0; i < 8; i++) bw[i] = __ldg((const uint32_t*)(b2 + warp * 64 + i * 8 + 2 * q));
      const uint4* pp = g_P + ((t * 8 + c) * 8 * 28 + 4 * warp) * 32 + lane;
      ll_issue<0, 8>(p, pp + 96, 896); ll_check<0, 8, false>(p, pp + 96, 896, tag);
      ll_issue<8, 8>(p, pp + 64 - 8 * 896, 896); ll_issue<16, 8>(p, pp + 32 - 16 * 896, 896); ll_issue<24, 8>(p, pp - 24 * 896, 896);
      MARK(17 + L * 19);
#define REDU(u, S) { if (S > 0) ll_check<S, 8, false>(p, pp + u * 32 - S * 896, 896, tag); \
      float e[8] = {blo(x1[u].x) + blo(bw[2 * u]), bhi(x1[u].x) + bhi(bw[2 * u]), blo(x1[u].y) + blo(bw[2 * u]), bhi(x1[u].y) + bhi(bw[2 * u]), \
                    blo(x1[u].z) + blo(bw[2 * u + 1]), bhi(x1[u].z) + bhi(bw[2 * u + 1]), blo(x1[u].w) + blo(bw[2 * u + 1]), bhi(x1[u].w) + bhi(bw[2 * u + 1])}; \
      _Pragma("unroll") for (int i = S; i < S + 8; i++) { e[0] += blo(p[i].x); e[1] += bhi(p[i].x); e[2] += blo(p[i].y); e[3] += bhi(p[i].y); \
        e[4] += blo(p[i].z); e[5] += bhi(p[i].z); e[6] += blo(p[i].w); e[7] += bhi(p[i].w); } \
      xw[u][0] = pack(e[0], e[1]); xw[u][1] = pack(e[2], e[3]); xw[u][2] = pack(e[4], e[5]); xw[u][3] = pack(e[6], e[7]); }
      REDU(3, 0) REDU(2, 8) REDU(1, 16) REDU(0, 24)
    }
    MARK(18 + L * 19);
  }
  if (warp < 7) {
    uint32_t* op = (uint32_t*)(out + xoff);
#pragma unroll
    for (int u = 0; u < 4; u++) { op[u * 8] = xw[u][0]; op[u * 8 + 1792] = xw[u][1]; op[u * 8 + 4] = xw[u][2]; op[u * 8 + 1796] = xw[u][3]; }
  } else if (blockIdx.x < 112 && lane < 4) stll(g_CS + blockIdx.x * 4 + lane, 0, 0, 0, 0);
  MARK(38);
  }
}

typedef CUresult (*EncFn)(CUtensorMap*, CUtensorMapDataType, cuuint32_t, void*, const cuuint64_t*, const cuuint64_t*, const cuuint32_t*, const cuuint32_t*,
                          CUtensorMapInterleave, CUtensorMapSwizzle, CUtensorMapL2promotion, CUtensorMapFloatOOBfill);

extern "C" void kernel_launch(void* const* d_in, const int* in_sizes, int n_in, void* d_out, int out_size) {
  static EncFn enc = nullptr;
  if (!enc) {
    void* fn = nullptr; cudaDriverEntryPointQueryResult qr;
    cudaGetDriverEntryPoint("cuTensorMapEncodeTiled", &fn, cudaEnableDefault, &qr);
    enc = (EncFn)fn;
    cudaFuncSetAttribute(fused_kernel, cudaFuncAttributeMaxDynamicSharedMemorySize, SMEM_BYTES);
  }
  CUtensorMap mQKV, mWO, mW1, mW2;
  const cuuint32_t es[3] = {1, 1, 1};
  auto enc2 = [&](CUtensorMap* m, void* p, cuuint64_t cols, cuuint64_t rows) {
    const cuuint64_t dims[2] = {cols, rows}, str[1] = {cols * 2}; const cuuint32_t box[2] = {32, 112};
    enc(m, CU_TENSOR_MAP_DATA_TYPE_BFLOAT16, 2, p, dims, str, box, es, CU_TENSOR_MAP_INTERLEAVE_NONE, CU_TENSOR_MAP_SWIZZLE_64B,
        CU_TENSOR_MAP_L2_PROMOTION_L2_128B, CU_TENSOR_MAP_FLOAT_OOB_FILL_NONE);
  };
  enc2(&mQKV, d_in[1], 1344, 448); enc2(&mWO, d_in[3], 448, 448); enc2(&mW2, d_in[7], 448, 1792);
  {
    const cuuint64_t dims[3] = {32, 448, 56}, str[2] = {3584, 64}; const cuuint32_t box[3] = {32, 64, 7};
    enc(&mW1, CU_TENSOR_MAP_DATA_TYPE_BFLOAT16, 3, d_in[5], dims, str, box, es, CU_TENSOR_MAP_INTERLEAVE_NONE, CU_TENSOR_MAP_SWIZZLE_64B,
        CU_TENSOR_MAP_L2_PROMOTION_L2_128B, CU_TENSOR_MAP_FLOAT_OOB_FILL_NONE);
  }
  typedef const __nv_bfloat16* BP;
  fused_kernel<<<128, 384, SMEM_BYTES>>>(mQKV, mWO, mW1, mW2, (BP)d_in[0], (BP)d_in[2], (BP)d_in[3], (BP)d_in[5], (BP)d_in[6], (BP)d_in[7], (BP)d_in[8],
                                         (__nv_bfloat16*)d_out);
}
```

```cpp
#include <cuda_runtime.h>
#include <cuda_bf16.h>
#include <cuda.h>
#include <stdint.h>

constexpr int NST = 6, STAGE = 28672;
constexpr int OFF_PHIK = NST * STAGE;
constexpr int OFF_V = OFF_PHIK + 32768;
constexpr int OFF_WPHI = OFF_V + 16384;
constexpr int OFF_CB = OFF_WPHI + 8192;
constexpr int OFF_LN = OFF_CB + 1792;
constexpr int OFF_BAR = OFF_LN + 896;
constexpr int SMEM_BYTES = OFF_BAR + 16 * NST;
constexpr int FR = 16 * 8 * 28 * 32;
constexpr int SPIN = 1 << 18;

__device__ uint4 g_F[4 * FR];
constexpr int XN = 0, XR = FR, OO = 2 * FR, X1 = 3 * FR;
__device__ uint4 g_P[8 * FR];
__device__ uint4 g_ST[16 * 8 * 8 * 8];
__device__ uint4 g_KVP[8 * 16 * 1024];
__device__ uint2 g_KVR[8 * 1024];
__device__ uint4 g_CS[448];
__device__ uint32_t g_H[16 * 8 * 8];
#define MARK(i)

__device__ __forceinline__ uint32_t s2u(const void* p) { return (uint32_t)__cvta_generic_to_shared(p); }
__device__ __forceinline__ void mbar_init(uint32_t b, uint32_t c) { asm volatile("mbarrier.init.shared::cta.b64 [%0], %1;" ::"r"(b), "r"(c)); }
__device__ __forceinline__ void mbar_expect(uint32_t b, uint32_t tx) { asm volatile("mbarrier.arrive.expect_tx.shared::cta.b64 _, [%0], %1;" ::"r"(b), "r"(tx) : "memory"); }
__device__ __forceinline__ void mbar_arrive(uint32_t b) { asm volatile("mbarrier.arrive.shared::cta.b64 _, [%0];" ::"r"(b) : "memory"); }
__device__ __forceinline__ void mbar_wait(uint32_t b, uint32_t ph) {
  uint32_t ok = 0;
#pragma unroll 1
  for (int it = 0; it < SPIN && !ok; it++)
    asm volatile("{.reg .pred p; mbarrier.try_wait.parity.shared::cta.b64 p,[%1],%2; selp.u32 %0,1,0,p;}" : "=r"(ok) : "r"(b), "r"(ph) : "memory");
}
__device__ __forceinline__ void tma2d(uint32_t dst, const CUtensorMap* m, int c0, int c1, uint32_t bar) {
  asm volatile("cp.async.bulk.tensor.2d.shared::cluster.global.mbarrier::complete_tx::bytes [%0], [%1, {%3, %4}], [%2];"
               ::"r"(dst), "l"(m), "r"(bar), "r"(c0), "r"(c1) : "memory");
}
__device__ __forceinline__ void tma3d(uint32_t dst, const CUtensorMap* m, int c0, int c1, int c2, uint32_t bar) {
  asm volatile("cp.async.bulk.tensor.3d.shared::cluster.global.mbarrier::complete_tx::bytes [%0], [%1, {%3, %4, %5}], [%2];"
               ::"r"(dst), "l"(m), "r"(bar), "r"(c0), "r"(c1), "r"(c2) : "memory");
}
__device__ __forceinline__ void l2pf(const void* p, uint32_t bytes) { asm volatile("cp.async.bulk.prefetch.L2.global [%0], %1;" ::"l"(p), "r"(bytes) : "memory"); }
__device__ __forceinline__ void wg_fence() { asm volatile("wgmma.fence.sync.aligned;" ::: "memory"); }
__device__ __forceinline__ void wg_commit() { asm volatile("wgmma.commit_group.sync.aligned;" ::: "memory"); }
template <int N> __device__ __forceinline__ void wg_wait() { asm volatile("wgmma.wait_group.sync.aligned %0;" ::"n"(N) : "memory"); }
template <int N> __device__ __forceinline__ void regfence(float (&d)[N]) {
#pragma unroll
  for (int i = 0; i < N; i++) asm volatile("" : "+f"(d[i])::"memory");
}
__device__ __forceinline__ void bar_cons() { asm volatile("bar.sync 1, 256;" ::: "memory"); }
__device__ __forceinline__ void bar_ln() { asm volatile("bar.sync 2, 224;" ::: "memory"); }
__device__ __forceinline__ void fence_async() { asm volatile("fence.proxy.async.shared::cta;" ::: "memory"); }
struct Desc { uint32_t lo, hi; };
__device__ __forceinline__ Desc mkdesc(uint32_t base16, uint32_t off, uint32_t lbo, uint32_t sbo, uint32_t swz) {
  return Desc{base16 + ((off >> 4) | ((lbo >> 4) << 16)), (sbo >> 4) | (swz << 30)};
}
__device__ __forceinline__ uint4 ldll(const uint4* p) {
  uint4 v; asm volatile("ld.relaxed.gpu.global.v4.u32 {%0,%1,%2,%3}, [%4];" : "=r"(v.x), "=r"(v.y), "=r"(v.z), "=r"(v.w) : "l"(p) : "memory"); return v;
}
__device__ __forceinline__ uint2 ldll2(const uint2* p) {
  uint2 v; asm volatile("ld.relaxed.gpu.global.v2.u32 {%0,%1}, [%2];" : "=r"(v.x), "=r"(v.y) : "l"(p) : "memory"); return v;
}
__device__ __forceinline__ void stll(uint4* p, uint32_t x, uint32_t y, uint32_t z, uint32_t w) {
  asm volatile("st.relaxed.gpu.global.v4.u32 [%0], {%1,%2,%3,%4};" ::"l"(p), "r"(x), "r"(y), "r"(z), "r"(w) : "memory");
}
__device__ __forceinline__ void stll2(void* p, uint32_t x, uint32_t y) {
  asm volatile("st.relaxed.gpu.global.v2.u32 [%0], {%1,%2};" ::"l"(p), "r"(x), "r"(y) : "memory");
}
__device__ __forceinline__ uint32_t tg(uint32_t w, uint32_t tag) { return (w & ~1u) | tag; }
__device__ __forceinline__ uint32_t pack(float lo, float hi) {
  uint32_t r; asm("cvt.rn.bf16x2.f32 %0, %1, %2;" : "=r"(r) : "f"(hi), "f"(lo)); return r;
}
__device__ __forceinline__ float blo(uint32_t w) { return __uint_as_float(w << 16); }
__device__ __forceinline__ float bhi(uint32_t w) { return __uint_as_float(w & 0xffff0000u); }
__device__ __forceinline__ float ex2(float x) { float r; asm("ex2.approx.ftz.f32 %0, %1;" : "=f"(r) : "f"(x)); return r; }
__device__ __forceinline__ float rcp(float x) { float r; asm("rcp.approx.ftz.f32 %0, %1;" : "=f"(r) : "f"(x)); return r; }
__device__ __forceinline__ float qsum(float v) { v += __shfl_xor_sync(~0u, v, 1); v += __shfl_xor_sync(~0u, v, 2); return v; }
__device__ __forceinline__ void sts32(uint32_t a, uint32_t v) { asm volatile("st.shared.u32 [%0], %1;" ::"r"(a), "r"(v) : "memory"); }
__device__ __forceinline__ void sts16(uint32_t a, uint32_t v) { asm volatile("st.shared.u16 [%0], %1;" ::"r"(a), "h"((uint16_t)v) : "memory"); }
__device__ __forceinline__ void sts128(uint32_t a, uint32_t x, uint32_t y, uint32_t z, uint32_t w) {
  asm volatile("st.shared.v4.u32 [%0], {%1,%2,%3,%4};" ::"r"(a), "r"(x), "r"(y), "r"(z), "r"(w) : "memory");
}
__device__ __forceinline__ uint32_t sw128(int row, int col) { return row * 128 + ((((col >> 3) ^ row) & 7) << 4) + (col & 7) * 2; }

__device__ __forceinline__ void wgmma_rs56(float (&d)[28], const uint32_t a0, const uint32_t a1, const uint32_t a2, const uint32_t a3, Desc db, int sd) {
  asm volatile("{.reg .pred p; .reg .b64 da, db; setp.ne.b32 p, %33, 0; mov.b64 db, {%32, %34};\n wgmma.mma_async.sync.aligned.m64n56k16.f32.bf16.bf16 {%0,%1,%2,%3,%4,%5,%6,%7,%8,%9,%10,%11,%12,%13,%14,%15,%16,%17,%18,%19,%20,%21,%22,%23,%24,%25,%26,%27}, {%28,%29,%30,%31}, db, p, 1, 1, 1;}"
   : "+f"(d[0]),"+f"(d[1]),"+f"(d[2]),"+f"(d[3]),"+f"(d[4]),"+f"(d[5]),"+f"(d[6]),"+f"(d[7]),"+f"(d[8]),"+f"(d[9]),"+f"(d[10]),"+f"(d[11]),"+f"(d[12]),"+f"(d[13]),"+f"(d[14]),"+f"(d[15]),"+f"(d[16]),"+f"(d[17]),"+f"(d[18]),"+f"(d[19]),"+f"(d[20]),"+f"(d[21]),"+f"(d[22]),"+f"(d[23]),"+f"(d[24]),"+f"(d[25]),"+f"(d[26]),"+f"(d[27])
   : "r"(a0),"r"(a1),"r"(a2),"r"(a3),"r"(db.lo),"r"(sd),"r"(db.hi));
}
__device__ __forceinline__ void wgmma_rs64(float (&d)[32], const uint32_t a0, const uint32_t a1, const uint32_t a2, const uint32_t a3, Desc db, int sd) {
  asm volatile("{.reg .pred p; .reg .b64 da, db; setp.ne.b32 p, %37, 0; mov.b64 db, {%36, %38};\n wgmma.mma_async.sync.aligned.m64n64k16.f32.bf16.bf16 {%0,%1,%2,%3,%4,%5,%6,%7,%8,%9,%10,%11,%12,%13,%14,%15,%16,%17,%18,%19,%20,%21,%22,%23,%24,%25,%26,%27,%28,%29,%30,%31}, {%32,%33,%34,%35}, db, p, 1, 1, 1;}"
   : "+f"(d[0]),"+f"(d[1]),"+f"(d[2]),"+f"(d[3]),"+f"(d[4]),"+f"(d[5]),"+f"(d[6]),"+f"(d[7]),"+f"(d[8]),"+f"(d[9]),"+f"(d[10]),"+f"(d[11]),"+f"(d[12]),"+f"(d[13]),"+f"(d[14]),"+f"(d[15]),"+f"(d[16]),"+f"(d[17]),"+f"(d[18]),"+f"(d[19]),"+f"(d[20]),"+f"(d[21]),"+f"(d[22]),"+f"(d[23]),"+f"(d[24]),"+f"(d[25]),"+f"(d[26]),"+f"(d[27]),"+f"(d[28]),"+f"(d[29]),"+f"(d[30]),"+f"(d[31])
   : "r"(a0),"r"(a1),"r"(a2),"r"(a3),"r"(db.lo),"r"(sd),"r"(db.hi));
}
__device__ __forceinline__ void wgmma_rs224(float (&d)[112], const uint32_t a0, const uint32_t a1, const uint32_t a2, const uint32_t a3, Desc db, int sd) {
  asm volatile("{.reg .pred p; .reg .b64 da, db; setp.ne.b32 p, %117, 0; mov.b64 db, {%116, %118};\n wgmma.mma_async.sync.aligned.m64n224k16.f32.bf16.bf16 {%0,%1,%2,%3,%4,%5,%6,%7,%8,%9,%10,%11,%12,%13,%14,%15,%16,%17,%18,%19,%20,%21,%22,%23,%24,%25,%26,%27,%28,%29,%30,%31,%32,%33,%34,%35,%36,%37,%38,%39,%40,%41,%42,%43,%44,%45,%46,%47,%48,%49,%50,%51,%52,%53,%54,%55,%56,%57,%58,%59,%60,%61,%62,%63,%64,%65,%66,%67,%68,%69,%70,%71,%72,%73,%74,%75,%76,%77,%78,%79,%80,%81,%82,%83,%84,%85,%86,%87,%88,%89,%90,%91,%92,%93,%94,%95,%96,%97,%98,%99,%100,%101,%102,%103,%104,%105,%106,%107,%108,%109,%110,%111}, {%112,%113,%114,%115}, db, p, 1, 1, 1;}"
   : "+f"(d[0]),"+f"(d[1]),"+f"(d[2]),"+f"(d[3]),"+f"(d[4]),"+f"(d[5]),"+f"(d[6]),"+f"(d[7]),"+f"(d[8]),"+f"(d[9]),"+f"(d[10]),"+f"(d[11]),"+f"(d[12]),"+f"(d[13]),"+f"(d[14]),"+f"(d[15]),"+f"(d[16]),"+f"(d[17]),"+f"(d[18]),"+f"(d[19]),"+f"(d[20]),"+f"(d[21]),"+f"(d[22]),"+f"(d[23]),"+f"(d[24]),"+f"(d[25]),"+f"(d[26]),"+f"(d[27]),"+f"(d[28]),"+f"(d[29]),"+f"(d[30]),"+f"(d[31]),"+f"(d[32]),"+f"(d[33]),"+f"(d[34]),"+f"(d[35]),"+f"(d[36]),"+f"(d[37]),"+f"(d[38]),"+f"(d[39]),"+f"(d[40]),"+f"(d[41]),"+f"(d[42]),"+f"(d[43]),"+f"(d[44]),"+f"(d[45]),"+f"(d[46]),"+f"(d[47]),"+f"(d[48]),"+f"(d[49]),"+f"(d[50]),"+f"(d[51]),"+f"(d[52]),"+f"(d[53]),"+f"(d[54]),"+f"(d[55]),"+f"(d[56]),"+f"(d[57]),"+f"(d[58]),"+f"(d[59]),"+f"(d[60]),"+f"(d[61]),"+f"(d[62]),"+f"(d[63]),"+f"(d[64]),"+f"(d[65]),"+f"(d[66]),"+f"(d[67]),"+f"(d[68]),"+f"(d[69]),"+f"(d[70]),"+f"(d[71]),"+f"(d[72]),"+f"(d[73]),"+f"(d[74]),"+f"(d[75]),"+f"(d[76]),"+f"(d[77]),"+f"(d[78]),"+f"(d[79]),"+f"(d[80]),"+f"(d[81]),"+f"(d[82]),"+f"(d[83]),"+f"(d[84]),"+f"(d[85]),"+f"(d[86]),"+f"(d[87]),"+f"(d[88]),"+f"(d[89]),"+f"(d[90]),"+f"(d[91]),"+f"(d[92]),"+f"(d[93]),"+f"(d[94]),"+f"(d[95]),"+f"(d[96]),"+f"(d[97]),"+f"(d[98]),"+f"(d[99]),"+f"(d[100]),"+f"(d[101]),"+f"(d[102]),"+f"(d[103]),"+f"(d[104]),"+f"(d[105]),"+f"(d[106]),"+f"(d[107]),"+f"(d[108]),"+f"(d[109]),"+f"(d[110]),"+f"(d[111])
   : "r"(a0),"r"(a1),"r"(a2),"r"(a3),"r"(db.lo),"r"(sd),"r"(db.hi));
}
__device__ __forceinline__ void wgmma_ss64(float (&d)[32], Desc da, Desc db, int sd) {
  asm volatile("{.reg .pred p; .reg .b64 da, db; setp.ne.b32 p, %34, 0; mov.b64 da, {%32, %35}; mov.b64 db, {%33, %35};\n wgmma.mma_async.sync.aligned.m64n64k16.f32.bf16.bf16 {%0,%1,%2,%3,%4,%5,%6,%7,%8,%9,%10,%11,%12,%13,%14,%15,%16,%17,%18,%19,%20,%21,%22,%23,%24,%25,%26,%27,%28,%29,%30,%31}, da, db, p, 1, 1, 1, 1;}"
   : "+f"(d[0]),"+f"(d[1]),"+f"(d[2]),"+f"(d[3]),"+f"(d[4]),"+f"(d[5]),"+f"(d[6]),"+f"(d[7]),"+f"(d[8]),"+f"(d[9]),"+f"(d[10]),"+f"(d[11]),"+f"(d[12]),"+f"(d[13]),"+f"(d[14]),"+f"(d[15]),"+f"(d[16]),"+f"(d[17]),"+f"(d[18]),"+f"(d[19]),"+f"(d[20]),"+f"(d[21]),"+f"(d[22]),"+f"(d[23]),"+f"(d[24]),"+f"(d[25]),"+f"(d[26]),"+f"(d[27]),"+f"(d[28]),"+f"(d[29]),"+f"(d[30]),"+f"(d[31])
   : "r"(da.lo),"r"(db.lo),"r"(sd),"r"(db.hi));
}

template <int S, int N, bool SPL = false, int T> __device__ __forceinline__ void ll_issue(uint4 (&v)[T], const uint4* p, int stride, const uint2* p2 = nullptr) {
#pragma unroll
  for (int i = S; i < S + N; i++) {
    if (SPL && i % 7 == 3) { const uint2 lo = ldll2(p2 + i * 64), hi = ldll2(p2 + i * 64 + 32); v[i] = make_uint4(lo.x, lo.y, hi.x, hi.y); }
    else v[i] = ldll(p + i * stride);
  }
}
template <int S, int N, bool SPL, int T> __device__ __forceinline__ void ll_check(uint4 (&v)[T], const uint4* p, int stride, uint32_t tag, const uint2* p2 = nullptr) {
#pragma unroll 1
  for (int it = 0; it < SPIN; it++) {
    uint32_t bad = 0;
#pragma unroll
    for (int i = S; i < S + N; i++) bad |= (v[i].x ^ tag) | ((SPL && i % 7 == 3) ? (v[i].z ^ tag) : 0u);
    if (!__any_sync(~0u, bad & 1)) break;
    ll_issue<S, N, SPL>(v, p, stride, p2);
  }
}
__device__ __forceinline__ void hint_post(uint32_t* p, uint32_t v, int lane) {
  if (lane == 0) asm volatile("st.relaxed.gpu.global.u32 [%0], %1;" ::"l"(p), "r"(v) : "memory");
}
__device__ __forceinline__ void hint_wait(const uint32_t* p, uint32_t s) {
#pragma unroll 1
  for (int it = 0; it < SPIN; it++) {
    uint32_t v; asm volatile("ld.relaxed.gpu.global.u32 %0, [%1];" : "=r"(v) : "l"(p) : "memory");
    if (__all_sync(~0u, v - s < 10u)) break;
  }
}
__device__ __forceinline__ void slice_store(uint4* pf, uint2* ph, const uint32_t (&w)[14], bool odd) {
#pragma unroll
  for (int u = 0; u < 3; u++)
    stll(pf + u * 32, odd ? w[4 * u + 2] : w[4 * u], odd ? w[4 * u + 3] : w[4 * u + 1], odd ? w[4 * u + 4] : w[4 * u + 2], odd ? w[4 * u + 5] : w[4 * u + 3]);
  stll2(ph, odd ? w[0] : w[12], odd ? w[1] : w[13]);
}
template <class F> __device__ __forceinline__ void hedgehog(const float (&d)[28], F sink) {
  const float L2E = 1.4426950408889634f;
#pragma unroll
  for (int r = 0; r < 2; r++)
#pragma unroll
    for (int h = 0; h < 2; h++) {
      float x[7];
#pragma unroll
      for (int p = 0; p < 6; p++) x[p] = d[h * 16 + (p >> 1) * 4 + (p & 1) + 2 * r] * L2E;
      x[6] = d[12 + h + 2 * r] * L2E;
      float mx = x[0], mn = x[0];
#pragma unroll
      for (int p = 1; p < 7; p++) { mx = fmaxf(mx, x[p]); mn = fminf(mn, x[p]); }
      mx = fmaxf(mx, __shfl_xor_sync(~0u, mx, 1)); mn = fminf(mn, __shfl_xor_sync(~0u, mn, 1));
      mx = fmaxf(mx, __shfl_xor_sync(~0u, mx, 2)); mn = fminf(mn, __shfl_xor_sync(~0u, mn, 2));
      float ep[7], en[7], sp = 0.f, sn = 0.f;
#pragma unroll
      for (int p = 0; p < 7; p++) { ep[p] = ex2(x[p] - mx); en[p] = ex2(mn - x[p]); sp += ep[p]; sn += en[p]; }
      sp = rcp(qsum(sp)); sn = rcp(qsum(sn));
#pragma unroll
      for (int p = 0; p < 7; p++) sink(r, h, p, pack(ep[p] * sp, en[p] * sn));
    }
}
__device__ __forceinline__ void phi_gemm(const float (&x)[28], float (&y)[28], uint32_t wphi) {
  uint32_t f[14];
#pragma unroll
  for (int j = 0; j < 14; j++) f[j] = pack(x[2 * j], x[2 * j + 1]);
  wg_fence();
#pragma unroll
  for (int ks = 0; ks < 3; ks++) wgmma_rs56(y, f[4 * ks], f[4 * ks + 1], f[4 * ks + 2], f[4 * ks + 3], mkdesc(wphi >> 4, ks * 2048, 1024, 1024, 1), ks);
  wgmma_rs56(y, f[12], f[13], 0u, 0u, mkdesc(wphi >> 4, 3 * 2048, 1024, 1024, 1), 1);
  wg_commit();
}
__device__ __forceinline__ void ln_publish(uint32_t (&xw)[4][4], float* sLN, int warp, int lane, uint4* fb, uint32_t tag) {
  const int g = lane >> 2;
  float s0 = 0.f, s1 = 0.f;
#pragma unroll
  for (int u = 0; u < 4; u++) {
    stll(fb + XR + u * 32, tg(xw[u][0], tag), xw[u][1], tg(xw[u][2], tag), xw[u][3]);
    s0 += blo(xw[u][0]) + bhi(xw[u][0]) + blo(xw[u][2]) + bhi(xw[u][2]);
    s1 += blo(xw[u][1]) + bhi(xw[u][1]) + blo(xw[u][3]) + bhi(xw[u][3]);
  }
  s0 = qsum(s0) * (1.f / 64); s1 = qsum(s1) * (1.f / 64);
  float v0 = 0.f, v1 = 0.f;
#pragma unroll
  for (int u = 0; u < 4; u++)
#pragma unroll
    for (int k = 0; k < 4; k += 2) {
      float a = blo(xw[u][k]) - s0, b = bhi(xw[u][k]) - s0, c2 = blo(xw[u][k + 1]) - s1, d2 = bhi(xw[u][k + 1]) - s1;
      v0 += a * a + b * b; v1 += c2 * c2 + d2 * d2;
    }
  v0 = qsum(v0); v1 = qsum(v1);
  if ((lane & 3) == 0) { sLN[warp * 16 + g] = s0; sLN[warp * 16 + g + 8] = s1; sLN[112 + warp * 16 + g] = v0; sLN[112 + warp * 16 + g + 8] = v1; }
  bar_ln();
  float m0 = 0.f, m1 = 0.f; v0 = 0.f; v1 = 0.f;
#pragma unroll
  for (int w = 0; w < 7; w++) { m0 += sLN[w * 16 + g]; m1 += sLN[w * 16 + g + 8]; }
  m0 *= (1.f / 7); m1 *= (1.f / 7);
#pragma unroll
  for (int w = 0; w < 7; w++) {
    float a = sLN[w * 16 + g] - m0, b = sLN[w * 16 + g + 8] - m1;
    v0 += sLN[112 + w * 16 + g] + 64.f * a * a; v1 += sLN[112 + w * 16 + g + 8] + 64.f * b * b;
  }
  const float r0 = rsqrtf(v0 * (1.f / 448) + 1e-5f), r1 = rsqrtf(v1 * (1.f / 448) + 1e-5f);
#pragma unroll
  for (int u = 0; u < 4; u++)
    stll(fb + XN + u * 32, tg(pack((blo(xw[u][0]) - m0) * r0, (bhi(xw[u][0]) - m0) * r0), tag), pack((blo(xw[u][1]) - m1) * r1, (bhi(xw[u][1]) - m1) * r1),
         pack((blo(xw[u][2]) - m0) * r0, (bhi(xw[u][2]) - m0) * r0), pack((blo(xw[u][3]) - m1) * r1, (bhi(xw[u][3]) - m1) * r1));
}

__global__ void __launch_bounds__(384, 1)
fused_kernel(const __grid_constant__ CUtensorMap mQKV, const __grid_constant__ CUtensorMap mWO, const __grid_constant__ CUtensorMap mW1,
             const __grid_constant__ CUtensorMap mW2, const __nv_bfloat16* __restrict__ x, const __nv_bfloat16* __restrict__ wphi,
             const __nv_bfloat16* __restrict__ wo, const __nv_bfloat16* __restrict__ w1, const __nv_bfloat16* __restrict__ b1,
             const __nv_bfloat16* __restrict__ w2, const __nv_bfloat16* __restrict__ b2, __nv_bfloat16* __restrict__ out) {
  extern __shared__ __align__(1024) uint8_t sm[];
  const uint32_t sb = s2u(sm);
  const int tid = threadIdx.x, warp = __shfl_sync(~0u, tid >> 5, 0), lane = tid & 31, t = blockIdx.x >> 3, c = blockIdx.x & 7;
  const uint32_t bfull = sb + OFF_BAR, bempty = bfull + 8 * NST;

  if (tid == 256) {
    for (int s = 0; s < NST; s++) { mbar_init(bfull + 8 * s, 1); mbar_init(bempty + 8 * s, 8); }
    asm volatile("fence.mbarrier_init.release.cluster;" ::: "memory");
    fence_async();
  }
  __syncthreads();
  if (warp >= 8) {
    asm volatile("setmaxnreg.dec.sync.aligned.u32 40;");
    auto issue = [&](int i, int s) {
      const uint32_t dst = sb + s * STAGE, bar = bfull + 8 * s;
      mbar_expect(bar, STAGE);
      if (i < 4) {
        tma2d(dst, &mQKV, 448 + 56 * c, 112 * i, bar); tma2d(dst + 7168, &mQKV, 480 + 56 * c, 112 * i, bar);
        tma2d(dst + 14336, &mQKV, 896 + 56 * c, 112 * i, bar); tma2d(dst + 21504, &mQKV, 928 + 56 * c, 112 * i, bar);
      } else if (i >= 8 && i < 15) {
        tma3d(dst, &mW1, 0, 64 * (i - 8), 7 * c, bar);
      } else {
        const CUtensorMap* m = i < 6 ? &mQKV : (i < 8 ? &mWO : &mW2);
        const int n0 = i < 8 ? 56 * c : 64 * (i - 15), k0 = i < 8 ? 224 * (i & 1) : 224 * c;
        tma2d(dst, m, n0, k0, bar); tma2d(dst + 7168, m, n0, k0 + 112, bar);
        tma2d(dst + 14336, m, n0 + 32, k0, bar); tma2d(dst + 21504, m, n0 + 32, k0 + 112, bar);
      }
    };
    if (tid == 256) {
      int s = 0; uint32_t ph = 1;
      for (int n = 0; n < 44; n++) {
        mbar_wait(bempty + 8 * s, ph);
        issue(n >= 22 ? n - 22 : n, s);
        if (++s == NST) { s = 0; ph ^= 1; }
      }
    } else if (warp == 9) {
      mbar_wait(bfull + 8 * 3, 0);
      if (lane == 0) {
        l2pf((const uint8_t*)wo + blockIdx.x * 3136, 3136);
        l2pf((const uint8_t*)w1 + blockIdx.x * 12544, 12544);
        l2pf((const uint8_t*)w2 + blockIdx.x * 12544, 12544);
      }
      if (blockIdx.x < 112) {
        const uint2* wp = (const uint2*)(w1 + (size_t)(lane >> 2) * 1792 + blockIdx.x * 16 + (lane & 3) * 4);
        float s0 = 0.f, s1 = 0.f, s2 = 0.f, s3 = 0.f;
#pragma unroll 8
        for (int i = 0; i < 56; i++) { const uint2 v = __ldg(wp + i * 8 * 448); s0 += blo(v.x); s1 += bhi(v.x); s2 += blo(v.y); s3 += bhi(v.y); }
#pragma unroll 1
        for (int o = 4; o < 32; o <<= 1) { s0 += __shfl_xor_sync(~0u, s0, o); s1 += __shfl_xor_sync(~0u, s1, o); s2 += __shfl_xor_sync(~0u, s2, o); s3 += __shfl_xor_sync(~0u, s3, o); }
        if (lane < 4) stll(g_CS + blockIdx.x * 4 + lane, tg(__float_as_uint(s0), 1), __float_as_uint(s1), __float_as_uint(s2), __float_as_uint(s3));
      }
#pragma unroll 1
      for (int i = 0; i < 2; i++) {
        const int e = lane < 28 ? lane + 28 * i : 0;
        uint4 cv[1];
        ll_issue<0, 1>(cv, g_CS + 56 * c + e, 0); ll_check<0, 1, false>(cv, g_CS + 56 * c + e, 0, 1u);
        const uint2 bb = __ldg((const uint2*)(b1 + 224 * c + 4 * e));
        sts128(sb + OFF_CB + e * 32, cv[0].x, cv[0].y, bb.x << 16, bb.x & 0xffff0000u);
        sts128(sb + OFF_CB + e * 32 + 16, cv[0].z, cv[0].w, bb.y << 16, bb.y & 0xffff0000u);
      }
      asm volatile("bar.arrive 4, 288;" ::: "memory");
    } else if (warp >= 10) {
      const int h = warp - 10;
      uint32_t wv[13];
#pragma unroll
      for (int i = 0; i < 13; i++) { const int e = lane + 32 * i; wv[i] = e < 392 ? __ldg((const uint32_t*)wphi + (2 * c + h) * 392 + e) : 0u; }
#pragma unroll 1
      for (int i = 0; i < 8; i++) sts128(sb + OFF_WPHI + (h * 256 + i * 32 + lane) * 16, 0, 0, 0, 0);
#pragma unroll 1
      for (int i = 0; i < 4; i++) sts128(sb + OFF_PHIK + sw128(h * 128 + i * 32 + lane, 56), 0, 0, 0, 0);
      asm volatile("bar.sync 5, 64;" ::: "memory");
#pragma unroll
      for (int i = 0; i < 13; i++) {
        const int e = lane + 32 * i, d = e / 14, f2 = 2 * (e - 14 * d), k = 28 * h + d;
        if (e < 392) {
          if (f2 < 24) sts32(sb + OFF_WPHI + sw128(k, 32 * h + f2), wv[i]);
          else { sts16(sb + OFF_WPHI + sw128(k, 2 * f2 - 24 + h), wv[i]); sts16(sb + OFF_WPHI + sw128(k, 2 * f2 - 22 + h), wv[i] >> 16); }
        }
      }
      fence_async();
      asm volatile("bar.arrive 3, 320;" ::: "memory");
    }
  } else {
  asm volatile("setmaxnreg.inc.sync.aligned.u32 232;");

  const int wg = warp >> 2, g = lane >> 2, q = lane & 3, t128 = tid & 127;
  const int row0 = warp * 16 + g;
  uint4* const fm = g_F + ((t * 8 + warp) * 28) * 32 + lane;
  uint4* const fr = g_F + ((t * 8 + c) * 28 + 4 * warp) * 32 + lane;
  uint2* const fe = (uint2*)(fm + ((7 * c) >> 1) * 32) + (c & 1);
  uint2* const fo = (uint2*)(fm + ((7 * c + 1) >> 1) * 32) + ((c + 1) & 1);
  uint4* const sf = fm + (7 * (c >> 1) + 4 * (c & 1)) * 32;
  uint2* const f2 = (uint2*)(fm - lane) + lane;
  uint2* const sh = f2 + (7 * (c >> 1) + 3) * 64 + 32 * (c & 1);
  uint32_t* const hme = g_H + (t * 8 + warp) * 8 + c;
  const uint32_t* const hrow = g_H + (t * 8 + warp) * 8 + (lane & 7);
#define SL(j, B) (((j) & 1 ? fo : fe) + ((j) >> 1) * 64 + 2 * (B))
  float* sLN = (float*)(sm + OFF_LN);
  const uint32_t sPK = sb + OFF_PHIK, sV = sb + OFF_V, sW = sb + OFF_WPHI;
  const size_t xoff = (size_t)(t * 128 + c * 16 + g) * 448 + warp * 64 + 2 * q;
  MARK(0);
  uint32_t xw[4][4];
  if (warp < 7) {
    const uint32_t* xp = (const uint32_t*)(x + xoff);
#pragma unroll
    for (int u = 0; u < 4; u++) { xw[u][0] = __ldg(xp + u * 8); xw[u][1] = __ldg(xp + u * 8 + 1792); xw[u][2] = __ldg(xp + u * 8 + 4); xw[u][3] = __ldg(xp + u * 8 + 1796); }
  }
  int cs = 0, rs = 0; uint32_t cph = 0;
  auto acquire = [&]() -> uint32_t { mbar_wait(bfull + 8 * cs, cph); const uint32_t a = (sb >> 4) + cs * (STAGE >> 4); if (++cs == NST) { cs = 0; cph ^= 1; } return a; };
  auto release = [&]() { if (lane == 0) mbar_arrive(bempty + 8 * rs); if (++rs == NST) rs = 0; };

#pragma unroll 1
  for (int L = 0; L < 2; L++) {
    const uint32_t tag = 1 - L;
    uint32_t phq[2][2][7];
    const uint32_t hs = 10 * L;
    if (warp < 7) { ln_publish(xw, sLN, warp, lane, fr, tag); hint_post(hme, hs + 1, lane); }
    MARK(1 + L * 19);
    {
      uint4 a[28];
      const uint4* pa = fm + XN;
      hint_wait(g_H + (t * 8 + (lane < 7 ? lane : 0)) * 8 + warp, hs + 1); ll_issue<0, 28>(a, pa, 32);
      MARK(2 + L * 19);
      float ak[28], av[28], aq[28], pp[28];
#define KVSTAGE(i) { ll_check<7 * i, 7, false>(a, pa, 32, tag); const uint32_t st = acquire(); wg_fence(); \
      _Pragma("unroll") for (int ks = 0; ks < 7; ks++) { const uint4 f = a[7 * i + ks]; \
        wgmma_rs56(ak, f.x, f.y, f.z, f.w, mkdesc(st, ks * 1024, 7168, 512, 2), i | ks); \
        wgmma_rs56(av, f.x, f.y, f.z, f.w, mkdesc(st, 14336 + ks * 1024, 7168, 512, 2), i | ks); } \
      wg_commit(); if (i > 0) { wg_wait<1>(); release(); } }
      KVSTAGE(0) KVSTAGE(1) KVSTAGE(2) KVSTAGE(3)
      wg_wait<0>(); release(); regfence(ak); regfence(av);
      MARK(3 + L * 19);
      if (L == 0) asm volatile("bar.sync 3, 320;" ::: "memory");
      phi_gemm(ak, pp, sW);
#pragma unroll
      for (int j = 0; j < 7; j++) {
        const int n = 8 * j + 2 * q, n2 = n < 28 ? n : n + 4;
        sts32(sV + sw128(row0, n2), pack(av[4 * j], av[4 * j + 1])); sts32(sV + sw128(row0 + 8, n2), pack(av[4 * j + 2], av[4 * j + 3]));
      }
      { const int n2 = 28 + 2 * (q & 1) + 32 * (q >> 1); const uint32_t v = (q & 1) ? 0u : 0x3F80u; sts32(sV + sw128(row0, n2), v); sts32(sV + sw128(row0 + 8, n2), v); }
#pragma unroll
      for (int i = 0; i < 2; i++) {
        const uint32_t st = acquire(); wg_fence();
#pragma unroll
        for (int ks = 0; ks < 14; ks++) { const uint4 f = a[14 * i + ks]; wgmma_rs56(aq, f.x, f.y, f.z, f.w, mkdesc(st, ks * 1024, 14336, 512, 2), i | ks); }
        wg_commit();
      }
      wg_wait<2>(); regfence(pp);
      hedgehog(pp, [&](int r, int h, int p, uint32_t v) { sts32(sPK + h * 16384 + sw128(row0 + 8 * r, 8 * p + 2 * q), v); });
      fence_async();
      wg_wait<0>(); release(); release(); regfence(aq);
      bar_cons();
      MARK(4 + L * 19);
      float kv[32];
      wg_fence();
#pragma unroll
      for (int ks = 0; ks < 8; ks++) wgmma_ss64(kv, mkdesc((sPK + wg * 16384) >> 4, ks * 2048, 1024, 1024, 1), mkdesc(sV >> 4, ks * 2048, 1024, 1024, 1), ks);
      wg_commit();
      phi_gemm(aq, pp, sW);
      wg_wait<1>(); regfence(kv);
#pragma unroll
      for (int u = 0; u < 4; u++) {
        float e[4];
#pragma unroll
        for (int i = 0; i < 4; i++) e[i] = wg ? kv[16 + 4 * u + i] : kv[4 * u + i];
        stll(g_KVP + (c * 16 + t) * 1024 + wg * 512 + u * 128 + t128, tg(__float_as_uint(e[0]), tag), __float_as_uint(e[1]), __float_as_uint(e[2]), __float_as_uint(e[3]));
      }
      MARK(5 + L * 19);
      bar_cons();
#pragma unroll
      for (int i = 0; i < 4; i++) sts128(sV + (tid + i * 256) * 16, 0, 0, 0, 0);
      wg_wait<0>(); regfence(pp);
      hedgehog(pp, [&](int r, int h, int p, uint32_t v) { phq[r][h][p] = v; });
    }
    MARK(6 + L * 19);
    {
      uint4 k4[4];
      const uint4* pk = g_KVP + (c * 16 + 4 * q) * 1024 + 64 * t + (tid >> 2);
      ll_issue<0, 4>(k4, pk, 1024); ll_check<0, 4, false>(k4, pk, 1024, tag);
      float s0 = 0, s1 = 0, s2 = 0, s3 = 0;
#pragma unroll
      for (int i = 0; i < 4; i++) { s0 += __uint_as_float(k4[i].x); s1 += __uint_as_float(k4[i].y); s2 += __uint_as_float(k4[i].z); s3 += __uint_as_float(k4[i].w); }
      s0 = qsum(s0); s1 = qsum(s1); s2 = qsum(s2); s3 = qsum(s3);
      if (q == 0) stll2(g_KVR + c * 1024 + 64 * t + (tid >> 2), tg(pack(s0, s1), tag), pack(s2, s3));
      MARK(7 + L * 19);
      bar_cons();
      uint2 r[4];
      const uint2* pr = g_KVR + c * 1024 + wg * 512 + t128;
#pragma unroll 1
      for (int it = 0; it < SPIN; it++) {
        uint32_t bad = 0;
#pragma unroll
        for (int u = 0; u < 4; u++) { r[u] = ldll2(pr + u * 128); bad |= r[u].x ^ tag; }
        if (!__any_sync(~0u, bad & 1)) break;
      }
#pragma unroll
      for (int u = 0; u < 4; u++) {
        const int d = 8 * u + 2 * q;
        if (d < 28) { sts32(sV + sw128(row0, 28 * wg + d), r[u].x); sts32(sV + sw128(row0 + 8, 28 * wg + d), r[u].y); }
        else if (d == 28) {
#pragma unroll
          for (int j = 0; j < 4; j++) { sts16(sV + sw128(row0, 56 + 2 * j + wg), r[u].x); sts16(sV + sw128(row0 + 8, 56 + 2 * j + wg), r[u].y); }
        }
      }
      fence_async();
      bar_cons();
      MARK(8 + L * 19);
      float o[32];
      wg_fence();
#pragma unroll
      for (int ks = 0; ks < 8; ks++) {
        const int h = ks >> 2, p = 2 * (ks & 3);
        wgmma_rs64(o, phq[0][h][p], phq[1][h][p], p < 6 ? phq[0][h][p < 6 ? p + 1 : 0] : 0u, p < 6 ? phq[1][h][p < 6 ? p + 1 : 0] : 0u, mkdesc(sV >> 4, ks * 2048, 1024, 1024, 1), ks);
      }
      wg_commit(); wg_wait<0>(); regfence(o);
      const float iA0 = rcp(o[28] + 1e-6f), iB0 = rcp(o[29] + 1e-6f), iA1 = rcp(o[30] + 1e-6f), iB1 = rcp(o[31] + 1e-6f);
      uint32_t w[14];
#pragma unroll
      for (int j = 0; j < 7; j++) {
        const bool hb = 8 * j + 2 * q >= 28; const float i0 = hb ? iB0 : iA0, i1 = hb ? iB1 : iA1;
        w[2 * j] = pack(o[4 * j] * i0, o[4 * j + 1] * i0); w[2 * j + 1] = pack(o[4 * j + 2] * i1, o[4 * j + 3] * i1);
        if (j == 0 || ((j ^ c) & 1) == 0) w[2 * j] = tg(w[2 * j], tag);
      }
      slice_store(sf + OO, sh + 2 * OO, w, c & 1);
      hint_post(hme, hs + 2, lane);
    }
    MARK(9 + L * 19);
    {
      uint2 xr[7];
#pragma unroll 1
      for (int it = 0; it < SPIN; it++) {
        uint32_t bad = 0;
#pragma unroll
        for (int j = 0; j < 7; j++) { xr[j] = ldll2(SL(j, XR)); bad |= xr[j].x ^ tag; }
        if (!__any_sync(~0u, bad & 1)) break;
      }
      uint4 a[28];
      const uint4* pa = fm + OO;
      hint_wait(hrow, hs + 2);
      ll_issue<0, 28, true>(a, pa, 32, f2 + 2 * OO);
      float y[28];
      uint32_t st;
#define WOSTEP(i) { ll_check<7 * i, 7, true>(a, pa, 32, tag, f2 + 2 * OO); if (!(i & 1)) st = acquire(); wg_fence(); \
      _Pragma("unroll") for (int ks = 0; ks < 7; ks++) { const uint4 f = a[7 * i + ks]; \
        wgmma_rs56(y, f.x, f.y, f.z, f.w, mkdesc(st, ((i & 1) * 7 + ks) * 1024, 14336, 512, 2), i | ks); } wg_commit(); }
      WOSTEP(0) MARK(10 + L * 19); WOSTEP(1) WOSTEP(2) WOSTEP(3)
      wg_wait<0>(); release(); release(); regfence(y);
      MARK(11 + L * 19);
      float s0 = 0.f, s1 = 0.f;
      uint32_t w[14];
#pragma unroll
      for (int j = 0; j < 7; j++) {
        w[2 * j] = pack(blo(xr[j].x) + y[4 * j], bhi(xr[j].x) + y[4 * j + 1]); w[2 * j + 1] = pack(blo(xr[j].y) + y[4 * j + 2], bhi(xr[j].y) + y[4 * j + 3]);
        if (j == 0 || ((j ^ c) & 1) == 0) w[2 * j] = tg(w[2 * j], tag);
      }
      slice_store(sf + X1, sh + 2 * X1, w, c & 1);
      hint_post(hme, hs + 3, lane);
#pragma unroll
      for (int j = 0; j < 7; j++) {
        y[4 * j] = blo(w[2 * j]); y[4 * j + 1] = bhi(w[2 * j]); y[4 * j + 2] = blo(w[2 * j + 1]); y[4 * j + 3] = bhi(w[2 * j + 1]);
        s0 += y[4 * j] + y[4 * j + 1]; s1 += y[4 * j + 2] + y[4 * j + 3];
      }
      s0 = qsum(s0) * (1.f / 56); s1 = qsum(s1) * (1.f / 56);
      float v0 = 0.f, v1 = 0.f;
#pragma unroll
      for (int j = 0; j < 7; j++) {
        const float d0 = y[4 * j] - s0, d1 = y[4 * j + 1] - s0, d2 = y[4 * j + 2] - s1, d3 = y[4 * j + 3] - s1;
        v0 += d0 * d0 + d1 * d1; v1 += d2 * d2 + d3 * d3;
      }
      v0 = qsum(v0); v1 = qsum(v1);
      if (q == 0) stll(g_ST + ((t * 8 + warp) * 8 + c) * 8 + g, tg(__float_as_uint(s0), tag), __float_as_uint(v0), __float_as_uint(s1), __float_as_uint(v1));
    }
    MARK(12 + L * 19);
    uint32_t hf[56];
    {
      uint4 a[28];
      const uint4* pa = fm + X1;
      hint_wait(hrow, hs + 3);
      ll_issue<0, 16, true>(a, pa, 32, f2 + 2 * X1);
      float y[112];
#define F1STAGE(i) { ll_check<4 * i, 4, true>(a, pa, 32, tag, f2 + 2 * X1); const uint32_t st = acquire(); wg_fence(); \
      _Pragma("unroll") for (int ks = 0; ks < 4; ks++) { const uint4 f = a[4 * i + ks]; \
        wgmma_rs224(y, f.x, f.y, f.z, f.w, mkdesc(st, ks * 1024, 4096, 512, 2), i | ks); } \
      wg_commit(); if (i > 0) { wg_wait<1>(); release(); if (i < 4) ll_issue<(i < 4 ? 4 * i + 12 : 0), 4, true>(a, pa, 32, f2 + 2 * X1); } }
      F1STAGE(0) MARK(13 + L * 19); F1STAGE(1) F1STAGE(2) F1STAGE(3) F1STAGE(4) F1STAGE(5)
      uint4 sv[2];
      const uint4* ps = g_ST + ((t * 8 + warp) * 8 + 2 * q) * 8 + g;
      ll_issue<0, 2>(sv, ps, 8);
      F1STAGE(6)
      ll_check<0, 2, false>(sv, ps, 8, tag);
      const float ma = __uint_as_float(sv[0].x), mb = __uint_as_float(sv[1].x), mc = __uint_as_float(sv[0].z), md = __uint_as_float(sv[1].z);
      const float m0 = qsum(ma + mb) * 0.125f, m1 = qsum(mc + md) * 0.125f;
      const float v0 = qsum(__uint_as_float(sv[0].y) + __uint_as_float(sv[1].y) + 56.f * ((ma - m0) * (ma - m0) + (mb - m0) * (mb - m0)));
      const float v1 = qsum(__uint_as_float(sv[0].w) + __uint_as_float(sv[1].w) + 56.f * ((mc - m1) * (mc - m1) + (md - m1) * (md - m1)));
      const float r0 = rsqrtf(v0 * (1.f / 448) + 1e-5f), r1 = rsqrtf(v1 * (1.f / 448) + 1e-5f);
      const float n0 = -m0 * r0, n1 = -m1 * r1;
      if (L == 0) asm volatile("bar.sync 4, 288;" ::: "memory");
      wg_wait<0>(); release(); regfence(y);
      MARK(14 + L * 19);
#pragma unroll
      for (int j = 0; j < 28; j++) {
        const float4 cb = *(const float4*)(sm + OFF_CB + (j * 4 + q) * 16);
        const float h0 = fmaxf(fmaf(y[4 * j], r0, fmaf(n0, cb.x, cb.z)), 0.f), h1 = fmaxf(fmaf(y[4 * j + 1], r0, fmaf(n0, cb.y, cb.w)), 0.f);
        const float h2 = fmaxf(fmaf(y[4 * j + 2], r1, fmaf(n1, cb.x, cb.z)), 0.f), h3 = fmaxf(fmaf(y[4 * j + 3], r1, fmaf(n1, cb.y, cb.w)), 0.f);
        hf[2 * j] = pack(h0 * h0, h1 * h1); hf[2 * j + 1] = pack(h2 * h2, h3 * h3);
      }
    }
    MARK(15 + L * 19);
    {
      float ya[32], yb[32];
      uint4* pp = g_P + ((t * 8 + warp) * 8 + c) * 28 * 32 + lane;
#define F2STORE(j, Y) { regfence(Y); _Pragma("unroll") for (int u = 0; u < 4; u++) \
      stll(pp + (4 * (j) + u) * 32, tg(pack(Y[8 * u], Y[8 * u + 1]), tag), pack(Y[8 * u + 2], Y[8 * u + 3]), pack(Y[8 * u + 4], Y[8 * u + 5]), pack(Y[8 * u + 6], Y[8 * u + 7])); hint_post(hme, hs + 4 + (j), lane); }
#define F2PASS(j, Y, Z) { const uint32_t st = acquire(); wg_fence(); \
      _Pragma("unroll") for (int ks = 0; ks < 14; ks++) wgmma_rs64(Y, hf[4 * ks], hf[4 * ks + 1], hf[4 * ks + 2], hf[4 * ks + 3], mkdesc(st, ks * 1024, 14336, 512, 2), ks); \
      wg_commit(); if (j > 0) { wg_wait<1>(); release(); F2STORE(j - 1, Z) } }
      F2PASS(0, ya, yb) F2PASS(1, yb, ya) F2PASS(2, ya, yb) F2PASS(3, yb, ya) F2PASS(4, ya, yb) F2PASS(5, yb, ya) F2PASS(6, ya, yb)
      wg_wait<0>(); release(); F2STORE(6, ya)
    }
    MARK(16 + L * 19);
    if (warp < 7) {
      uint4 x1[4], p[32];
      uint32_t bw[8];
#pragma unroll
      for (int u = 0; u < 4; u++) {
        const bool spl = (4 * warp + u) % 7 == 3;
        const uint2* p0 = (const uint2*)(fr + X1 + u * 32) - (spl ? lane : 0);
        const uint2 lo = ldll2(p0), hi = ldll2(p0 + (spl ? 32 : 1)); x1[u] = make_uint4(lo.x, lo.y, hi.x, hi.y);
      }
#pragma unroll
      for (int i = 0; i < 8; i++) bw[i] = __ldg((const uint32_t*)(b2 + warp * 64 + i * 8 + 2 * q));
      const uint4* pp = g_P + ((t * 8 + c) * 8 * 28 + 4 * warp) * 32 + lane;
      hint_wait(g_H + (t * 8 + c) * 8 + (lane & 7), hs + 4 + warp);
      ll_issue<0, 8>(p, pp + 96, 896);
      ll_issue<8, 8>(p, pp + 64 - 8 * 896, 896); ll_issue<16, 8>(p, pp + 32 - 16 * 896, 896); ll_issue<24, 8>(p, pp - 24 * 896, 896);
      MARK(17 + L * 19);
#define REDU(u, S) { ll_check<S, 8, false>(p, pp + u * 32 - S * 896, 896, tag); \
      float e[8] = {blo(x1[u].x) + blo(bw[2 * u]), bhi(x1[u].x) + bhi(bw[2 * u]), blo(x1[u].y) + blo(bw[2 * u]), bhi(x1[u].y) + bhi(bw[2 * u]), \
                    blo(x1[u].z) + blo(bw[2 * u + 1]), bhi(x1[u].z) + bhi(bw[2 * u + 1]), blo(x1[u].w) + blo(bw[2 * u + 1]), bhi(x1[u].w) + bhi(bw[2 * u + 1])}; \
      _Pragma("unroll") for (int i = S; i < S + 8; i++) { e[0] += blo(p[i].x); e[1] += bhi(p[i].x); e[2] += blo(p[i].y); e[3] += bhi(p[i].y); \
        e[4] += blo(p[i].z); e[5] += bhi(p[i].z); e[6] += blo(p[i].w); e[7] += bhi(p[i].w); } \
      xw[u][0] = pack(e[0], e[1]); xw[u][1] = pack(e[2], e[3]); xw[u][2] = pack(e[4], e[5]); xw[u][3] = pack(e[6], e[7]); }
      REDU(3, 0) REDU(2, 8) REDU(1, 16) REDU(0, 24)
    }
    MARK(18 + L * 19);
  }
  if (warp < 7) {
    uint32_t* op = (uint32_t*)(out + xoff);
#pragma unroll
    for (int u = 0; u < 4; u++) { op[u * 8] = xw[u][0]; op[u * 8 + 1792] = xw[u][1]; op[u * 8 + 4] = xw[u][2]; op[u * 8 + 1796] = xw[u][3]; }
  } else if (blockIdx.x < 112 && lane < 4) stll(g_CS + blockIdx.x * 4 + lane, 0, 0, 0, 0);
  MARK(38);
  }
}

typedef CUresult (*EncFn)(CUtensorMap*, CUtensorMapDataType, cuuint32_t, void*, const cuuint64_t*, const cuuint64_t*, const cuuint32_t*, const cuuint32_t*,
                          CUtensorMapInterleave, CUtensorMapSwizzle, CUtensorMapL2promotion, CUtensorMapFloatOOBfill);

extern "C" void kernel_launch(void* const* d_in, const int* in_sizes, int n_in, void* d_out, int out_size) {
  static EncFn enc = nullptr;
  if (!enc) {
    void* fn = nullptr; cudaDriverEntryPointQueryResult qr;
    cudaGetDriverEntryPoint("cuTensorMapEncodeTiled", &fn, cudaEnableDefault, &qr);
    enc = (EncFn)fn;
    cudaFuncSetAttribute(fused_kernel, cudaFuncAttributeMaxDynamicSharedMemorySize, SMEM_BYTES);
  }
  CUtensorMap mQKV, mWO, mW1, mW2;
  const cuuint32_t es[3] = {1, 1, 1};
  auto enc2 = [&](CUtensorMap* m, void* p, cuuint64_t cols, cuuint64_t rows) {
    const cuuint64_t dims[2] = {cols, rows}, str[1] = {cols * 2}; const cuuint32_t box[2] = {32, 112};
    enc(m, CU_TENSOR_MAP_DATA_TYPE_BFLOAT16, 2, p, dims, str, box, es, CU_TENSOR_MAP_INTERLEAVE_NONE, CU_TENSOR_MAP_SWIZZLE_64B,
        CU_TENSOR_MAP_L2_PROMOTION_L2_128B, CU_TENSOR_MAP_FLOAT_OOB_FILL_NONE);
  };
  enc2(&mQKV, d_in[1], 1344, 448); enc2(&mWO, d_in[3], 448, 448); enc2(&mW2, d_in[7], 448, 1792);
  {
    const cuuint64_t dims[3] = {32, 448, 56}, str[2] = {3584, 64}; const cuuint32_t box[3] = {32, 64, 7};
    enc(&mW1, CU_TENSOR_MAP_DATA_TYPE_BFLOAT16, 3, d_in[5], dims, str, box, es, CU_TENSOR_MAP_INTERLEAVE_NONE, CU_TENSOR_MAP_SWIZZLE_64B,
        CU_TENSOR_MAP_L2_PROMOTION_L2_128B, CU_TENSOR_MAP_FLOAT_OOB_FILL_NONE);
  }
  typedef const __nv_bfloat16* BP;
  fused_kernel<<<128, 384, SMEM_BYTES>>>(mQKV, mWO, mW1, mW2, (BP)d_in[0], (BP)d_in[2], (BP)d_in[3], (BP)d_in[5], (BP)d_in[6], (BP)d_in[7], (BP)d_in[8],
                                         (__nv_bfloat16*)d_out);
}
```

```cpp
#include <cuda_runtime.h>
#include <cuda_bf16.h>
#include <cuda.h>
#include <stdint.h>

constexpr int NST = 6, STAGE = 28672;
constexpr int OFF_PHIK = NST * STAGE;
constexpr int OFF_V = OFF_PHIK + 32768;
constexpr int OFF_WPHI = OFF_V + 16384;
constexpr int OFF_CB = OFF_WPHI + 8192;
constexpr int OFF_LN = OFF_CB + 1792;
constexpr int OFF_BAR = OFF_LN + 896;
constexpr int SMEM_BYTES = OFF_BAR + 16 * NST;
constexpr int FR = 16 * 8 * 28 * 32;
constexpr int SPIN = 1 << 18;

__device__ uint4 g_F[4 * FR];
constexpr int XN = 0, XR = FR, OO = 2 * FR, X1 = 3 * FR;
__device__ uint4 g_P[8 * FR];
__device__ uint4 g_ST[16 * 8 * 8 * 8];
__device__ uint4 g_KVP[8 * 16 * 1024];
__device__ uint2 g_KVR[8 * 1024];
__device__ uint4 g_CS[448];
__device__ uint32_t g_H[16 * 8 * 8];
#define MARK(i)

__device__ __forceinline__ uint32_t s2u(const void* p) { return (uint32_t)__cvta_generic_to_shared(p); }
__device__ __forceinline__ void mbar_init(uint32_t b, uint32_t c) { asm volatile("mbarrier.init.shared::cta.b64 [%0], %1;" ::"r"(b), "r"(c)); }
__device__ __forceinline__ void mbar_expect(uint32_t b, uint32_t tx) { asm volatile("mbarrier.arrive.expect_tx.shared::cta.b64 _, [%0], %1;" ::"r"(b), "r"(tx) : "memory"); }
__device__ __forceinline__ void mbar_arrive(uint32_t b) { asm volatile("mbarrier.arrive.shared::cta.b64 _, [%0];" ::"r"(b) : "memory"); }
__device__ __forceinline__ void mbar_wait(uint32_t b, uint32_t ph) {
  uint32_t ok = 0;
#pragma unroll 1
  for (int it = 0; it < SPIN && !ok; it++)
    asm volatile("{.reg .pred p; mbarrier.try_wait.parity.shared::cta.b64 p,[%1],%2; selp.u32 %0,1,0,p;}" : "=r"(ok) : "r"(b), "r"(ph) : "memory");
}
__device__ __forceinline__ void tma2d(uint32_t dst, const CUtensorMap* m, int c0, int c1, uint32_t bar) {
  asm volatile("cp.async.bulk.tensor.2d.shared::cluster.global.mbarrier::complete_tx::bytes [%0], [%1, {%3, %4}], [%2];"
               ::"r"(dst), "l"(m), "r"(bar), "r"(c0), "r"(c1) : "memory");
}
__device__ __forceinline__ void tma3d(uint32_t dst, const CUtensorMap* m, int c0, int c1, int c2, uint32_t bar) {
  asm volatile("cp.async.bulk.tensor.3d.shared::cluster.global.mbarrier::complete_tx::bytes [%0], [%1, {%3, %4, %5}], [%2];"
               ::"r"(dst), "l"(m), "r"(bar), "r"(c0), "r"(c1), "r"(c2) : "memory");
}
__device__ __forceinline__ void l2pf(const void* p, uint32_t bytes) { asm volatile("cp.async.bulk.prefetch.L2.global [%0], %1;" ::"l"(p), "r"(bytes) : "memory"); }
__device__ __forceinline__ void wg_fence() { asm volatile("wgmma.fence.sync.aligned;" ::: "memory"); }
__device__ __forceinline__ void wg_commit() { asm volatile("wgmma.commit_group.sync.aligned;" ::: "memory"); }
template <int N> __device__ __forceinline__ void wg_wait() { asm volatile("wgmma.wait_group.sync.aligned %0;" ::"n"(N) : "memory"); }
template <int N> __device__ __forceinline__ void regfence(float (&d)[N]) {
#pragma unroll
  for (int i = 0; i < N; i++) asm volatile("" : "+f"(d[i])::"memory");
}
__device__ __forceinline__ void bar_cons() { asm volatile("bar.sync 1, 256;" ::: "memory"); }
__device__ __forceinline__ void bar_ln() { asm volatile("bar.sync 2, 224;" ::: "memory"); }
__device__ __forceinline__ void fence_async() { asm volatile("fence.proxy.async.shared::cta;" ::: "memory"); }
struct Desc { uint32_t lo, hi; };
__device__ __forceinline__ Desc mkdesc(uint32_t base16, uint32_t off, uint32_t lbo, uint32_t sbo, uint32_t swz) {
  return Desc{base16 + ((off >> 4) | ((lbo >> 4) << 16)), (sbo >> 4) | (swz << 30)};
}
__device__ __forceinline__ uint4 ldll(const uint4* p) {
  uint4 v; asm volatile("ld.relaxed.gpu.global.v4.u32 {%0,%1,%2,%3}, [%4];" : "=r"(v.x), "=r"(v.y), "=r"(v.z), "=r"(v.w) : "l"(p) : "memory"); return v;
}
__device__ __forceinline__ uint2 ldll2(const uint2* p) {
  uint2 v; asm volatile("ld.relaxed.gpu.global.v2.u32 {%0,%1}, [%2];" : "=r"(v.x), "=r"(v.y) : "l"(p) : "memory"); return v;
}
__device__ __forceinline__ void stll(uint4* p, uint32_t x, uint32_t y, uint32_t z, uint32_t w) {
  asm volatile("st.relaxed.gpu.global.v4.u32 [%0], {%1,%2,%3,%4};" ::"l"(p), "r"(x), "r"(y), "r"(z), "r"(w) : "memory");
}
__device__ __forceinline__ void stll2(void* p, uint32_t x, uint32_t y) {
  asm volatile("st.relaxed.gpu.global.v2.u32 [%0], {%1,%2};" ::"l"(p), "r"(x), "r"(y) : "memory");
}
__device__ __forceinline__ int laneid() { int l; asm volatile("mov.u32 %0, %%laneid;" : "=r"(l)); return l; }
__device__ __forceinline__ uint32_t tg(uint32_t w, uint32_t tag) { return (w & ~1u) | tag; }
__device__ __forceinline__ uint32_t pack(float lo, float hi) {
  uint32_t r; asm("cvt.rn.bf16x2.f32 %0, %1, %2;" : "=r"(r) : "f"(hi), "f"(lo)); return r;
}
__device__ __forceinline__ float blo(uint32_t w) { return __uint_as_float(w << 16); }
__device__ __forceinline__ float bhi(uint32_t w) { return __uint_as_float(w & 0xffff0000u); }
__device__ __forceinline__ float ex2(float x) { float r; asm("ex2.approx.ftz.f32 %0, %1;" : "=f"(r) : "f"(x)); return r; }
__device__ __forceinline__ float rcp(float x) { float r; asm("rcp.approx.ftz.f32 %0, %1;" : "=f"(r) : "f"(x)); return r; }
__device__ __forceinline__ float qsum(float v) { v += __shfl_xor_sync(~0u, v, 1); v += __shfl_xor_sync(~0u, v, 2); return v; }
__device__ __forceinline__ void sts32(uint32_t a, uint32_t v) { asm volatile("st.shared.u32 [%0], %1;" ::"r"(a), "r"(v) : "memory"); }
__device__ __forceinline__ void sts16(uint32_t a, uint32_t v) { asm volatile("st.shared.u16 [%0], %1;" ::"r"(a), "h"((uint16_t)v) : "memory"); }
__device__ __forceinline__ void sts128(uint32_t a, uint32_t x, uint32_t y, uint32_t z, uint32_t w) {
  asm volatile("st.shared.v4.u32 [%0], {%1,%2,%3,%4};" ::"r"(a), "r"(x), "r"(y), "r"(z), "r"(w) : "memory");
}
__device__ __forceinline__ uint32_t sw128(int row, int col) { return row * 128 + ((((col >> 3) ^ row) & 7) << 4) + (col & 7) * 2; }

__device__ __forceinline__ void wgmma_rs56(float (&d)[28], const uint32_t a0, const uint32_t a1, const uint32_t a2, const uint32_t a3, Desc db, int sd) {
  asm volatile("{.reg .pred p; .reg .b64 da, db; setp.ne.b32 p, %33, 0; mov.b64 db, {%32, %34};\n wgmma.mma_async.sync.aligned.m64n56k16.f32.bf16.bf16 {%0,%1,%2,%3,%4,%5,%6,%7,%8,%9,%10,%11,%12,%13,%14,%15,%16,%17,%18,%19,%20,%21,%22,%23,%24,%25,%26,%27}, {%28,%29,%30,%31}, db, p, 1, 1, 1;}"
   : "+f"(d[0]),"+f"(d[1]),"+f"(d[2]),"+f"(d[3]),"+f"(d[4]),"+f"(d[5]),"+f"(d[6]),"+f"(d[7]),"+f"(d[8]),"+f"(d[9]),"+f"(d[10]),"+f"(d[11]),"+f"(d[12]),"+f"(d[13]),"+f"(d[14]),"+f"(d[15]),"+f"(d[16]),"+f"(d[17]),"+f"(d[18]),"+f"(d[19]),"+f"(d[20]),"+f"(d[21]),"+f"(d[22]),"+f"(d[23]),"+f"(d[24]),"+f"(d[25]),"+f"(d[26]),"+f"(d[27])
   : "r"(a0),"r"(a1),"r"(a2),"r"(a3),"r"(db.lo),"r"(sd),"r"(db.hi));
}
__device__ __forceinline__ void wgmma_rs64(float (&d)[32], const uint32_t a0, const uint32_t a1, const uint32_t a2, const uint32_t a3, Desc db, int sd) {
  asm volatile("{.reg .pred p; .reg .b64 da, db; setp.ne.b32 p, %37, 0; mov.b64 db, {%36, %38};\n wgmma.mma_async.sync.aligned.m64n64k16.f32.bf16.bf16 {%0,%1,%2,%3,%4,%5,%6,%7,%8,%9,%10,%11,%12,%13,%14,%15,%16,%17,%18,%19,%20,%21,%22,%23,%24,%25,%26,%27,%28,%29,%30,%31}, {%32,%33,%34,%35}, db, p, 1, 1, 1;}"
   : "+f"(d[0]),"+f"(d[1]),"+f"(d[2]),"+f"(d[3]),"+f"(d[4]),"+f"(d[5]),"+f"(d[6]),"+f"(d[7]),"+f"(d[8]),"+f"(d[9]),"+f"(d[10]),"+f"(d[11]),"+f"(d[12]),"+f"(d[13]),"+f"(d[14]),"+f"(d[15]),"+f"(d[16]),"+f"(d[17]),"+f"(d[18]),"+f"(d[19]),"+f"(d[20]),"+f"(d[21]),"+f"(d[22]),"+f"(d[23]),"+f"(d[24]),"+f"(d[25]),"+f"(d[26]),"+f"(d[27]),"+f"(d[28]),"+f"(d[29]),"+f"(d[30]),"+f"(d[31])
   : "r"(a0),"r"(a1),"r"(a2),"r"(a3),"r"(db.lo),"r"(sd),"r"(db.hi));
}
__device__ __forceinline__ void wgmma_rs224(float (&d)[112], const uint32_t a0, const uint32_t a1, const uint32_t a2, const uint32_t a3, Desc db, int sd) {
  asm volatile("{.reg .pred p; .reg .b64 da, db; setp.ne.b32 p, %117, 0; mov.b64 db, {%116, %118};\n wgmma.mma_async.sync.aligned.m64n224k16.f32.bf16.bf16 {%0,%1,%2,%3,%4,%5,%6,%7,%8,%9,%10,%11,%12,%13,%14,%15,%16,%17,%18,%19,%20,%21,%22,%23,%24,%25,%26,%27,%28,%29,%30,%31,%32,%33,%34,%35,%36,%37,%38,%39,%40,%41,%42,%43,%44,%45,%46,%47,%48,%49,%50,%51,%52,%53,%54,%55,%56,%57,%58,%59,%60,%61,%62,%63,%64,%65,%66,%67,%68,%69,%70,%71,%72,%73,%74,%75,%76,%77,%78,%79,%80,%81,%82,%83,%84,%85,%86,%87,%88,%89,%90,%91,%92,%93,%94,%95,%96,%97,%98,%99,%100,%101,%102,%103,%104,%105,%106,%107,%108,%109,%110,%111}, {%112,%113,%114,%115}, db, p, 1, 1, 1;}"
   : "+f"(d[0]),"+f"(d[1]),"+f"(d[2]),"+f"(d[3]),"+f"(d[4]),"+f"(d[5]),"+f"(d[6]),"+f"(d[7]),"+f"(d[8]),"+f"(d[9]),"+f"(d[10]),"+f"(d[11]),"+f"(d[12]),"+f"(d[13]),"+f"(d[14]),"+f"(d[15]),"+f"(d[16]),"+f"(d[17]),"+f"(d[18]),"+f"(d[19]),"+f"(d[20]),"+f"(d[21]),"+f"(d[22]),"+f"(d[23]),"+f"(d[24]),"+f"(d[25]),"+f"(d[26]),"+f"(d[27]),"+f"(d[28]),"+f"(d[29]),"+f"(d[30]),"+f"(d[31]),"+f"(d[32]),"+f"(d[33]),"+f"(d[34]),"+f"(d[35]),"+f"(d[36]),"+f"(d[37]),"+f"(d[38]),"+f"(d[39]),"+f"(d[40]),"+f"(d[41]),"+f"(d[42]),"+f"(d[43]),"+f"(d[44]),"+f"(d[45]),"+f"(d[46]),"+f"(d[47]),"+f"(d[48]),"+f"(d[49]),"+f"(d[50]),"+f"(d[51]),"+f"(d[52]),"+f"(d[53]),"+f"(d[54]),"+f"(d[55]),"+f"(d[56]),"+f"(d[57]),"+f"(d[58]),"+f"(d[59]),"+f"(d[60]),"+f"(d[61]),"+f"(d[62]),"+f"(d[63]),"+f"(d[64]),"+f"(d[65]),"+f"(d[66]),"+f"(d[67]),"+f"(d[68]),"+f"(d[69]),"+f"(d[70]),"+f"(d[71]),"+f"(d[72]),"+f"(d[73]),"+f"(d[74]),"+f"(d[75]),"+f"(d[76]),"+f"(d[77]),"+f"(d[78]),"+f"(d[79]),"+f"(d[80]),"+f"(d[81]),"+f"(d[82]),"+f"(d[83]),"+f"(d[84]),"+f"(d[85]),"+f"(d[86]),"+f"(d[87]),"+f"(d[88]),"+f"(d[89]),"+f"(d[90]),"+f"(d[91]),"+f"(d[92]),"+f"(d[93]),"+f"(d[94]),"+f"(d[95]),"+f"(d[96]),"+f"(d[97]),"+f"(d[98]),"+f"(d[99]),"+f"(d[100]),"+f"(d[101]),"+f"(d[102]),"+f"(d[103]),"+f"(d[104]),"+f"(d[105]),"+f"(d[106]),"+f"(d[107]),"+f"(d[108]),"+f"(d[109]),"+f"(d[110]),"+f"(d[111])
   : "r"(a0),"r"(a1),"r"(a2),"r"(a3),"r"(db.lo),"r"(sd),"r"(db.hi));
}
__device__ __forceinline__ void wgmma_ss64(float (&d)[32], Desc da, Desc db, int sd) {
  asm volatile("{.reg .pred p; .reg .b64 da, db; setp.ne.b32 p, %34, 0; mov.b64 da, {%32, %35}; mov.b64 db, {%33, %35};\n wgmma.mma_async.sync.aligned.m64n64k16.f32.bf16.bf16 {%0,%1,%2,%3,%4,%5,%6,%7,%8,%9,%10,%11,%12,%13,%14,%15,%16,%17,%18,%19,%20,%21,%22,%23,%24,%25,%26,%27,%28,%29,%30,%31}, da, db, p, 1, 1, 1, 1;}"
   : "+f"(d[0]),"+f"(d[1]),"+f"(d[2]),"+f"(d[3]),"+f"(d[4]),"+f"(d[5]),"+f"(d[6]),"+f"(d[7]),"+f"(d[8]),"+f"(d[9]),"+f"(d[10]),"+f"(d[11]),"+f"(d[12]),"+f"(d[13]),"+f"(d[14]),"+f"(d[15]),"+f"(d[16]),"+f"(d[17]),"+f"(d[18]),"+f"(d[19]),"+f"(d[20]),"+f"(d[21]),"+f"(d[22]),"+f"(d[23]),"+f"(d[24]),"+f"(d[25]),"+f"(d[26]),"+f"(d[27]),"+f"(d[28]),"+f"(d[29]),"+f"(d[30]),"+f"(d[31])
   : "r"(da.lo),"r"(db.lo),"r"(sd),"r"(db.hi));
}

template <int S, int N, bool SPL = false, int T> __device__ __forceinline__ void ll_issue(uint4 (&v)[T], const uint4* p, int stride, const uint2* p2 = nullptr) {
#pragma unroll
  for (int i = S; i < S + N; i++) {
    if (SPL && i % 7 == 3) { const uint2 lo = ldll2(p2 + i * 64), hi = ldll2(p2 + i * 64 + 32); v[i] = make_uint4(lo.x, lo.y, hi.x, hi.y); }
    else v[i] = ldll(p + i * stride);
  }
}
template <int S, int N, bool SPL, int T> __device__ __forceinline__ void ll_check(uint4 (&v)[T], const uint4* p, int stride, uint32_t tag, const uint2* p2 = nullptr) {
#pragma unroll 1
  for (int it = 0; it < SPIN; it++) {
    uint32_t bad = 0;
#pragma unroll
    for (int i = S; i < S + N; i++) bad |= (v[i].x ^ tag) | ((SPL && i % 7 == 3) ? (v[i].z ^ tag) : 0u);
    if (!__any_sync(~0u, bad & 1)) break;
    ll_issue<S, N, SPL>(v, p, stride, p2);
  }
}
__device__ __forceinline__ void hint_post(uint32_t* p, uint32_t v, int lane) {
  if (lane == 0) asm volatile("st.relaxed.gpu.global.u32 [%0], %1;" ::"l"(p), "r"(v) : "memory");
}
__device__ __forceinline__ void hint_wait(const uint32_t* p, uint32_t s) {
#pragma unroll 1
  for (int it = 0; it < SPIN; it++) {
    uint32_t v; asm volatile("ld.relaxed.gpu.global.u32 %0, [%1];" : "=r"(v) : "l"(p) : "memory");
    if (__all_sync(~0u, v - s < 10u)) break;
  }
}
__device__ __forceinline__ void slice_store(uint4* pf, uint2* ph, const uint32_t (&w)[14], bool odd) {
#pragma unroll
  for (int u = 0; u < 3; u++)
    stll(pf + u * 32, odd ? w[4 * u + 2] : w[4 * u], odd ? w[4 * u + 3] : w[4 * u + 1], odd ? w[4 * u + 4] : w[4 * u + 2], odd ? w[4 * u + 5] : w[4 * u + 3]);
  stll2(ph, odd ? w[0] : w[12], odd ? w[1] : w[13]);
}
template <class F> __device__ __forceinline__ void hedgehog(const float (&d)[28], F sink) {
  const float L2E = 1.4426950408889634f;
#pragma unroll
  for (int r = 0; r < 2; r++)
#pragma unroll
    for (int h = 0; h < 2; h++) {
      float x[7];
#pragma unroll
      for (int p = 0; p < 6; p++) x[p] = d[h * 16 + (p >> 1) * 4 + (p & 1) + 2 * r] * L2E;
      x[6] = d[12 + h + 2 * r] * L2E;
      float mx = x[0], mn = x[0];
#pragma unroll
      for (int p = 1; p < 7; p++) { mx = fmaxf(mx, x[p]); mn = fminf(mn, x[p]); }
      mx = fmaxf(mx, __shfl_xor_sync(~0u, mx, 1)); mn = fminf(mn, __shfl_xor_sync(~0u, mn, 1));
      mx = fmaxf(mx, __shfl_xor_sync(~0u, mx, 2)); mn = fminf(mn, __shfl_xor_sync(~0u, mn, 2));
      float ep[7], en[7], sp = 0.f, sn = 0.f;
#pragma unroll
      for (int p = 0; p < 7; p++) { ep[p] = ex2(x[p] - mx); en[p] = ex2(mn - x[p]); sp += ep[p]; sn += en[p]; }
      sp = rcp(qsum(sp)); sn = rcp(qsum(sn));
#pragma unroll
      for (int p = 0; p < 7; p++) sink(r, h, p, pack(ep[p] * sp, en[p] * sn));
    }
}
__device__ __forceinline__ void phi_gemm(const float (&x)[28], float (&y)[28], uint32_t wphi) {
  uint32_t f[14];
#pragma unroll
  for (int j = 0; j < 14; j++) f[j] = pack(x[2 * j], x[2 * j + 1]);
  wg_fence();
#pragma unroll
  for (int ks = 0; ks < 3; ks++) wgmma_rs56(y, f[4 * ks], f[4 * ks + 1], f[4 * ks + 2], f[4 * ks + 3], mkdesc(wphi >> 4, ks * 2048, 1024, 1024, 1), ks);
  wgmma_rs56(y, f[12], f[13], 0u, 0u, mkdesc(wphi >> 4, 3 * 2048, 1024, 1024, 1), 1);
  wg_commit();
}
__device__ __forceinline__ void ln_publish(uint32_t (&xw)[4][4], float* sLN, int warp, int lane, uint4* fb, uint32_t tag) {
  const int g = lane >> 2;
  float s0 = 0.f, s1 = 0.f;
#pragma unroll
  for (int u = 0; u < 4; u++) {
    stll(fb + XR + u * 32, tg(xw[u][0], tag), xw[u][1], tg(xw[u][2], tag), xw[u][3]);
    s0 += blo(xw[u][0]) + bhi(xw[u][0]) + blo(xw[u][2]) + bhi(xw[u][2]);
    s1 += blo(xw[u][1]) + bhi(xw[u][1]) + blo(xw[u][3]) + bhi(xw[u][3]);
  }
  s0 = qsum(s0) * (1.f / 64); s1 = qsum(s1) * (1.f / 64);
  float v0 = 0.f, v1 = 0.f;
#pragma unroll
  for (int u = 0; u < 4; u++)
#pragma unroll
    for (int k = 0; k < 4; k += 2) {
      float a = blo(xw[u][k]) - s0, b = bhi(xw[u][k]) - s0, c2 = blo(xw[u][k + 1]) - s1, d2 = bhi(xw[u][k + 1]) - s1;
      v0 += a * a + b * b; v1 += c2 * c2 + d2 * d2;
    }
  v0 = qsum(v0); v1 = qsum(v1);
  if ((lane & 3) == 0) { sLN[warp * 16 + g] = s0; sLN[warp * 16 + g + 8] = s1; sLN[112 + warp * 16 + g] = v0; sLN[112 + warp * 16 + g + 8] = v1; }
  bar_ln();
  float m0 = 0.f, m1 = 0.f; v0 = 0.f; v1 = 0.f;
#pragma unroll
  for (int w = 0; w < 7; w++) { m0 += sLN[w * 16 + g]; m1 += sLN[w * 16 + g + 8]; }
  m0 *= (1.f / 7); m1 *= (1.f / 7);
#pragma unroll
  for (int w = 0; w < 7; w++) {
    float a = sLN[w * 16 + g] - m0, b = sLN[w * 16 + g + 8] - m1;
    v0 += sLN[112 + w * 16 + g] + 64.f * a * a; v1 += sLN[112 + w * 16 + g + 8] + 64.f * b * b;
  }
  const float r0 = rsqrtf(v0 * (1.f / 448) + 1e-5f), r1 = rsqrtf(v1 * (1.f / 448) + 1e-5f);
#pragma unroll
  for (int u = 0; u < 4; u++)
    stll(fb + XN + u * 32, tg(pack((blo(xw[u][0]) - m0) * r0, (bhi(xw[u][0]) - m0) * r0), tag), pack((blo(xw[u][1]) - m1) * r1, (bhi(xw[u][1]) - m1) * r1),
         pack((blo(xw[u][2]) - m0) * r0, (bhi(xw[u][2]) - m0) * r0), pack((blo(xw[u][3]) - m1) * r1, (bhi(xw[u][3]) - m1) * r1));
}

__global__ void __launch_bounds__(384, 1)
fused_kernel(const __grid_constant__ CUtensorMap mQKV, const __grid_constant__ CUtensorMap mWO, const __grid_constant__ CUtensorMap mW1,
             const __grid_constant__ CUtensorMap mW2, const __nv_bfloat16* __restrict__ x, const __nv_bfloat16* __restrict__ wphi,
             const __nv_bfloat16* __restrict__ wo, const __nv_bfloat16* __restrict__ w1, const __nv_bfloat16* __restrict__ b1,
             const __nv_bfloat16* __restrict__ w2, const __nv_bfloat16* __restrict__ b2, __nv_bfloat16* __restrict__ out) {
  extern __shared__ __align__(1024) uint8_t sm[];
  const uint32_t sb = s2u(sm);
  const int tid = threadIdx.x, warp = __shfl_sync(~0u, tid >> 5, 0), lane = tid & 31, t = blockIdx.x >> 3, c = blockIdx.x & 7;
  const uint32_t bfull = sb + OFF_BAR, bempty = bfull + 8 * NST;

  if (tid == 256) {
    for (int s = 0; s < NST; s++) { mbar_init(bfull + 8 * s, 1); mbar_init(bempty + 8 * s, 8); }
    asm volatile("fence.mbarrier_init.release.cluster;" ::: "memory");
    fence_async();
  }
  __syncthreads();
  if (warp >= 8) {
    asm volatile("setmaxnreg.dec.sync.aligned.u32 40;");
    auto issue = [&](int i, int s) {
      const uint32_t dst = sb + s * STAGE, bar = bfull + 8 * s;
      mbar_expect(bar, STAGE);
      if (i < 4) {
        tma2d(dst, &mQKV, 448 + 56 * c, 112 * i, bar); tma2d(dst + 7168, &mQKV, 480 + 56 * c, 112 * i, bar);
        tma2d(dst + 14336, &mQKV, 896 + 56 * c, 112 * i, bar); tma2d(dst + 21504, &mQKV, 928 + 56 * c, 112 * i, bar);
      } else if (i >= 8 && i < 15) {
        tma3d(dst, &mW1, 0, 64 * (i - 8), 7 * c, bar);
      } else {
        const CUtensorMap* m = i < 6 ? &mQKV : (i < 8 ? &mWO : &mW2);
        const int n0 = i < 8 ? 56 * c : 64 * (i - 15), k0 = i < 8 ? 224 * (i & 1) : 224 * c;
        tma2d(dst, m, n0, k0, bar); tma2d(dst + 7168, m, n0, k0 + 112, bar);
        tma2d(dst + 14336, m, n0 + 32, k0, bar); tma2d(dst + 21504, m, n0 + 32, k0 + 112, bar);
      }
    };
    if (tid == 256) {
      int s = 0; uint32_t ph = 1;
      for (int n = 0; n < 44; n++) {
        mbar_wait(bempty + 8 * s, ph);
        issue(n >= 22 ? n - 22 : n, s);
        if (++s == NST) { s = 0; ph ^= 1; }
      }
    } else if (warp == 9) {
      mbar_wait(bfull + 8 * 3, 0);
      if (lane == 0) {
        l2pf((const uint8_t*)wo + blockIdx.x * 3136, 3136);
        l2pf((const uint8_t*)w1 + blockIdx.x * 12544, 12544);
        l2pf((const uint8_t*)w2 + blockIdx.x * 12544, 12544);
      }
      if (blockIdx.x < 112) {
        const uint2* wp = (const uint2*)(w1 + (size_t)(lane >> 2) * 1792 + blockIdx.x * 16 + (lane & 3) * 4);
        float s0 = 0.f, s1 = 0.f, s2 = 0.f, s3 = 0.f;
#pragma unroll 8
        for (int i = 0; i < 56; i++) { const uint2 v = __ldg(wp + i * 8 * 448); s0 += blo(v.x); s1 += bhi(v.x); s2 += blo(v.y); s3 += bhi(v.y); }
#pragma unroll 1
        for (int o = 4; o < 32; o <<= 1) { s0 += __shfl_xor_sync(~0u, s0, o); s1 += __shfl_xor_sync(~0u, s1, o); s2 += __shfl_xor_sync(~0u, s2, o); s3 += __shfl_xor_sync(~0u, s3, o); }
        if (lane < 4) stll(g_CS + blockIdx.x * 4 + lane, tg(__float_as_uint(s0), 1), __float_as_uint(s1), __float_as_uint(s2), __float_as_uint(s3));
      }
#pragma unroll 1
      for (int i = 0; i < 2; i++) {
        const int e = lane < 28 ? lane + 28 * i : 0;
        uint4 cv[1];
        ll_issue<0, 1>(cv, g_CS + 56 * c + e, 0); ll_check<0, 1, false>(cv, g_CS + 56 * c + e, 0, 1u);
        const uint2 bb = __ldg((const uint2*)(b1 + 224 * c + 4 * e));
        sts128(sb + OFF_CB + e * 32, cv[0].x, cv[0].y, bb.x << 16, bb.x & 0xffff0000u);
        sts128(sb + OFF_CB + e * 32 + 16, cv[0].z, cv[0].w, bb.y << 16, bb.y & 0xffff0000u);
      }
      asm volatile("bar.arrive 4, 288;" ::: "memory");
    } else if (warp >= 10) {
      const int h = warp - 10;
      uint32_t wv[13];
#pragma unroll
      for (int i = 0; i < 13; i++) { const int e = lane + 32 * i; wv[i] = e < 392 ? __ldg((const uint32_t*)wphi + (2 * c + h) * 392 + e) : 0u; }
#pragma unroll 1
      for (int i = 0; i < 8; i++) sts128(sb + OFF_WPHI + (h * 256 + i * 32 + lane) * 16, 0, 0, 0, 0);
#pragma unroll 1
      for (int i = 0; i < 4; i++) sts128(sb + OFF_PHIK + sw128(h * 128 + i * 32 + lane, 56), 0, 0, 0, 0);
      asm volatile("bar.sync 5, 64;" ::: "memory");
#pragma unroll
      for (int i = 0; i < 13; i++) {
        const int e = lane + 32 * i, d = e / 14, f2 = 2 * (e - 14 * d), k = 28 * h + d;
        if (e < 392) {
          if (f2 < 24) sts32(sb + OFF_WPHI + sw128(k, 32 * h + f2), wv[i]);
          else { sts16(sb + OFF_WPHI + sw128(k, 2 * f2 - 24 + h), wv[i]); sts16(sb + OFF_WPHI + sw128(k, 2 * f2 - 22 + h), wv[i] >> 16); }
        }
      }
      fence_async();
      asm volatile("bar.arrive 3, 320;" ::: "memory");
    }
  } else {
  asm volatile("setmaxnreg.inc.sync.aligned.u32 232;");

  const int wg = warp >> 2, g = lane >> 2, q = lane & 3;
  const int row0 = warp * 16 + g;
#define PTRS const int ln_ = laneid(); \
  uint4* const fm = g_F + ((t * 8 + warp) * 28) * 32 + ln_;            \
  uint4* const fr = g_F + ((t * 8 + c) * 28 + 4 * warp) * 32 + ln_;    \
  uint2* const fe = (uint2*)(fm + ((7 * c) >> 1) * 32) + (c & 1);       \
  uint2* const fo = (uint2*)(fm + ((7 * c + 1) >> 1) * 32) + ((c + 1) & 1); \
  uint4* const sf = fm + (7 * (c >> 1) + 4 * (c & 1)) * 32;             \
  uint2* const f2 = (uint2*)(fm - ln_) + ln_;                           \
  uint2* const sh = f2 + (7 * (c >> 1) + 3) * 64 + 32 * (c & 1);        \
  uint32_t* const hme = g_H + (t * 8 + warp) * 8 + c; \
  const uint32_t* const hrow = g_H + (t * 8 + warp) * 8 + (ln_ & 7); \
  (void)fm; (void)fr; (void)fe; (void)fo; (void)sf; (void)f2; (void)sh; (void)hme; (void)hrow;
#define SL(j, B) (((j) & 1 ? fo : fe) + ((j) >> 1) * 64 + 2 * (B))
  float* sLN = (float*)(sm + OFF_LN);
  const uint32_t sPK = sb + OFF_PHIK, sV = sb + OFF_V, sW = sb + OFF_WPHI;
  #define XOFF(l) ((t * 128 + c * 16 + ((l) >> 2)) * 448 + warp * 64 + 2 * ((l) & 3))
  MARK(0);
  uint32_t xw[4][4];
  if (warp < 7) {
    const uint32_t* xp = (const uint32_t*)(x + XOFF(lane));
#pragma unroll
    for (int u = 0; u < 4; u++) { xw[u][0] = __ldg(xp + u * 8); xw[u][1] = __ldg(xp + u * 8 + 1792); xw[u][2] = __ldg(xp + u * 8 + 4); xw[u][3] = __ldg(xp + u * 8 + 1796); }
  }
  int cs = 0, rs = 0; uint32_t cph = 0;
  auto acquire = [&]() -> uint32_t { mbar_wait(bfull + 8 * cs, cph); const uint32_t a = (sb >> 4) + cs * (STAGE >> 4); if (++cs == NST) { cs = 0; cph ^= 1; } return a; };
  auto release = [&]() { if (lane == 0) mbar_arrive(bempty + 8 * rs); if (++rs == NST) rs = 0; };

#pragma unroll 1
  for (int L = 0; L < 2; L++) {
    const uint32_t tag = 1 - L;
    uint32_t phq[2][2][7];
    const uint32_t hs = 10 * L;
    if (warp < 7) { PTRS ln_publish(xw, sLN, warp, lane, fr, tag); hint_post(hme, hs + 1, lane); }
    MARK(1 + L * 19);
    {
      PTRS
      uint4 a[28];
      const uint4* pa = fm + XN;
      hint_wait(g_H + (t * 8 + (lane < 7 ? lane : 0)) * 8 + warp, hs + 1); ll_issue<0, 28>(a, pa, 32);
      MARK(2 + L * 19);
      float ak[28], av[28], aq[28], pp[28];
#define KVSTAGE(i) { ll_check<7 * i, 7, false>(a, pa, 32, tag); const uint32_t st = acquire(); wg_fence(); \
      _Pragma("unroll") for (int ks = 0; ks < 7; ks++) { const uint4 f = a[7 * i + ks]; \
        wgmma_rs56(ak, f.x, f.y, f.z, f.w, mkdesc(st, ks * 1024, 7168, 512, 2), i | ks); \
        wgmma_rs56(av, f.x, f.y, f.z, f.w, mkdesc(st, 14336 + ks * 1024, 7168, 512, 2), i | ks); } \
      wg_commit(); if (i > 0) { wg_wait<1>(); release(); } }
      KVSTAGE(0) KVSTAGE(1) KVSTAGE(2) KVSTAGE(3)
      wg_wait<0>(); release(); regfence(ak); regfence(av);
      MARK(3 + L * 19);
      if (L == 0) asm volatile("bar.sync 3, 320;" ::: "memory");
      phi_gemm(ak, pp, sW);
#pragma unroll
      for (int j = 0; j < 7; j++) {
        const int n = 8 * j + 2 * q, n2 = n < 28 ? n : n + 4;
        sts32(sV + sw128(row0, n2), pack(av[4 * j], av[4 * j + 1])); sts32(sV + sw128(row0 + 8, n2), pack(av[4 * j + 2], av[4 * j + 3]));
      }
      { const int n2 = 28 + 2 * (q & 1) + 32 * (q >> 1); const uint32_t v = (q & 1) ? 0u : 0x3F80u; sts32(sV + sw128(row0, n2), v); sts32(sV + sw128(row0 + 8, n2), v); }
#pragma unroll
      for (int i = 0; i < 2; i++) {
        const uint32_t st = acquire(); wg_fence();
#pragma unroll
        for (int ks = 0; ks < 14; ks++) { const uint4 f = a[14 * i + ks]; wgmma_rs56(aq, f.x, f.y, f.z, f.w, mkdesc(st, ks * 1024, 14336, 512, 2), i | ks); }
        wg_commit();
      }
      wg_wait<2>(); regfence(pp);
      hedgehog(pp, [&](int r, int h, int p, uint32_t v) { sts32(sPK + h * 16384 + sw128(row0 + 8 * r, 8 * p + 2 * q), v); });
      fence_async();
      wg_wait<0>(); release(); release(); regfence(aq);
      bar_cons();
      MARK(4 + L * 19);
      float kv[32];
      wg_fence();
#pragma unroll
      for (int ks = 0; ks < 8; ks++) wgmma_ss64(kv, mkdesc((sPK + wg * 16384) >> 4, ks * 2048, 1024, 1024, 1), mkdesc(sV >> 4, ks * 2048, 1024, 1024, 1), ks);
      wg_commit();
      phi_gemm(aq, pp, sW);
      wg_wait<1>(); regfence(kv);
      const int ln2 = laneid();
#pragma unroll
      for (int u = 0; u < 4; u++) {
        float e[4];
#pragma unroll
        for (int i = 0; i < 4; i++) e[i] = wg ? kv[16 + 4 * u + i] : kv[4 * u + i];
        stll(g_KVP + (c * 16 + t) * 1024 + wg * 512 + u * 128 + (warp & 3) * 32 + ln2, tg(__float_as_uint(e[0]), tag), __float_as_uint(e[1]), __float_as_uint(e[2]), __float_as_uint(e[3]));
      }
      MARK(5 + L * 19);
      bar_cons();
#pragma unroll
      for (int i = 0; i < 4; i++) sts128(sV + (tid + i * 256) * 16, 0, 0, 0, 0);
      wg_wait<0>(); regfence(pp);
      hedgehog(pp, [&](int r, int h, int p, uint32_t v) { phq[r][h][p] = v; });
    }
    MARK(6 + L * 19);
    {
      uint4 k4[4];
      const int ln2 = laneid();
      const uint4* pk = g_KVP + (c * 16 + 4 * (ln2 & 3)) * 1024 + 64 * t + warp * 8 + (ln2 >> 2);
      ll_issue<0, 4>(k4, pk, 1024); ll_check<0, 4, false>(k4, pk, 1024, tag);
      float s0 = 0, s1 = 0, s2 = 0, s3 = 0;
#pragma unroll
      for (int i = 0; i < 4; i++) { s0 += __uint_as_float(k4[i].x); s1 += __uint_as_float(k4[i].y); s2 += __uint_as_float(k4[i].z); s3 += __uint_as_float(k4[i].w); }
      s0 = qsum(s0); s1 = qsum(s1); s2 = qsum(s2); s3 = qsum(s3);
      if (q == 0) stll2(g_KVR + c * 1024 + 64 * t + warp * 8 + (ln2 >> 2), tg(pack(s0, s1), tag), pack(s2, s3));
      MARK(7 + L * 19);
      bar_cons();
      uint2 r[4];
      const uint2* pr = g_KVR + c * 1024 + wg * 512 + (warp & 3) * 32 + ln2;
#pragma unroll 1
      for (int it = 0; it < SPIN; it++) {
        uint32_t bad = 0;
#pragma unroll
        for (int u = 0; u < 4; u++) { r[u] = ldll2(pr + u * 128); bad |= r[u].x ^ tag; }
        if (!__any_sync(~0u, bad & 1)) break;
      }
#pragma unroll
      for (int u = 0; u < 4; u++) {
        const int d = 8 * u + 2 * q;
        if (d < 28) { sts32(sV + sw128(row0, 28 * wg + d), r[u].x); sts32(sV + sw128(row0 + 8, 28 * wg + d), r[u].y); }
        else if (d == 28) {
#pragma unroll
          for (int j = 0; j < 4; j++) { sts16(sV + sw128(row0, 56 + 2 * j + wg), r[u].x); sts16(sV + sw128(row0 + 8, 56 + 2 * j + wg), r[u].y); }
        }
      }
      fence_async();
      bar_cons();
      MARK(8 + L * 19);
      float o[32];
      wg_fence();
#pragma unroll
      for (int ks = 0; ks < 8; ks++) {
        const int h = ks >> 2, p = 2 * (ks & 3);
        wgmma_rs64(o, phq[0][h][p], phq[1][h][p], p < 6 ? phq[0][h][p < 6 ? p + 1 : 0] : 0u, p < 6 ? phq[1][h][p < 6 ? p + 1 : 0] : 0u, mkdesc(sV >> 4, ks * 2048, 1024, 1024, 1), ks);
      }
      wg_commit(); wg_wait<0>(); regfence(o);
      const float iA0 = rcp(o[28] + 1e-6f), iB0 = rcp(o[29] + 1e-6f), iA1 = rcp(o[30] + 1e-6f), iB1 = rcp(o[31] + 1e-6f);
      uint32_t w[14];
      PTRS
#pragma unroll
      for (int j = 0; j < 7; j++) {
        const bool hb = 8 * j + 2 * q >= 28; const float i0 = hb ? iB0 : iA0, i1 = hb ? iB1 : iA1;
        w[2 * j] = pack(o[4 * j] * i0, o[4 * j + 1] * i0); w[2 * j + 1] = pack(o[4 * j + 2] * i1, o[4 * j + 3] * i1);
        if (j == 0 || ((j ^ c) & 1) == 0) w[2 * j] = tg(w[2 * j], tag);
      }
      slice_store(sf + OO, sh + 2 * OO, w, c & 1);
      hint_post(hme, hs + 2, lane);
    }
    MARK(9 + L * 19);
    {
      PTRS
      uint2 xr[7];
#pragma unroll
      for (int j = 0; j < 7; j++) xr[j] = ldll2(SL(j, XR));
      uint4 a[28];
      const uint4* pa = fm + OO;
      hint_wait(hrow, hs + 2);
      MARK(10 + L * 19);
      ll_issue<0, 28, true>(a, pa, 32, f2 + 2 * OO);
      float y[28];
      uint32_t st;
#define WOSTEP(i) { ll_check<7 * i, 7, true>(a, pa, 32, tag, f2 + 2 * OO); if (!(i & 1)) st = acquire(); wg_fence(); \
      _Pragma("unroll") for (int ks = 0; ks < 7; ks++) { const uint4 f = a[7 * i + ks]; \
        wgmma_rs56(y, f.x, f.y, f.z, f.w, mkdesc(st, ((i & 1) * 7 + ks) * 1024, 14336, 512, 2), i | ks); } wg_commit(); }
      WOSTEP(0) WOSTEP(1) WOSTEP(2) WOSTEP(3)
#pragma unroll 1
      for (int it = 0; it < SPIN; it++) {
        uint32_t bad = 0;
#pragma unroll
        for (int j = 0; j < 7; j++) bad |= xr[j].x ^ tag;
        if (!__any_sync(~0u, bad & 1)) break;
#pragma unroll
        for (int j = 0; j < 7; j++) xr[j] = ldll2(SL(j, XR));
      }
      wg_wait<0>(); release(); release(); regfence(y);
      MARK(11 + L * 19);
      float s0 = 0.f, s1 = 0.f;
      uint32_t w[14];
#pragma unroll
      for (int j = 0; j < 7; j++) {
        w[2 * j] = pack(blo(xr[j].x) + y[4 * j], bhi(xr[j].x) + y[4 * j + 1]); w[2 * j + 1] = pack(blo(xr[j].y) + y[4 * j + 2], bhi(xr[j].y) + y[4 * j + 3]);
        if (j == 0 || ((j ^ c) & 1) == 0) w[2 * j] = tg(w[2 * j], tag);
      }
      slice_store(sf + X1, sh + 2 * X1, w, c & 1);
      hint_post(hme, hs + 3, lane);
#pragma unroll
      for (int j = 0; j < 7; j++) {
        y[4 * j] = blo(w[2 * j]); y[4 * j + 1] = bhi(w[2 * j]); y[4 * j + 2] = blo(w[2 * j + 1]); y[4 * j + 3] = bhi(w[2 * j + 1]);
        s0 += y[4 * j] + y[4 * j + 1]; s1 += y[4 * j + 2] + y[4 * j + 3];
      }
      s0 = qsum(s0) * (1.f / 56); s1 = qsum(s1) * (1.f / 56);
      float v0 = 0.f, v1 = 0.f;
#pragma unroll
      for (int j = 0; j < 7; j++) {
        const float d0 = y[4 * j] - s0, d1 = y[4 * j + 1] - s0, d2 = y[4 * j + 2] - s1, d3 = y[4 * j + 3] - s1;
        v0 += d0 * d0 + d1 * d1; v1 += d2 * d2 + d3 * d3;
      }
      v0 = qsum(v0); v1 = qsum(v1);
      if (q == 0) stll(g_ST + ((t * 8 + warp) * 8 + c) * 8 + (ln_ >> 2), tg(__float_as_uint(s0), tag), __float_as_uint(v0), __float_as_uint(s1), __float_as_uint(v1));
    }
    uint32_t hf[56];
    {
      PTRS
      uint4 a[28];
      const uint4* pa = fm + X1;
      hint_wait(hrow, hs + 3);
      MARK(12 + L * 19);
      ll_issue<0, 16, true>(a, pa, 32, f2 + 2 * X1);
      float y[112];
#define F1STAGE(i) { ll_check<4 * i, 4, true>(a, pa, 32, tag, f2 + 2 * X1); const uint32_t st = acquire(); wg_fence(); \
      _Pragma("unroll") for (int ks = 0; ks < 4; ks++) { const uint4 f = a[4 * i + ks]; \
        wgmma_rs224(y, f.x, f.y, f.z, f.w, mkdesc(st, ks * 1024, 4096, 512, 2), i | ks); } \
      wg_commit(); if (i > 0) { wg_wait<1>(); release(); if (i < 4) ll_issue<(i < 4 ? 4 * i + 12 : 0), 4, true>(a, pa, 32, f2 + 2 * X1); } }
      F1STAGE(0) MARK(13 + L * 19); F1STAGE(1) F1STAGE(2) F1STAGE(3) F1STAGE(4) F1STAGE(5)
      uint4 sv[2];
      const uint4* ps = g_ST + ((t * 8 + warp) * 8 + 2 * (laneid() & 3)) * 8 + (laneid() >> 2);
      ll_issue<0, 2>(sv, ps, 8);
      F1STAGE(6)
      ll_check<0, 2, false>(sv, ps, 8, tag);
      const float ma = __uint_as_float(sv[0].x), mb = __uint_as_float(sv[1].x), mc = __uint_as_float(sv[0].z), md = __uint_as_float(sv[1].z);
      const float m0 = qsum(ma + mb) * 0.125f, m1 = qsum(mc + md) * 0.125f;
      const float v0 = qsum(__uint_as_float(sv[0].y) + __uint_as_float(sv[1].y) + 56.f * ((ma - m0) * (ma - m0) + (mb - m0) * (mb - m0)));
      const float v1 = qsum(__uint_as_float(sv[0].w) + __uint_as_float(sv[1].w) + 56.f * ((mc - m1) * (mc - m1) + (md - m1) * (md - m1)));
      const float r0 = rsqrtf(v0 * (1.f / 448) + 1e-5f), r1 = rsqrtf(v1 * (1.f / 448) + 1e-5f);
      const float n0 = -m0 * r0, n1 = -m1 * r1;
      if (L == 0) asm volatile("bar.sync 4, 288;" ::: "memory");
      wg_wait<0>(); release(); regfence(y);
      MARK(14 + L * 19);
#pragma unroll
      for (int j = 0; j < 28; j++) {
        const float4 cb = *(const float4*)(sm + OFF_CB + (j * 4 + q) * 16);
        const float h0 = fmaxf(fmaf(y[4 * j], r0, fmaf(n0, cb.x, cb.z)), 0.f), h1 = fmaxf(fmaf(y[4 * j + 1], r0, fmaf(n0, cb.y, cb.w)), 0.f);
        const float h2 = fmaxf(fmaf(y[4 * j + 2], r1, fmaf(n1, cb.x, cb.z)), 0.f), h3 = fmaxf(fmaf(y[4 * j + 3], r1, fmaf(n1, cb.y, cb.w)), 0.f);
        hf[2 * j] = pack(h0 * h0, h1 * h1); hf[2 * j + 1] = pack(h2 * h2, h3 * h3);
      }
    }
    MARK(15 + L * 19);
    {
      PTRS
      float ya[32], yb[32];
      uint4* pp = g_P + ((t * 8 + warp) * 8 + c) * 28 * 32 + ln_;
#define F2STORE(j, Y) { regfence(Y); _Pragma("unroll") for (int u = 0; u < 4; u++) \
      stll(pp + (4 * (j) + u) * 32, tg(pack(Y[8 * u], Y[8 * u + 1]), tag), pack(Y[8 * u + 2], Y[8 * u + 3]), pack(Y[8 * u + 4], Y[8 * u + 5]), pack(Y[8 * u + 6], Y[8 * u + 7])); hint_post(hme, hs + (4 + (j)), lane); }
#define F2PASS(j, Y, Z) { const uint32_t st = acquire(); wg_fence(); \
      _Pragma("unroll") for (int ks = 0; ks < 14; ks++) wgmma_rs64(Y, hf[4 * ks], hf[4 * ks + 1], hf[4 * ks + 2], hf[4 * ks + 3], mkdesc(st, ks * 1024, 14336, 512, 2), ks); \
      wg_commit(); if (j > 0) { wg_wait<1>(); release(); F2STORE(j - 1, Z) } }
      F2PASS(0, ya, yb) F2PASS(1, yb, ya) F2PASS(2, ya, yb) F2PASS(3, yb, ya) F2PASS(4, ya, yb) F2PASS(5, yb, ya) F2PASS(6, ya, yb)
      wg_wait<0>(); release(); F2STORE(6, ya)
    }
    MARK(16 + L * 19);
    if (warp < 7) {
      PTRS
      uint4 x1[4], p[32];
      uint32_t bw[8];
#pragma unroll
      for (int u = 0; u < 4; u++) {
        const bool spl = (4 * warp + u) % 7 == 3;
        const uint2* p0 = (const uint2*)(fr + X1 + u * 32) - (spl ? lane : 0);
        const uint2 lo = ldll2(p0), hi = ldll2(p0 + (spl ? 32 : 1)); x1[u] = make_uint4(lo.x, lo.y, hi.x, hi.y);
      }
#pragma unroll
      for (int i = 0; i < 8; i++) bw[i] = __ldg((const uint32_t*)(b2 + warp * 64 + i * 8 + 2 * q));
      const uint4* pp = g_P + ((t * 8 + c) * 8 * 28 + 4 * warp) * 32 + ln_;
      hint_wait(g_H + (t * 8 + c) * 8 + (lane & 7), hs + 4 + warp);
      ll_issue<0, 8>(p, pp + 96, 896);
      ll_issue<8, 8>(p, pp + 64 - 8 * 896, 896); ll_issue<16, 8>(p, pp + 32 - 16 * 896, 896); ll_issue<24, 8>(p, pp - 24 * 896, 896);
      MARK(17 + L * 19);
#define REDU(u, S) { ll_check<S, 8, false>(p, pp + u * 32 - S * 896, 896, tag); \
      float e[8] = {blo(x1[u].x) + blo(bw[2 * u]), bhi(x1[u].x) + bhi(bw[2 * u]), blo(x1[u].y) + blo(bw[2 * u]), bhi(x1[u].y) + bhi(bw[2 * u]), \
                    blo(x1[u].z) + blo(bw[2 * u + 1]), bhi(x1[u].z) + bhi(bw[2 * u + 1]), blo(x1[u].w) + blo(bw[2 * u + 1]), bhi(x1[u].w) + bhi(bw[2 * u + 1])}; \
      _Pragma("unroll") for (int i = S; i < S + 8; i++) { e[0] += blo(p[i].x); e[1] += bhi(p[i].x); e[2] += blo(p[i].y); e[3] += bhi(p[i].y); \
        e[4] += blo(p[i].z); e[5] += bhi(p[i].z); e[6] += blo(p[i].w); e[7] += bhi(p[i].w); } \
      xw[u][0] = pack(e[0], e[1]); xw[u][1] = pack(e[2], e[3]); xw[u][2] = pack(e[4], e[5]); xw[u][3] = pack(e[6], e[7]); }
      REDU(3, 0) REDU(2, 8) REDU(1, 16) REDU(0, 24)
    }
    MARK(18 + L * 19);
  }
  if (warp < 7) {
    uint32_t* op = (uint32_t*)(out + XOFF(laneid()));
#pragma unroll
    for (int u = 0; u < 4; u++) { op[u * 8] = xw[u][0]; op[u * 8 + 1792] = xw[u][1]; op[u * 8 + 4] = xw[u][2]; op[u * 8 + 1796] = xw[u][3]; }
  } else if (blockIdx.x < 112 && lane < 4) stll(g_CS + blockIdx.x * 4 + lane, 0, 0, 0, 0);
  MARK(38);
  }
}

typedef CUresult (*EncFn)(CUtensorMap*, CUtensorMapDataType, cuuint32_t, void*, const cuuint64_t*, const cuuint64_t*, const cuuint32_t*, const cuuint32_t*,
                          CUtensorMapInterleave, CUtensorMapSwizzle, CUtensorMapL2promotion, CUtensorMapFloatOOBfill);

extern "C" void kernel_launch(void* const* d_in, const int* in_sizes, int n_in, void* d_out, int out_size) {
  static EncFn enc = nullptr;
  if (!enc) {
    void* fn = nullptr; cudaDriverEntryPointQueryResult qr;
    cudaGetDriverEntryPoint("cuTensorMapEncodeTiled", &fn, cudaEnableDefault, &qr);
    enc = (EncFn)fn;
    cudaFuncSetAttribute(fused_kernel, cudaFuncAttributeMaxDynamicSharedMemorySize, SMEM_BYTES);
  }
  CUtensorMap mQKV, mWO, mW1, mW2;
  const cuuint32_t es[3] = {1, 1, 1};
  auto enc2 = [&](CUtensorMap* m, void* p, cuuint64_t cols, cuuint64_t rows) {
    const cuuint64_t dims[2] = {cols, rows}, str[1] = {cols * 2}; const cuuint32_t box[2] = {32, 112};
    enc(m, CU_TENSOR_MAP_DATA_TYPE_BFLOAT16, 2, p, dims, str, box, es, CU_TENSOR_MAP_INTERLEAVE_NONE, CU_TENSOR_MAP_SWIZZLE_64B,
        CU_TENSOR_MAP_L2_PROMOTION_L2_128B, CU_TENSOR_MAP_FLOAT_OOB_FILL_NONE);
  };
  enc2(&mQKV, d_in[1], 1344, 448); enc2(&mWO, d_in[3], 448, 448); enc2(&mW2, d_in[7], 448, 1792);
  {
    const cuuint64_t dims[3] = {32, 448, 56}, str[2] = {3584, 64}; const cuuint32_t box[3] = {32, 64, 7};
    enc(&mW1, CU_TENSOR_MAP_DATA_TYPE_BFLOAT16, 3, d_in[5], dims, str, box, es, CU_TENSOR_MAP_INTERLEAVE_NONE, CU_TENSOR_MAP_SWIZZLE_64B,
        CU_TENSOR_MAP_L2_PROMOTION_L2_128B, CU_TENSOR_MAP_FLOAT_OOB_FILL_NONE);
  }
  typedef const __nv_bfloat16* BP;
  fused_kernel<<<128, 384, SMEM_BYTES>>>(mQKV, mWO, mW1, mW2, (BP)d_in[0], (BP)d_in[2], (BP)d_in[3], (BP)d_in[5], (BP)d_in[6], (BP)d_in[7], (BP)d_in[8],
                                         (__nv_bfloat16*)d_out);
}
```

```cpp
#include <cuda_runtime.h>
#include <cuda_bf16.h>
#include <cuda.h>
#include <stdint.h>

constexpr int NST = 6, STAGE = 28672;
constexpr int OFF_PHIK = NST * STAGE;
constexpr int OFF_V = OFF_PHIK + 32768;
constexpr int OFF_WPHI = OFF_V + 16384;
constexpr int OFF_CB = OFF_WPHI + 8192;
constexpr int OFF_LN = OFF_CB + 1792;
constexpr int OFF_BAR = OFF_LN + 896;
constexpr int SMEM_BYTES = OFF_BAR + 16 * NST;
constexpr int FR = 16 * 8 * 28 * 32;
constexpr int SPIN = 1 << 18;

__device__ uint4 g_F[4 * FR];
constexpr int XN = 0, XR = FR, OO = 2 * FR, X1 = 3 * FR;
__device__ uint4 g_P[8 * FR];
__device__ uint4 g_ST[16 * 8 * 8 * 8];
__device__ uint4 g_KVP[8 * 16 * 1024];
__device__ uint2 g_KVR[8 * 1024];
__device__ uint4 g_CS[448];
__device__ uint32_t g_H[16 * 8 * 8];
#define MARK(i)

__device__ __forceinline__ uint32_t s2u(const void* p) { return (uint32_t)__cvta_generic_to_shared(p); }
__device__ __forceinline__ void mbar_init(uint32_t b, uint32_t c) { asm volatile("mbarrier.init.shared::cta.b64 [%0], %1;" ::"r"(b), "r"(c)); }
__device__ __forceinline__ void mbar_expect(uint32_t b, uint32_t tx) { asm volatile("mbarrier.arrive.expect_tx.shared::cta.b64 _, [%0], %1;" ::"r"(b), "r"(tx) : "memory"); }
__device__ __forceinline__ void mbar_arrive(uint32_t b) { asm volatile("mbarrier.arrive.shared::cta.b64 _, [%0];" ::"r"(b) : "memory"); }
__device__ __forceinline__ void mbar_wait(uint32_t b, uint32_t ph) {
  uint32_t ok = 0;
#pragma unroll 1
  for (int it = 0; it < SPIN && !ok; it++)
    asm volatile("{.reg .pred p; mbarrier.try_wait.parity.shared::cta.b64 p,[%1],%2; selp.u32 %0,1,0,p;}" : "=r"(ok) : "r"(b), "r"(ph) : "memory");
}
__device__ __forceinline__ void tma2d(uint32_t dst, const CUtensorMap* m, int c0, int c1, uint32_t bar) {
  asm volatile("cp.async.bulk.tensor.2d.shared::cluster.global.mbarrier::complete_tx::bytes [%0], [%1, {%3, %4}], [%2];"
               ::"r"(dst), "l"(m), "r"(bar), "r"(c0), "r"(c1) : "memory");
}
__device__ __forceinline__ void tma3d(uint32_t dst, const CUtensorMap* m, int c0, int c1, int c2, uint32_t bar) {
  asm volatile("cp.async.bulk.tensor.3d.shared::cluster.global.mbarrier::complete_tx::bytes [%0], [%1, {%3, %4, %5}], [%2];"
               ::"r"(dst), "l"(m), "r"(bar), "r"(c0), "r"(c1), "r"(c2) : "memory");
}
__device__ __forceinline__ void l2pf(const void* p, uint32_t bytes) { asm volatile("cp.async.bulk.prefetch.L2.global [%0], %1;" ::"l"(p), "r"(bytes) : "memory"); }
__device__ __forceinline__ void wg_fence() { asm volatile("wgmma.fence.sync.aligned;" ::: "memory"); }
__device__ __forceinline__ void wg_commit() { asm volatile("wgmma.commit_group.sync.aligned;" ::: "memory"); }
template <int N> __device__ __forceinline__ void wg_wait() { asm volatile("wgmma.wait_group.sync.aligned %0;" ::"n"(N) : "memory"); }
template <int N> __device__ __forceinline__ void regfence(float (&d)[N]) {
#pragma unroll
  for (int i = 0; i < N; i++) asm volatile("" : "+f"(d[i])::"memory");
}
__device__ __forceinline__ void bar_cons() { asm volatile("bar.sync 1, 256;" ::: "memory"); }
__device__ __forceinline__ void bar_ln() { asm volatile("bar.sync 2, 224;" ::: "memory"); }
__device__ __forceinline__ void fence_async() { asm volatile("fence.proxy.async.shared::cta;" ::: "memory"); }
struct Desc { uint32_t lo, hi; };
__device__ __forceinline__ Desc mkdesc(uint32_t base16, uint32_t off, uint32_t lbo, uint32_t sbo, uint32_t swz) {
  return Desc{base16 + ((off >> 4) | ((lbo >> 4) << 16)), (sbo >> 4) | (swz << 30)};
}
__device__ __forceinline__ uint4 ldll(const uint4* p) {
  uint4 v; asm volatile("ld.relaxed.gpu.global.v4.u32 {%0,%1,%2,%3}, [%4];" : "=r"(v.x), "=r"(v.y), "=r"(v.z), "=r"(v.w) : "l"(p) : "memory"); return v;
}
__device__ __forceinline__ uint2 ldll2(const uint2* p) {
  uint2 v; asm volatile("ld.relaxed.gpu.global.v2.u32 {%0,%1}, [%2];" : "=r"(v.x), "=r"(v.y) : "l"(p) : "memory"); return v;
}
__device__ __forceinline__ void stll(uint4* p, uint32_t x, uint32_t y, uint32_t z, uint32_t w) {
  asm volatile("st.relaxed.gpu.global.v4.u32 [%0], {%1,%2,%3,%4};" ::"l"(p), "r"(x), "r"(y), "r"(z), "r"(w) : "memory");
}
__device__ __forceinline__ void stll2(void* p, uint32_t x, uint32_t y) {
  asm volatile("st.relaxed.gpu.global.v2.u32 [%0], {%1,%2};" ::"l"(p), "r"(x), "r"(y) : "memory");
}
__device__ __forceinline__ int laneid() { int l; asm volatile("mov.u32 %0, %%laneid;" : "=r"(l)); return l; }
__device__ __forceinline__ uint32_t tg(uint32_t w, uint32_t tag) { return (w & ~1u) | tag; }
__device__ __forceinline__ uint32_t pack(float lo, float hi) {
  uint32_t r; asm("cvt.rn.bf16x2.f32 %0, %1, %2;" : "=r"(r) : "f"(hi), "f"(lo)); return r;
}
__device__ __forceinline__ float blo(uint32_t w) { return __uint_as_float(w << 16); }
__device__ __forceinline__ float bhi(uint32_t w) { return __uint_as_float(w & 0xffff0000u); }
__device__ __forceinline__ float ex2(float x) { float r; asm("ex2.approx.ftz.f32 %0, %1;" : "=f"(r) : "f"(x)); return r; }
__device__ __forceinline__ float rcp(float x) { float r; asm("rcp.approx.ftz.f32 %0, %1;" : "=f"(r) : "f"(x)); return r; }
__device__ __forceinline__ float qsum(float v) { v += __shfl_xor_sync(~0u, v, 1); v += __shfl_xor_sync(~0u, v, 2); return v; }
__device__ __forceinline__ void sts32(uint32_t a, uint32_t v) { asm volatile("st.shared.u32 [%0], %1;" ::"r"(a), "r"(v) : "memory"); }
__device__ __forceinline__ void sts16(uint32_t a, uint32_t v) { asm volatile("st.shared.u16 [%0], %1;" ::"r"(a), "h"((uint16_t)v) : "memory"); }
__device__ __forceinline__ void sts128(uint32_t a, uint32_t x, uint32_t y, uint32_t z, uint32_t w) {
  asm volatile("st.shared.v4.u32 [%0], {%1,%2,%3,%4};" ::"r"(a), "r"(x), "r"(y), "r"(z), "r"(w) : "memory");
}
__device__ __forceinline__ uint32_t sw128(int row, int col) { return row * 128 + ((((col >> 3) ^ row) & 7) << 4) + (col & 7) * 2; }

__device__ __forceinline__ void wgmma_rs56(float (&d)[28], const uint32_t a0, const uint32_t a1, const uint32_t a2, const uint32_t a3, Desc db, int sd) {
  asm volatile("{.reg .pred p; .reg .b64 da, db; setp.ne.b32 p, %33, 0; mov.b64 db, {%32, %34};\n wgmma.mma_async.sync.aligned.m64n56k16.f32.bf16.bf16 {%0,%1,%2,%3,%4,%5,%6,%7,%8,%9,%10,%11,%12,%13,%14,%15,%16,%17,%18,%19,%20,%21,%22,%23,%24,%25,%26,%27}, {%28,%29,%30,%31}, db, p, 1, 1, 1;}"
   : "+f"(d[0]),"+f"(d[1]),"+f"(d[2]),"+f"(d[3]),"+f"(d[4]),"+f"(d[5]),"+f"(d[6]),"+f"(d[7]),"+f"(d[8]),"+f"(d[9]),"+f"(d[10]),"+f"(d[11]),"+f"(d[12]),"+f"(d[13]),"+f"(d[14]),"+f"(d[15]),"+f"(d[16]),"+f"(d[17]),"+f"(d[18]),"+f"(d[19]),"+f"(d[20]),"+f"(d[21]),"+f"(d[22]),"+f"(d[23]),"+f"(d[24]),"+f"(d[25]),"+f"(d[26]),"+f"(d[27])
   : "r"(a0),"r"(a1),"r"(a2),"r"(a3),"r"(db.lo),"r"(sd),"r"(db.hi));
}
__device__ __forceinline__ void wgmma_rs64(float (&d)[32], const uint32_t a0, const uint32_t a1, const uint32_t a2, const uint32_t a3, Desc db, int sd) {
  asm volatile("{.reg .pred p; .reg .b64 da, db; setp.ne.b32 p, %37, 0; mov.b64 db, {%36, %38};\n wgmma.mma_async.sync.aligned.m64n64k16.f32.bf16.bf16 {%0,%1,%2,%3,%4,%5,%6,%7,%8,%9,%10,%11,%12,%13,%14,%15,%16,%17,%18,%19,%20,%21,%22,%23,%24,%25,%26,%27,%28,%29,%30,%31}, {%32,%33,%34,%35}, db, p, 1, 1, 1;}"
   : "+f"(d[0]),"+f"(d[1]),"+f"(d[2]),"+f"(d[3]),"+f"(d[4]),"+f"(d[5]),"+f"(d[6]),"+f"(d[7]),"+f"(d[8]),"+f"(d[9]),"+f"(d[10]),"+f"(d[11]),"+f"(d[12]),"+f"(d[13]),"+f"(d[14]),"+f"(d[15]),"+f"(d[16]),"+f"(d[17]),"+f"(d[18]),"+f"(d[19]),"+f"(d[20]),"+f"(d[21]),"+f"(d[22]),"+f"(d[23]),"+f"(d[24]),"+f"(d[25]),"+f"(d[26]),"+f"(d[27]),"+f"(d[28]),"+f"(d[29]),"+f"(d[30]),"+f"(d[31])
   : "r"(a0),"r"(a1),"r"(a2),"r"(a3),"r"(db.lo),"r"(sd),"r"(db.hi));
}
__device__ __forceinline__ void wgmma_rs224(float (&d)[112], const uint32_t a0, const uint32_t a1, const uint32_t a2, const uint32_t a3, Desc db, int sd) {
  asm volatile("{.reg .pred p; .reg .b64 da, db; setp.ne.b32 p, %117, 0; mov.b64 db, {%116, %118};\n wgmma.mma_async.sync.aligned.m64n224k16.f32.bf16.bf16 {%0,%1,%2,%3,%4,%5,%6,%7,%8,%9,%10,%11,%12,%13,%14,%15,%16,%17,%18,%19,%20,%21,%22,%23,%24,%25,%26,%27,%28,%29,%30,%31,%32,%33,%34,%35,%36,%37,%38,%39,%40,%41,%42,%43,%44,%45,%46,%47,%48,%49,%50,%51,%52,%53,%54,%55,%56,%57,%58,%59,%60,%61,%62,%63,%64,%65,%66,%67,%68,%69,%70,%71,%72,%73,%74,%75,%76,%77,%78,%79,%80,%81,%82,%83,%84,%85,%86,%87,%88,%89,%90,%91,%92,%93,%94,%95,%96,%97,%98,%99,%100,%101,%102,%103,%104,%105,%106,%107,%108,%109,%110,%111}, {%112,%113,%114,%115}, db, p, 1, 1, 1;}"
   : "+f"(d[0]),"+f"(d[1]),"+f"(d[2]),"+f"(d[3]),"+f"(d[4]),"+f"(d[5]),"+f"(d[6]),"+f"(d[7]),"+f"(d[8]),"+f"(d[9]),"+f"(d[10]),"+f"(d[11]),"+f"(d[12]),"+f"(d[13]),"+f"(d[14]),"+f"(d[15]),"+f"(d[16]),"+f"(d[17]),"+f"(d[18]),"+f"(d[19]),"+f"(d[20]),"+f"(d[21]),"+f"(d[22]),"+f"(d[23]),"+f"(d[24]),"+f"(d[25]),"+f"(d[26]),"+f"(d[27]),"+f"(d[28]),"+f"(d[29]),"+f"(d[30]),"+f"(d[31]),"+f"(d[32]),"+f"(d[33]),"+f"(d[34]),"+f"(d[35]),"+f"(d[36]),"+f"(d[37]),"+f"(d[38]),"+f"(d[39]),"+f"(d[40]),"+f"(d[41]),"+f"(d[42]),"+f"(d[43]),"+f"(d[44]),"+f"(d[45]),"+f"(d[46]),"+f"(d[47]),"+f"(d[48]),"+f"(d[49]),"+f"(d[50]),"+f"(d[51]),"+f"(d[52]),"+f"(d[53]),"+f"(d[54]),"+f"(d[55]),"+f"(d[56]),"+f"(d[57]),"+f"(d[58]),"+f"(d[59]),"+f"(d[60]),"+f"(d[61]),"+f"(d[62]),"+f"(d[63]),"+f"(d[64]),"+f"(d[65]),"+f"(d[66]),"+f"(d[67]),"+f"(d[68]),"+f"(d[69]),"+f"(d[70]),"+f"(d[71]),"+f"(d[72]),"+f"(d[73]),"+f"(d[74]),"+f"(d[75]),"+f"(d[76]),"+f"(d[77]),"+f"(d[78]),"+f"(d[79]),"+f"(d[80]),"+f"(d[81]),"+f"(d[82]),"+f"(d[83]),"+f"(d[84]),"+f"(d[85]),"+f"(d[86]),"+f"(d[87]),"+f"(d[88]),"+f"(d[89]),"+f"(d[90]),"+f"(d[91]),"+f"(d[92]),"+f"(d[93]),"+f"(d[94]),"+f"(d[95]),"+f"(d[96]),"+f"(d[97]),"+f"(d[98]),"+f"(d[99]),"+f"(d[100]),"+f"(d[101]),"+f"(d[102]),"+f"(d[103]),"+f"(d[104]),"+f"(d[105]),"+f"(d[106]),"+f"(d[107]),"+f"(d[108]),"+f"(d[109]),"+f"(d[110]),"+f"(d[111])
   : "r"(a0),"r"(a1),"r"(a2),"r"(a3),"r"(db.lo),"r"(sd),"r"(db.hi));
}
__device__ __forceinline__ void wgmma_ss64(float (&d)[32], Desc da, Desc db, int sd) {
  asm volatile("{.reg .pred p; .reg .b64 da, db; setp.ne.b32 p, %34, 0; mov.b64 da, {%32, %35}; mov.b64 db, {%33, %35};\n wgmma.mma_async.sync.aligned.m64n64k16.f32.bf16.bf16 {%0,%1,%2,%3,%4,%5,%6,%7,%8,%9,%10,%11,%12,%13,%14,%15,%16,%17,%18,%19,%20,%21,%22,%23,%24,%25,%26,%27,%28,%29,%30,%31}, da, db, p, 1, 1, 1, 1;}"
   : "+f"(d[0]),"+f"(d[1]),"+f"(d[2]),"+f"(d[3]),"+f"(d[4]),"+f"(d[5]),"+f"(d[6]),"+f"(d[7]),"+f"(d[8]),"+f"(d[9]),"+f"(d[10]),"+f"(d[11]),"+f"(d[12]),"+f"(d[13]),"+f"(d[14]),"+f"(d[15]),"+f"(d[16]),"+f"(d[17]),"+f"(d[18]),"+f"(d[19]),"+f"(d[20]),"+f"(d[21]),"+f"(d[22]),"+f"(d[23]),"+f"(d[24]),"+f"(d[25]),"+f"(d[26]),"+f"(d[27]),"+f"(d[28]),"+f"(d[29]),"+f"(d[30]),"+f"(d[31])
   : "r"(da.lo),"r"(db.lo),"r"(sd),"r"(db.hi));
}

template <int S, int N, bool SPL = false, int T> __device__ __forceinline__ void ll_issue(uint4 (&v)[T], const uint4* p, int stride, const uint2* p2 = nullptr) {
#pragma unroll
  for (int i = S; i < S + N; i++) {
    if (SPL && i % 7 == 3) { const uint2 lo = ldll2(p2 + i * 64), hi = ldll2(p2 + i * 64 + 32); v[i] = make_uint4(lo.x, lo.y, hi.x, hi.y); }
    else v[i] = ldll(p + i * stride);
  }
}
template <int S, int N, bool SPL, int T> __device__ __forceinline__ void ll_check(uint4 (&v)[T], const uint4* p, int stride, uint32_t tag, const uint2* p2 = nullptr) {
#pragma unroll 1
  for (int it = 0; it < SPIN; it++) {
    uint32_t bad = 0;
#pragma unroll
    for (int i = S; i < S + N; i++) bad |= (v[i].x ^ tag) | ((SPL && i % 7 == 3) ? (v[i].z ^ tag) : 0u);
    if (!__any_sync(~0u, bad & 1)) break;
    ll_issue<S, N, SPL>(v, p, stride, p2);
  }
}
__device__ __forceinline__ void hint_post(uint32_t* p, uint32_t v, int lane) {
  if (lane == 0) asm volatile("st.relaxed.gpu.global.u32 [%0], %1;" ::"l"(p), "r"(v) : "memory");
}
__device__ __forceinline__ void hint_wait(const uint32_t* p, uint32_t s) {
#pragma unroll 1
  for (int it = 0; it < SPIN; it++) {
    uint32_t v; asm volatile("ld.relaxed.gpu.global.u32 %0, [%1];" : "=r"(v) : "l"(p) : "memory");
    if (__all_sync(~0u, v - s < 10u)) break;
  }
}
__device__ __forceinline__ void slice_store(uint4* pf, uint2* ph, const uint32_t (&w)[14], bool odd) {
#pragma unroll
  for (int u = 0; u < 3; u++)
    stll(pf + u * 32, odd ? w[4 * u + 2] : w[4 * u], odd ? w[4 * u + 3] : w[4 * u + 1], odd ? w[4 * u + 4] : w[4 * u + 2], odd ? w[4 * u + 5] : w[4 * u + 3]);
  stll2(ph, odd ? w[0] : w[12], odd ? w[1] : w[13]);
}
template <class F> __device__ __forceinline__ void hedgehog(const float (&d)[28], F sink) {
  const float L2E = 1.4426950408889634f;
#pragma unroll
  for (int r = 0; r < 2; r++)
#pragma unroll
    for (int h = 0; h < 2; h++) {
      float x[7];
#pragma unroll
      for (int p = 0; p < 6; p++) x[p] = d[h * 16 + (p >> 1) * 4 + (p & 1) + 2 * r] * L2E;
      x[6] = d[12 + h + 2 * r] * L2E;
      float mx = x[0], mn = x[0];
#pragma unroll
      for (int p = 1; p < 7; p++) { mx = fmaxf(mx, x[p]); mn = fminf(mn, x[p]); }
      mx = fmaxf(mx, __shfl_xor_sync(~0u, mx, 1)); mn = fminf(mn, __shfl_xor_sync(~0u, mn, 1));
      mx = fmaxf(mx, __shfl_xor_sync(~0u, mx, 2)); mn = fminf(mn, __shfl_xor_sync(~0u, mn, 2));
      float ep[7], en[7], sp = 0.f, sn = 0.f;
#pragma unroll
      for (int p = 0; p < 7; p++) { ep[p] = ex2(x[p] - mx); en[p] = ex2(mn - x[p]); sp += ep[p]; sn += en[p]; }
      sp = rcp(qsum(sp)); sn = rcp(qsum(sn));
#pragma unroll
      for (int p = 0; p < 7; p++) sink(r, h, p, pack(ep[p] * sp, en[p] * sn));
    }
}
__device__ __forceinline__ void phi_gemm(const float (&x)[28], float (&y)[28], uint32_t wphi) {
  uint32_t f[14];
#pragma unroll
  for (int j = 0; j < 14; j++) f[j] = pack(x[2 * j], x[2 * j + 1]);
  wg_fence();
#pragma unroll
  for (int ks = 0; ks < 3; ks++) wgmma_rs56(y, f[4 * ks], f[4 * ks + 1], f[4 * ks + 2], f[4 * ks + 3], mkdesc(wphi >> 4, ks * 2048, 1024, 1024, 1), ks);
  wgmma_rs56(y, f[12], f[13], 0u, 0u, mkdesc(wphi >> 4, 3 * 2048, 1024, 1024, 1), 1);
  wg_commit();
}
__device__ __forceinline__ void ln_publish(uint32_t (&xw)[4][4], float* sLN, int warp, int lane, uint4* fb, uint32_t tag) {
  const int g = lane >> 2;
  float s0 = 0.f, s1 = 0.f;
#pragma unroll
  for (int u = 0; u < 4; u++) {
    stll(fb + XR + u * 32, tg(xw[u][0], tag), xw[u][1], tg(xw[u][2], tag), xw[u][3]);
    s0 += blo(xw[u][0]) + bhi(xw[u][0]) + blo(xw[u][2]) + bhi(xw[u][2]);
    s1 += blo(xw[u][1]) + bhi(xw[u][1]) + blo(xw[u][3]) + bhi(xw[u][3]);
  }
  s0 = qsum(s0) * (1.f / 64); s1 = qsum(s1) * (1.f / 64);
  float v0 = 0.f, v1 = 0.f;
#pragma unroll
  for (int u = 0; u < 4; u++)
#pragma unroll
    for (int k = 0; k < 4; k += 2) {
      float a = blo(xw[u][k]) - s0, b = bhi(xw[u][k]) - s0, c2 = blo(xw[u][k + 1]) - s1, d2 = bhi(xw[u][k + 1]) - s1;
      v0 += a * a + b * b; v1 += c2 * c2 + d2 * d2;
    }
  v0 = qsum(v0); v1 = qsum(v1);
  if ((lane & 3) == 0) { sLN[warp * 16 + g] = s0; sLN[warp * 16 + g + 8] = s1; sLN[112 + warp * 16 + g] = v0; sLN[112 + warp * 16 + g + 8] = v1; }
  bar_ln();
  float m0 = 0.f, m1 = 0.f; v0 = 0.f; v1 = 0.f;
#pragma unroll
  for (int w = 0; w < 7; w++) { m0 += sLN[w * 16 + g]; m1 += sLN[w * 16 + g + 8]; }
  m0 *= (1.f / 7); m1 *= (1.f / 7);
#pragma unroll
  for (int w = 0; w < 7; w++) {
    float a = sLN[w * 16 + g] - m0, b = sLN[w * 16 + g + 8] - m1;
    v0 += sLN[112 + w * 16 + g] + 64.f * a * a; v1 += sLN[112 + w * 16 + g + 8] + 64.f * b * b;
  }
  const float r0 = rsqrtf(v0 * (1.f / 448) + 1e-5f), r1 = rsqrtf(v1 * (1.f / 448) + 1e-5f);
#pragma unroll
  for (int u = 0; u < 4; u++)
    stll(fb + XN + u * 32, tg(pack((blo(xw[u][0]) - m0) * r0, (bhi(xw[u][0]) - m0) * r0), tag), pack((blo(xw[u][1]) - m1) * r1, (bhi(xw[u][1]) - m1) * r1),
         pack((blo(xw[u][2]) - m0) * r0, (bhi(xw[u][2]) - m0) * r0), pack((blo(xw[u][3]) - m1) * r1, (bhi(xw[u][3]) - m1) * r1));
}

__global__ void __launch_bounds__(384, 1)
fused_kernel(const __grid_constant__ CUtensorMap mQKV, const __grid_constant__ CUtensorMap mWO, const __grid_constant__ CUtensorMap mW1,
             const __grid_constant__ CUtensorMap mW2, const __nv_bfloat16* __restrict__ x, const __nv_bfloat16* __restrict__ wphi,
             const __nv_bfloat16* __restrict__ wo, const __nv_bfloat16* __restrict__ w1, const __nv_bfloat16* __restrict__ b1,
             const __nv_bfloat16* __restrict__ w2, const __nv_bfloat16* __restrict__ b2, __nv_bfloat16* __restrict__ out) {
  extern __shared__ __align__(1024) uint8_t sm[];
  const uint32_t sb = s2u(sm);
  const int tid = threadIdx.x, warp = __shfl_sync(~0u, tid >> 5, 0), lane = tid & 31, t = blockIdx.x >> 3, c = blockIdx.x & 7;
  const uint32_t bfull = sb + OFF_BAR, bempty = bfull + 8 * NST;

  if (tid == 256) {
    for (int s = 0; s < NST; s++) { mbar_init(bfull + 8 * s, 1); mbar_init(bempty + 8 * s, 8); }
    asm volatile("fence.mbarrier_init.release.cluster;" ::: "memory");
    fence_async();
  }
  __syncthreads();
  if (warp >= 8) {
    asm volatile("setmaxnreg.dec.sync.aligned.u32 24;");
    auto issue = [&](int i, int s) {
      const uint32_t dst = sb + s * STAGE, bar = bfull + 8 * s;
      mbar_expect(bar, STAGE);
      if (i < 4) {
        tma2d(dst, &mQKV, 448 + 56 * c, 112 * i, bar); tma2d(dst + 7168, &mQKV, 480 + 56 * c, 112 * i, bar);
        tma2d(dst + 14336, &mQKV, 896 + 56 * c, 112 * i, bar); tma2d(dst + 21504, &mQKV, 928 + 56 * c, 112 * i, bar);
      } else if (i >= 8 && i < 15) {
        tma3d(dst, &mW1, 0, 64 * (i - 8), 7 * c, bar);
      } else {
        const CUtensorMap* m = i < 6 ? &mQKV : (i < 8 ? &mWO : &mW2);
        const int n0 = i < 8 ? 56 * c : 64 * (i - 15), k0 = i < 8 ? 224 * (i & 1) : 224 * c;
        tma2d(dst, m, n0, k0, bar); tma2d(dst + 7168, m, n0, k0 + 112, bar);
        tma2d(dst + 14336, m, n0 + 32, k0, bar); tma2d(dst + 21504, m, n0 + 32, k0 + 112, bar);
      }
    };
    if (tid == 256) {
      int s = 0; uint32_t ph = 1;
      for (int n = 0; n < 44; n++) {
        mbar_wait(bempty + 8 * s, ph);
        issue(n >= 22 ? n - 22 : n, s);
        if (++s == NST) { s = 0; ph ^= 1; }
      }
    } else if (warp == 9) {
      mbar_wait(bfull + 8 * 3, 0);
      if (lane == 0) {
        l2pf((const uint8_t*)wo + blockIdx.x * 3136, 3136);
        l2pf((const uint8_t*)w1 + blockIdx.x * 12544, 12544);
        l2pf((const uint8_t*)w2 + blockIdx.x * 12544, 12544);
      }
      if (blockIdx.x < 112) {
        const uint2* wp = (const uint2*)(w1 + (size_t)(lane >> 2) * 1792 + blockIdx.x * 16 + (lane & 3) * 4);
        float s0 = 0.f, s1 = 0.f, s2 = 0.f, s3 = 0.f;
#pragma unroll 8
        for (int i = 0; i < 56; i++) { const uint2 v = __ldg(wp + i * 8 * 448); s0 += blo(v.x); s1 += bhi(v.x); s2 += blo(v.y); s3 += bhi(v.y); }
#pragma unroll 1
        for (int o = 4; o < 32; o <<= 1) { s0 += __shfl_xor_sync(~0u, s0, o); s1 += __shfl_xor_sync(~0u, s1, o); s2 += __shfl_xor_sync(~0u, s2, o); s3 += __shfl_xor_sync(~0u, s3, o); }
        if (lane < 4) stll(g_CS + blockIdx.x * 4 + lane, tg(__float_as_uint(s0), 1), __float_as_uint(s1), __float_as_uint(s2), __float_as_uint(s3));
      }
#pragma unroll 1
      for (int i = 0; i < 2; i++) {
        const int e = lane < 28 ? lane + 28 * i : 0;
        uint4 cv[1];
        ll_issue<0, 1>(cv, g_CS + 56 * c + e, 0); ll_check<0, 1, false>(cv, g_CS + 56 * c + e, 0, 1u);
        const uint2 bb = __ldg((const uint2*)(b1 + 224 * c + 4 * e));
        sts128(sb + OFF_CB + e * 32, cv[0].x, cv[0].y, bb.x << 16, bb.x & 0xffff0000u);
        sts128(sb + OFF_CB + e * 32 + 16, cv[0].z, cv[0].w, bb.y << 16, bb.y & 0xffff0000u);
      }
      asm volatile("bar.arrive 4, 288;" ::: "memory");
    } else if (warp >= 10) {
      const int h = warp - 10;
      uint32_t wv[13];
#pragma unroll
      for (int i = 0; i < 13; i++) { const int e = lane + 32 * i; wv[i] = e < 392 ? __ldg((const uint32_t*)wphi + (2 * c + h) * 392 + e) : 0u; }
#pragma unroll 1
      for (int i = 0; i < 8; i++) sts128(sb + OFF_WPHI + (h * 256 + i * 32 + lane) * 16, 0, 0, 0, 0);
#pragma unroll 1
      for (int i = 0; i < 4; i++) sts128(sb + OFF_PHIK + sw128(h * 128 + i * 32 + lane, 56), 0, 0, 0, 0);
      asm volatile("bar.sync 5, 64;" ::: "memory");
#pragma unroll
      for (int i = 0; i < 13; i++) {
        const int e = lane + 32 * i, d = e / 14, f2 = 2 * (e - 14 * d), k = 28 * h + d;
        if (e < 392) {
          if (f2 < 24) sts32(sb + OFF_WPHI + sw128(k, 32 * h + f2), wv[i]);
          else { sts16(sb + OFF_WPHI + sw128(k, 2 * f2 - 24 + h), wv[i]); sts16(sb + OFF_WPHI + sw128(k, 2 * f2 - 22 + h), wv[i] >> 16); }
        }
      }
      fence_async();
      asm volatile("bar.arrive 3, 320;" ::: "memory");
    }
  } else {
  asm volatile("setmaxnreg.inc.sync.aligned.u32 240;");

  const int wg = warp >> 2, g = lane >> 2, q = lane & 3;
  const int row0 = warp * 16 + g;
#define PTRS const int ln_ = laneid(); \
  uint4* const fm = g_F + ((t * 8 + warp) * 28) * 32 + ln_;            \
  uint4* const fr = g_F + ((t * 8 + c) * 28 + 4 * warp) * 32 + ln_;    \
  uint2* const fe = (uint2*)(fm + ((7 * c) >> 1) * 32) + (c & 1);       \
  uint2* const fo = (uint2*)(fm + ((7 * c + 1) >> 1) * 32) + ((c + 1) & 1); \
  uint4* const sf = fm + (7 * (c >> 1) + 4 * (c & 1)) * 32;             \
  uint2* const f2 = (uint2*)(fm - ln_) + ln_;                           \
  uint2* const sh = f2 + (7 * (c >> 1) + 3) * 64 + 32 * (c & 1);        \
  uint32_t* const hme = g_H + (t * 8 + warp) * 8 + c; \
  const uint32_t* const hrow = g_H + (t * 8 + warp) * 8 + (ln_ & 7); \
  (void)fm; (void)fr; (void)fe; (void)fo; (void)sf; (void)f2; (void)sh; (void)hme; (void)hrow;
#define SL(j, B) (((j) & 1 ? fo : fe) + ((j) >> 1) * 64 + 2 * (B))
  float* sLN = (float*)(sm + OFF_LN);
  const uint32_t sPK = sb + OFF_PHIK, sV = sb + OFF_V, sW = sb + OFF_WPHI;
  #define XOFF(l) ((t * 128 + c * 16 + ((l) >> 2)) * 448 + warp * 64 + 2 * ((l) & 3))
  MARK(0);
  uint32_t xw[4][4];
  if (warp < 7) {
    const uint32_t* xp = (const uint32_t*)(x + XOFF(lane));
#pragma unroll
    for (int u = 0; u < 4; u++) { xw[u][0] = __ldg(xp + u * 8); xw[u][1] = __ldg(xp + u * 8 + 1792); xw[u][2] = __ldg(xp + u * 8 + 4); xw[u][3] = __ldg(xp + u * 8 + 1796); }
  }
  int cs = 0, rs = 0; uint32_t cph = 0;
  auto acquire = [&]() -> uint32_t { mbar_wait(bfull + 8 * cs, cph); const uint32_t a = (sb >> 4) + cs * (STAGE >> 4); if (++cs == NST) { cs = 0; cph ^= 1; } return a; };
  auto release = [&]() { if (lane == 0) mbar_arrive(bempty + 8 * rs); if (++rs == NST) rs = 0; };

#pragma unroll 1
  for (int L = 0; L < 2; L++) {
    const uint32_t tag = 1 - L;
    uint32_t phq[2][2][7];
    const uint32_t hs = 10 * L;
    if (warp < 7) { PTRS ln_publish(xw, sLN, warp, lane, fr, tag); hint_post(hme, hs + 1, lane); }
#pragma unroll
    for (int i = 0; i < 16; i++) xw[i >> 2][i & 3] = 0;
    MARK(1 + L * 19);
    {
      PTRS
      uint4 a[28];
      const uint4* pa = fm + XN;
      hint_wait(g_H + (t * 8 + (lane < 7 ? lane : 0)) * 8 + warp, hs + 1); ll_issue<0, 28>(a, pa, 32);
      MARK(2 + L * 19);
      float ak[28], av[28], aq[28], pp[28];
#define KVSTAGE(i) { ll_check<7 * i, 7, false>(a, pa, 32, tag); const uint32_t st = acquire(); wg_fence(); \
      _Pragma("unroll") for (int ks = 0; ks < 7; ks++) { const uint4 f = a[7 * i + ks]; \
        wgmma_rs56(ak, f.x, f.y, f.z, f.w, mkdesc(st, ks * 1024, 7168, 512, 2), i | ks); \
        wgmma_rs56(av, f.x, f.y, f.z, f.w, mkdesc(st, 14336 + ks * 1024, 7168, 512, 2), i | ks); } \
      wg_commit(); if (i > 0) { wg_wait<1>(); release(); } }
      KVSTAGE(0) KVSTAGE(1) KVSTAGE(2) KVSTAGE(3)
      wg_wait<0>(); release(); regfence(ak); regfence(av);
      MARK(3 + L * 19);
      if (L == 0) asm volatile("bar.sync 3, 320;" ::: "memory");
      phi_gemm(ak, pp, sW);
#pragma unroll
      for (int j = 0; j < 7; j++) {
        const int n = 8 * j + 2 * q, n2 = n < 28 ? n : n + 4;
        sts32(sV + sw128(row0, n2), pack(av[4 * j], av[4 * j + 1])); sts32(sV + sw128(row0 + 8, n2), pack(av[4 * j + 2], av[4 * j + 3]));
      }
      { const int n2 = 28 + 2 * (q & 1) + 32 * (q >> 1); const uint32_t v = (q & 1) ? 0u : 0x3F80u; sts32(sV + sw128(row0, n2), v); sts32(sV + sw128(row0 + 8, n2), v); }
#pragma unroll
      for (int i = 0; i < 2; i++) {
        const uint32_t st = acquire(); wg_fence();
#pragma unroll
        for (int ks = 0; ks < 14; ks++) { const uint4 f = a[14 * i + ks]; wgmma_rs56(aq, f.x, f.y, f.z, f.w, mkdesc(st, ks * 1024, 14336, 512, 2), i | ks); }
        wg_commit();
      }
      wg_wait<2>(); regfence(pp);
      hedgehog(pp, [&](int r, int h, int p, uint32_t v) { sts32(sPK + h * 16384 + sw128(row0 + 8 * r, 8 * p + 2 * q), v); });
      fence_async();
      wg_wait<0>(); release(); release(); regfence(aq);
      bar_cons();
      MARK(4 + L * 19);
      float kv[32];
      wg_fence();
#pragma unroll
      for (int ks = 0; ks < 8; ks++) wgmma_ss64(kv, mkdesc((sPK + wg * 16384) >> 4, ks * 2048, 1024, 1024, 1), mkdesc(sV >> 4, ks * 2048, 1024, 1024, 1), ks);
      wg_commit();
      phi_gemm(aq, pp, sW);
      wg_wait<1>(); regfence(kv);
      const int ln2 = laneid();
#pragma unroll
      for (int u = 0; u < 4; u++) {
        float e[4];
#pragma unroll
        for (int i = 0; i < 4; i++) e[i] = wg ? kv[16 + 4 * u + i] : kv[4 * u + i];
        stll(g_KVP + (c * 16 + t) * 1024 + wg * 512 + u * 128 + (warp & 3) * 32 + ln2, tg(__float_as_uint(e[0]), tag), __float_as_uint(e[1]), __float_as_uint(e[2]), __float_as_uint(e[3]));
      }
      MARK(5 + L * 19);
      bar_cons();
#pragma unroll
      for (int i = 0; i < 4; i++) sts128(sV + (tid + i * 256) * 16, 0, 0, 0, 0);
      wg_wait<0>(); regfence(pp);
      hedgehog(pp, [&](int r, int h, int p, uint32_t v) { phq[r][h][p] = v; });
    }
    MARK(6 + L * 19);
    {
      uint4 k4[4];
      const int ln2 = laneid();
      const uint4* pk = g_KVP + (c * 16 + 4 * (ln2 & 3)) * 1024 + 64 * t + warp * 8 + (ln2 >> 2);
      ll_issue<0, 4>(k4, pk, 1024); ll_check<0, 4, false>(k4, pk, 1024, tag);
      float s0 = 0, s1 = 0, s2 = 0, s3 = 0;
#pragma unroll
      for (int i = 0; i < 4; i++) { s0 += __uint_as_float(k4[i].x); s1 += __uint_as_float(k4[i].y); s2 += __uint_as_float(k4[i].z); s3 += __uint_as_float(k4[i].w); }
      s0 = qsum(s0); s1 = qsum(s1); s2 = qsum(s2); s3 = qsum(s3);
      if (q == 0) stll2(g_KVR + c * 1024 + 64 * t + warp * 8 + (ln2 >> 2), tg(pack(s0, s1), tag), pack(s2, s3));
      MARK(7 + L * 19);
      bar_cons();
      uint2 r[4];
      const uint2* pr = g_KVR + c * 1024 + wg * 512 + (warp & 3) * 32 + ln2;
#pragma unroll 1
      for (int it = 0; it < SPIN; it++) {
        uint32_t bad = 0;
#pragma unroll
        for (int u = 0; u < 4; u++) { r[u] = ldll2(pr + u * 128); bad |= r[u].x ^ tag; }
        if (!__any_sync(~0u, bad & 1)) break;
      }
#pragma unroll
      for (int u = 0; u < 4; u++) {
        const int d = 8 * u + 2 * q;
        if (d < 28) { sts32(sV + sw128(row0, 28 * wg + d), r[u].x); sts32(sV + sw128(row0 + 8, 28 * wg + d), r[u].y); }
        else if (d == 28) {
#pragma unroll
          for (int j = 0; j < 4; j++) { sts16(sV + sw128(row0, 56 + 2 * j + wg), r[u].x); sts16(sV + sw128(row0 + 8, 56 + 2 * j + wg), r[u].y); }
        }
      }
      fence_async();
      bar_cons();
      MARK(8 + L * 19);
      float o[32];
      wg_fence();
#pragma unroll
      for (int ks = 0; ks < 8; ks++) {
        const int h = ks >> 2, p = 2 * (ks & 3);
        wgmma_rs64(o, phq[0][h][p], phq[1][h][p], p < 6 ? phq[0][h][p < 6 ? p + 1 : 0] : 0u, p < 6 ? phq[1][h][p < 6 ? p + 1 : 0] : 0u, mkdesc(sV >> 4, ks * 2048, 1024, 1024, 1), ks);
      }
      wg_commit(); wg_wait<0>(); regfence(o);
      const float iA0 = rcp(o[28] + 1e-6f), iB0 = rcp(o[29] + 1e-6f), iA1 = rcp(o[30] + 1e-6f), iB1 = rcp(o[31] + 1e-6f);
      uint32_t w[14];
      PTRS
#pragma unroll
      for (int j = 0; j < 7; j++) {
        const bool hb = 8 * j + 2 * q >= 28; const float i0 = hb ? iB0 : iA0, i1 = hb ? iB1 : iA1;
        w[2 * j] = pack(o[4 * j] * i0, o[4 * j + 1] * i0); w[2 * j + 1] = pack(o[4 * j + 2] * i1, o[4 * j + 3] * i1);
        if (j == 0 || ((j ^ c) & 1) == 0) w[2 * j] = tg(w[2 * j], tag);
      }
      slice_store(sf + OO, sh + 2 * OO, w, c & 1);
      hint_post(hme, hs + 2, lane);
    }
    MARK(9 + L * 19);
    {
      PTRS
      uint2 xr[7];
#pragma unroll
      for (int j = 0; j < 7; j++) xr[j] = ldll2(SL(j, XR));
      uint4 a[28];
      const uint4* pa = fm + OO;
      hint_wait(hrow, hs + 2);
      MARK(10 + L * 19);
      ll_issue<0, 28, true>(a, pa, 32, f2 + 2 * OO);
      float y[28];
      uint32_t st;
#define WOSTEP(i) { ll_check<7 * i, 7, true>(a, pa, 32, tag, f2 + 2 * OO); if (!(i & 1)) st = acquire(); wg_fence(); \
      _Pragma("unroll") for (int ks = 0; ks < 7; ks++) { const uint4 f = a[7 * i + ks]; \
        wgmma_rs56(y, f.x, f.y, f.z, f.w, mkdesc(st, ((i & 1) * 7 + ks) * 1024, 14336, 512, 2), i | ks); } wg_commit(); }
      WOSTEP(0) WOSTEP(1) WOSTEP(2) WOSTEP(3)
#pragma unroll 1
      for (int it = 0; it < SPIN; it++) {
        uint32_t bad = 0;
#pragma unroll
        for (int j = 0; j < 7; j++) bad |= xr[j].x ^ tag;
        if (!__any_sync(~0u, bad & 1)) break;
#pragma unroll
        for (int j = 0; j < 7; j++) xr[j] = ldll2(SL(j, XR));
      }
      wg_wait<0>(); regfence(y);
      MARK(11 + L * 19);
      float s0 = 0.f, s1 = 0.f;
      uint32_t w[14];
#pragma unroll
      for (int j = 0; j < 7; j++) {
        w[2 * j] = pack(blo(xr[j].x) + y[4 * j], bhi(xr[j].x) + y[4 * j + 1]); w[2 * j + 1] = pack(blo(xr[j].y) + y[4 * j + 2], bhi(xr[j].y) + y[4 * j + 3]);
        if (j == 0 || ((j ^ c) & 1) == 0) w[2 * j] = tg(w[2 * j], tag);
      }
      slice_store(sf + X1, sh + 2 * X1, w, c & 1);
      hint_post(hme, hs + 3, lane);
#pragma unroll
      for (int j = 0; j < 7; j++) {
        y[4 * j] = blo(w[2 * j]); y[4 * j + 1] = bhi(w[2 * j]); y[4 * j + 2] = blo(w[2 * j + 1]); y[4 * j + 3] = bhi(w[2 * j + 1]);
        s0 += y[4 * j] + y[4 * j + 1]; s1 += y[4 * j + 2] + y[4 * j + 3];
      }
      s0 = qsum(s0) * (1.f / 56); s1 = qsum(s1) * (1.f / 56);
      float v0 = 0.f, v1 = 0.f;
#pragma unroll
      for (int j = 0; j < 7; j++) {
        const float d0 = y[4 * j] - s0, d1 = y[4 * j + 1] - s0, d2 = y[4 * j + 2] - s1, d3 = y[4 * j + 3] - s1;
        v0 += d0 * d0 + d1 * d1; v1 += d2 * d2 + d3 * d3;
      }
      v0 = qsum(v0); v1 = qsum(v1);
      if (q == 0) stll(g_ST + ((t * 8 + warp) * 8 + c) * 8 + (ln_ >> 2), tg(__float_as_uint(s0), tag), __float_as_uint(v0), __float_as_uint(s1), __float_as_uint(v1));
    }
    uint32_t hf[56];
    {
      PTRS
      uint4 a[28];
      const uint4* pa = fm + X1;
      hint_wait(hrow, hs + 3);
      MARK(12 + L * 19);
      ll_issue<0, 4, true>(a, pa, 32, f2 + 2 * X1); ll_check<0, 4, true>(a, pa, 32, tag, f2 + 2 * X1); ll_issue<4, 12, true>(a, pa, 32, f2 + 2 * X1);
      release(); release();
      float y[112];
#define F1STAGE(i) { if (i > 0) ll_check<4 * i, 4, true>(a, pa, 32, tag, f2 + 2 * X1); const uint32_t st = acquire(); wg_fence(); \
      _Pragma("unroll") for (int ks = 0; ks < 4; ks++) { const uint4 f = a[4 * i + ks]; \
        wgmma_rs224(y, f.x, f.y, f.z, f.w, mkdesc(st, ks * 1024, 4096, 512, 2), i | ks); } \
      wg_commit(); if (i > 0) { wg_wait<1>(); release(); if (i < 4) ll_issue<(i < 4 ? 4 * i + 12 : 0), 4, true>(a, pa, 32, f2 + 2 * X1); } }
      F1STAGE(0) MARK(13 + L * 19); F1STAGE(1) F1STAGE(2) F1STAGE(3) F1STAGE(4) F1STAGE(5)
      uint4 sv[2];
      const uint4* ps = g_ST + ((t * 8 + warp) * 8 + 2 * (laneid() & 3)) * 8 + (laneid() >> 2);
      ll_issue<0, 2>(sv, ps, 8);
      F1STAGE(6)
      ll_check<0, 2, false>(sv, ps, 8, tag);
      const float ma = __uint_as_float(sv[0].x), mb = __uint_as_float(sv[1].x), mc = __uint_as_float(sv[0].z), md = __uint_as_float(sv[1].z);
      const float m0 = qsum(ma + mb) * 0.125f, m1 = qsum(mc + md) * 0.125f;
      const float v0 = qsum(__uint_as_float(sv[0].y) + __uint_as_float(sv[1].y) + 56.f * ((ma - m0) * (ma - m0) + (mb - m0) * (mb - m0)));
      const float v1 = qsum(__uint_as_float(sv[0].w) + __uint_as_float(sv[1].w) + 56.f * ((mc - m1) * (mc - m1) + (md - m1) * (md - m1)));
      const float r0 = rsqrtf(v0 * (1.f / 448) + 1e-5f), r1 = rsqrtf(v1 * (1.f / 448) + 1e-5f);
      const float n0 = -m0 * r0, n1 = -m1 * r1;
      if (L == 0) asm volatile("bar.sync 4, 288;" ::: "memory");
      wg_wait<0>(); release(); regfence(y);
      MARK(14 + L * 19);
#pragma unroll
      for (int j = 0; j < 28; j++) {
        const float4 cb = *(const float4*)(sm + OFF_CB + (j * 4 + q) * 16);
        const float h0 = fmaxf(fmaf(y[4 * j], r0, fmaf(n0, cb.x, cb.z)), 0.f), h1 = fmaxf(fmaf(y[4 * j + 1], r0, fmaf(n0, cb.y, cb.w)), 0.f);
        const float h2 = fmaxf(fmaf(y[4 * j + 2], r1, fmaf(n1, cb.x, cb.z)), 0.f), h3 = fmaxf(fmaf(y[4 * j + 3], r1, fmaf(n1, cb.y, cb.w)), 0.f);
        hf[2 * j] = pack(h0 * h0, h1 * h1); hf[2 * j + 1] = pack(h2 * h2, h3 * h3);
      }
    }
    MARK(15 + L * 19);
    {
      PTRS
      float ya[32], yb[32];
      uint4* pp = g_P + ((t * 8 + warp) * 8 + c) * 28 * 32 + ln_;
#define F2STORE(j, Y) { regfence(Y); _Pragma("unroll") for (int u = 0; u < 4; u++) \
      stll(pp + (4 * (j) + u) * 32, tg(pack(Y[8 * u], Y[8 * u + 1]), tag), pack(Y[8 * u + 2], Y[8 * u + 3]), pack(Y[8 * u + 4], Y[8 * u + 5]), pack(Y[8 * u + 6], Y[8 * u + 7])); hint_post(hme, hs + (4 + (j)), lane); }
#define F2PASS(j, Y, Z) { const uint32_t st = acquire(); wg_fence(); \
      _Pragma("unroll") for (int ks = 0; ks < 14; ks++) wgmma_rs64(Y, hf[4 * ks], hf[4 * ks + 1], hf[4 * ks + 2], hf[4 * ks + 3], mkdesc(st, ks * 1024, 14336, 512, 2), ks); \
      wg_commit(); if (j > 0) { wg_wait<1>(); release(); F2STORE(j - 1, Z) } }
      F2PASS(0, ya, yb) F2PASS(1, yb, ya) F2PASS(2, ya, yb) F2PASS(3, yb, ya) F2PASS(4, ya, yb) F2PASS(5, yb, ya) F2PASS(6, ya, yb)
      wg_wait<0>(); release(); F2STORE(6, ya)
    }
    MARK(16 + L * 19);
    if (warp < 7) {
      PTRS
      uint4 x1[4], p[32];
      uint32_t bw[8];
#pragma unroll
      for (int u = 0; u < 4; u++) {
        const bool spl = (4 * warp + u) % 7 == 3;
        const uint2* p0 = (const uint2*)(fr + X1 + u * 32) - (spl ? lane : 0);
        const uint2 lo = ldll2(p0), hi = ldll2(p0 + (spl ? 32 : 1)); x1[u] = make_uint4(lo.x, lo.y, hi.x, hi.y);
      }
#pragma unroll
      for (int i = 0; i < 8; i++) bw[i] = __ldg((const uint32_t*)(b2 + warp * 64 + i * 8 + 2 * q));
      const uint4* pp = g_P + ((t * 8 + c) * 8 * 28 + 4 * warp) * 32 + ln_;
      hint_wait(g_H + (t * 8 + c) * 8 + (lane & 7), hs + 4 + warp);
      ll_issue<0, 8>(p, pp + 96, 896);
      ll_issue<8, 8>(p, pp + 64 - 8 * 896, 896); ll_issue<16, 8>(p, pp + 32 - 16 * 896, 896); ll_issue<24, 8>(p, pp - 24 * 896, 896);
      MARK(17 + L * 19);
#define REDU(u, S) { ll_check<S, 8, false>(p, pp + u * 32 - S * 896, 896, tag); \
      float e[8] = {blo(x1[u].x) + blo(bw[2 * u]), bhi(x1[u].x) + bhi(bw[2 * u]), blo(x1[u].y) + blo(bw[2 * u]), bhi(x1[u].y) + bhi(bw[2 * u]), \
                    blo(x1[u].z) + blo(bw[2 * u + 1]), bhi(x1[u].z) + bhi(bw[2 * u + 1]), blo(x1[u].w) + blo(bw[2 * u + 1]), bhi(x1[u].w) + bhi(bw[2 * u + 1])}; \
      _Pragma("unroll") for (int i = S; i < S + 8; i++) { e[0] += blo(p[i].x); e[1] += bhi(p[i].x); e[2] += blo(p[i].y); e[3] += bhi(p[i].y); \
        e[4] += blo(p[i].z); e[5] += bhi(p[i].z); e[6] += blo(p[i].w); e[7] += bhi(p[i].w); } \
      xw[u][0] = pack(e[0], e[1]); xw[u][1] = pack(e[2], e[3]); xw[u][2] = pack(e[4], e[5]); xw[u][3] = pack(e[6], e[7]); }
      REDU(3, 0) REDU(2, 8) REDU(1, 16) REDU(0, 24)
    }
    MARK(18 + L * 19);
  }
  if (warp < 7) {
    uint32_t* op = (uint32_t*)(out + XOFF(laneid()));
#pragma unroll
    for (int u = 0; u < 4; u++) { op[u * 8] = xw[u][0]; op[u * 8 + 1792] = xw[u][1]; op[u * 8 + 4] = xw[u][2]; op[u * 8 + 1796] = xw[u][3]; }
  } else if (blockIdx.x < 112 && lane < 4) stll(g_CS + blockIdx.x * 4 + lane, 0, 0, 0, 0);
  MARK(38);
  }
}

typedef CUresult (*EncFn)(CUtensorMap*, CUtensorMapDataType, cuuint32_t, void*, const cuuint64_t*, const cuuint64_t*, const cuuint32_t*, const cuuint32_t*,
                          CUtensorMapInterleave, CUtensorMapSwizzle, CUtensorMapL2promotion, CUtensorMapFloatOOBfill);

extern "C" void kernel_launch(void* const* d_in, const int* in_sizes, int n_in, void* d_out, int out_size) {
  static EncFn enc = nullptr;
  if (!enc) {
    void* fn = nullptr; cudaDriverEntryPointQueryResult qr;
    cudaGetDriverEntryPoint("cuTensorMapEncodeTiled", &fn, cudaEnableDefault, &qr);
    enc = (EncFn)fn;
    cudaFuncSetAttribute(fused_kernel, cudaFuncAttributeMaxDynamicSharedMemorySize, SMEM_BYTES);
  }
  CUtensorMap mQKV, mWO, mW1, mW2;
  const cuuint32_t es[3] = {1, 1, 1};
  auto enc2 = [&](CUtensorMap* m, void* p, cuuint64_t cols, cuuint64_t rows) {
    const cuuint64_t dims[2] = {cols, rows}, str[1] = {cols * 2}; const cuuint32_t box[2] = {32, 112};
    enc(m, CU_TENSOR_MAP_DATA_TYPE_BFLOAT16, 2, p, dims, str, box, es, CU_TENSOR_MAP_INTERLEAVE_NONE, CU_TENSOR_MAP_SWIZZLE_64B,
        CU_TENSOR_MAP_L2_PROMOTION_L2_128B, CU_TENSOR_MAP_FLOAT_OOB_FILL_NONE);
  };
  enc2(&mQKV, d_in[1], 1344, 448); enc2(&mWO, d_in[3], 448, 448); enc2(&mW2, d_in[7], 448, 1792);
  {
    const cuuint64_t dims[3] = {32, 448, 56}, str[2] = {3584, 64}; const cuuint32_t box[3] = {32, 64, 7};
    enc(&mW1, CU_TENSOR_MAP_DATA_TYPE_BFLOAT16, 3, d_in[5], dims, str, box, es, CU_TENSOR_MAP_INTERLEAVE_NONE, CU_TENSOR_MAP_SWIZZLE_64B,
        CU_TENSOR_MAP_L2_PROMOTION_L2_128B, CU_TENSOR_MAP_FLOAT_OOB_FILL_NONE);
  }
  typedef const __nv_bfloat16* BP;
  fused_kernel<<<128, 384, SMEM_BYTES>>>(mQKV, mWO, mW1, mW2, (BP)d_in[0], (BP)d_in[2], (BP)d_in[3], (BP)d_in[5], (BP)d_in[6], (BP)d_in[7], (BP)d_in[8],
                                         (__nv_bfloat16*)d_out);
}
```

```cpp
#include <cuda_runtime.h>
#include <cuda_bf16.h>
#include <cuda.h>
#include <stdint.h>

constexpr int NST = 6, STAGE = 28672;
constexpr int OFF_PHIK = NST * STAGE;
constexpr int OFF_V = OFF_PHIK + 32768;
constexpr int OFF_WPHI = OFF_V + 16384;
constexpr int OFF_CB = OFF_WPHI + 7168;
constexpr int OFF_BAR = OFF_CB + 3584;
constexpr int SMEM_BYTES = OFF_BAR + 16 * NST;
constexpr int FR = 16 * 8 * 28 * 32;
constexpr int SPIN = 1 << 18;

__device__ uint4 g_F[4 * FR];
constexpr int XN = 0, XR = FR, OO = 2 * FR, X1 = 3 * FR;
__device__ uint4 g_P[8 * FR];
__device__ uint4 g_ST[16 * 8 * 8 * 8];
__device__ uint4 g_KVP[8 * 16 * 1024];
__device__ uint2 g_KVR[8 * 1024];
__device__ uint4 g_CS[448];
__device__ uint32_t g_H[16 * 8 * 8];
#define MARK(i)

__device__ __forceinline__ uint32_t s2u(const void* p) { return (uint32_t)__cvta_generic_to_shared(p); }
__device__ __forceinline__ void mbar_init(uint32_t b, uint32_t c) { asm volatile("mbarrier.init.shared::cta.b64 [%0], %1;" ::"r"(b), "r"(c)); }
__device__ __forceinline__ void mbar_expect(uint32_t b, uint32_t tx) { asm volatile("mbarrier.arrive.expect_tx.shared::cta.b64 _, [%0], %1;" ::"r"(b), "r"(tx) : "memory"); }
__device__ __forceinline__ void mbar_arrive(uint32_t b) { asm volatile("mbarrier.arrive.shared::cta.b64 _, [%0];" ::"r"(b) : "memory"); }
__device__ __forceinline__ void mbar_wait(uint32_t b, uint32_t ph) {
  uint32_t ok = 0;
#pragma unroll 1
  for (int it = 0; it < SPIN && !ok; it++)
    asm volatile("{.reg .pred p; mbarrier.try_wait.parity.shared::cta.b64 p,[%1],%2; selp.u32 %0,1,0,p;}" : "=r"(ok) : "r"(b), "r"(ph) : "memory");
}
__device__ __forceinline__ void tma2d(uint32_t dst, const CUtensorMap* m, int c0, int c1, uint32_t bar) {
  asm volatile("cp.async.bulk.tensor.2d.shared::cluster.global.mbarrier::complete_tx::bytes [%0], [%1, {%3, %4}], [%2];"
               ::"r"(dst), "l"(m), "r"(bar), "r"(c0), "r"(c1) : "memory");
}
__device__ __forceinline__ void tma3d(uint32_t dst, const CUtensorMap* m, int c0, int c1, int c2, uint32_t bar) {
  asm volatile("cp.async.bulk.tensor.3d.shared::cluster.global.mbarrier::complete_tx::bytes [%0], [%1, {%3, %4, %5}], [%2];"
               ::"r"(dst), "l"(m), "r"(bar), "r"(c0), "r"(c1), "r"(c2) : "memory");
}
__device__ __forceinline__ void l2pf(const void* p, uint32_t bytes) { asm volatile("cp.async.bulk.prefetch.L2.global [%0], %1;" ::"l"(p), "r"(bytes) : "memory"); }
__device__ __forceinline__ void wg_fence() { asm volatile("wgmma.fence.sync.aligned;" ::: "memory"); }
__device__ __forceinline__ void wg_commit() { asm volatile("wgmma.commit_group.sync.aligned;" ::: "memory"); }
template <int N> __device__ __forceinline__ void wg_wait() { asm volatile("wgmma.wait_group.sync.aligned %0;" ::"n"(N) : "memory"); }
template <int N> __device__ __forceinline__ void regfence(float (&d)[N]) {
#pragma unroll
  for (int i = 0; i < N; i++) asm volatile("" : "+f"(d[i])::"memory");
}
__device__ __forceinline__ void bar_cons() { asm volatile("bar.sync 1, 256;" ::: "memory"); }
__device__ __forceinline__ void fence_async() { asm volatile("fence.proxy.async.shared::cta;" ::: "memory"); }
struct Desc { uint32_t lo, hi; };
__device__ __forceinline__ Desc mkdesc(uint32_t base16, uint32_t off, uint32_t lbo, uint32_t sbo, uint32_t swz) {
  return Desc{base16 + ((off >> 4) | ((lbo >> 4) << 16)), (sbo >> 4) | (swz << 30)};
}
__device__ __forceinline__ uint4 ldll(const uint4* p) {
  uint4 v; asm volatile("ld.relaxed.gpu.global.v4.u32 {%0,%1,%2,%3}, [%4];" : "=r"(v.x), "=r"(v.y), "=r"(v.z), "=r"(v.w) : "l"(p) : "memory"); return v;
}
__device__ __forceinline__ uint2 ldll2(const uint2* p) {
  uint2 v; asm volatile("ld.relaxed.gpu.global.v2.u32 {%0,%1}, [%2];" : "=r"(v.x), "=r"(v.y) : "l"(p) : "memory"); return v;
}
__device__ __forceinline__ void stll(uint4* p, uint32_t x, uint32_t y, uint32_t z, uint32_t w) {
  asm volatile("st.relaxed.gpu.global.v4.u32 [%0], {%1,%2,%3,%4};" ::"l"(p), "r"(x), "r"(y), "r"(z), "r"(w) : "memory");
}
__device__ __forceinline__ void stll2(void* p, uint32_t x, uint32_t y) {
  asm volatile("st.relaxed.gpu.global.v2.u32 [%0], {%1,%2};" ::"l"(p), "r"(x), "r"(y) : "memory");
}
__device__ __forceinline__ int laneid() { int l; asm volatile("mov.u32 %0, %%laneid;" : "=r"(l)); return l; }
__device__ __forceinline__ uint32_t tg(uint32_t w, uint32_t tag) { return (w & ~1u) | tag; }
__device__ __forceinline__ uint32_t pack(float lo, float hi) {
  uint32_t r; asm("cvt.rn.bf16x2.f32 %0, %1, %2;" : "=r"(r) : "f"(hi), "f"(lo)); return r;
}
__device__ __forceinline__ float blo(uint32_t w) { return __uint_as_float(w << 16); }
__device__ __forceinline__ float bhi(uint32_t w) { return __uint_as_float(w & 0xffff0000u); }
__device__ __forceinline__ float ex2(float x) { float r; asm("ex2.approx.ftz.f32 %0, %1;" : "=f"(r) : "f"(x)); return r; }
__device__ __forceinline__ float rcp(float x) { float r; asm("rcp.approx.ftz.f32 %0, %1;" : "=f"(r) : "f"(x)); return r; }
__device__ __forceinline__ float qsum(float v) { v += __shfl_xor_sync(~0u, v, 1); v += __shfl_xor_sync(~0u, v, 2); return v; }
__device__ __forceinline__ void sts32(uint32_t a, uint32_t v) { asm volatile("st.shared.u32 [%0], %1;" ::"r"(a), "r"(v) : "memory"); }
__device__ __forceinline__ void sts16(uint32_t a, uint32_t v) { asm volatile("st.shared.u16 [%0], %1;" ::"r"(a), "h"((uint16_t)v) : "memory"); }
__device__ __forceinline__ void sts128(uint32_t a, uint32_t x, uint32_t y, uint32_t z, uint32_t w) {
  asm volatile("st.shared.v4.u32 [%0], {%1,%2,%3,%4};" ::"r"(a), "r"(x), "r"(y), "r"(z), "r"(w) : "memory");
}
__device__ __forceinline__ uint32_t sw128(int row, int col) { return row * 128 + ((((col >> 3) ^ row) & 7) << 4) + (col & 7) * 2; }

__device__ __forceinline__ void wgmma_rs56(float (&d)[28], const uint32_t a0, const uint32_t a1, const uint32_t a2, const uint32_t a3, Desc db, int sd) {
  asm volatile("{.reg .pred p; .reg .b64 da, db; setp.ne.b32 p, %33, 0; mov.b64 db, {%32, %34};\n wgmma.mma_async.sync.aligned.m64n56k16.f32.bf16.bf16 {%0,%1,%2,%3,%4,%5,%6,%7,%8,%9,%10,%11,%12,%13,%14,%15,%16,%17,%18,%19,%20,%21,%22,%23,%24,%25,%26,%27}, {%28,%29,%30,%31}, db, p, 1, 1, 1;}"
   : "+f"(d[0]),"+f"(d[1]),"+f"(d[2]),"+f"(d[3]),"+f"(d[4]),"+f"(d[5]),"+f"(d[6]),"+f"(d[7]),"+f"(d[8]),"+f"(d[9]),"+f"(d[10]),"+f"(d[11]),"+f"(d[12]),"+f"(d[13]),"+f"(d[14]),"+f"(d[15]),"+f"(d[16]),"+f"(d[17]),"+f"(d[18]),"+f"(d[19]),"+f"(d[20]),"+f"(d[21]),"+f"(d[22]),"+f"(d[23]),"+f"(d[24]),"+f"(d[25]),"+f"(d[26]),"+f"(d[27])
   : "r"(a0),"r"(a1),"r"(a2),"r"(a3),"r"(db.lo),"r"(sd),"r"(db.hi));
}
__device__ __forceinline__ void wgmma_rs64(float (&d)[32], const uint32_t a0, const uint32_t a1, const uint32_t a2, const uint32_t a3, Desc db, int sd) {
  asm volatile("{.reg .pred p; .reg .b64 da, db; setp.ne.b32 p, %37, 0; mov.b64 db, {%36, %38};\n wgmma.mma_async.sync.aligned.m64n64k16.f32.bf16.bf16 {%0,%1,%2,%3,%4,%5,%6,%7,%8,%9,%10,%11,%12,%13,%14,%15,%16,%17,%18,%19,%20,%21,%22,%23,%24,%25,%26,%27,%28,%29,%30,%31}, {%32,%33,%34,%35}, db, p, 1, 1, 1;}"
   : "+f"(d[0]),"+f"(d[1]),"+f"(d[2]),"+f"(d[3]),"+f"(d[4]),"+f"(d[5]),"+f"(d[6]),"+f"(d[7]),"+f"(d[8]),"+f"(d[9]),"+f"(d[10]),"+f"(d[11]),"+f"(d[12]),"+f"(d[13]),"+f"(d[14]),"+f"(d[15]),"+f"(d[16]),"+f"(d[17]),"+f"(d[18]),"+f"(d[19]),"+f"(d[20]),"+f"(d[21]),"+f"(d[22]),"+f"(d[23]),"+f"(d[24]),"+f"(d[25]),"+f"(d[26]),"+f"(d[27]),"+f"(d[28]),"+f"(d[29]),"+f"(d[30]),"+f"(d[31])
   : "r"(a0),"r"(a1),"r"(a2),"r"(a3),"r"(db.lo),"r"(sd),"r"(db.hi));
}
__device__ __forceinline__ void wgmma_rs224(float (&d)[112], const uint32_t a0, const uint32_t a1, const uint32_t a2, const uint32_t a3, Desc db, int sd) {
  asm volatile("{.reg .pred p; .reg .b64 da, db; setp.ne.b32 p, %117, 0; mov.b64 db, {%116, %118};\n wgmma.mma_async.sync.aligned.m64n224k16.f32.bf16.bf16 {%0,%1,%2,%3,%4,%5,%6,%7,%8,%9,%10,%11,%12,%13,%14,%15,%16,%17,%18,%19,%20,%21,%22,%23,%24,%25,%26,%27,%28,%29,%30,%31,%32,%33,%34,%35,%36,%37,%38,%39,%40,%41,%42,%43,%44,%45,%46,%47,%48,%49,%50,%51,%52,%53,%54,%55,%56,%57,%58,%59,%60,%61,%62,%63,%64,%65,%66,%67,%68,%69,%70,%71,%72,%73,%74,%75,%76,%77,%78,%79,%80,%81,%82,%83,%84,%85,%86,%87,%88,%89,%90,%91,%92,%93,%94,%95,%96,%97,%98,%99,%100,%101,%102,%103,%104,%105,%106,%107,%108,%109,%110,%111}, {%112,%113,%114,%115}, db, p, 1, 1, 1;}"
   : "+f"(d[0]),"+f"(d[1]),"+f"(d[2]),"+f"(d[3]),"+f"(d[4]),"+f"(d[5]),"+f"(d[6]),"+f"(d[7]),"+f"(d[8]),"+f"(d[9]),"+f"(d[10]),"+f"(d[11]),"+f"(d[12]),"+f"(d[13]),"+f"(d[14]),"+f"(d[15]),"+f"(d[16]),"+f"(d[17]),"+f"(d[18]),"+f"(d[19]),"+f"(d[20]),"+f"(d[21]),"+f"(d[22]),"+f"(d[23]),"+f"(d[24]),"+f"(d[25]),"+f"(d[26]),"+f"(d[27]),"+f"(d[28]),"+f"(d[29]),"+f"(d[30]),"+f"(d[31]),"+f"(d[32]),"+f"(d[33]),"+f"(d[34]),"+f"(d[35]),"+f"(d[36]),"+f"(d[37]),"+f"(d[38]),"+f"(d[39]),"+f"(d[40]),"+f"(d[41]),"+f"(d[42]),"+f"(d[43]),"+f"(d[44]),"+f"(d[45]),"+f"(d[46]),"+f"(d[47]),"+f"(d[48]),"+f"(d[49]),"+f"(d[50]),"+f"(d[51]),"+f"(d[52]),"+f"(d[53]),"+f"(d[54]),"+f"(d[55]),"+f"(d[56]),"+f"(d[57]),"+f"(d[58]),"+f"(d[59]),"+f"(d[60]),"+f"(d[61]),"+f"(d[62]),"+f"(d[63]),"+f"(d[64]),"+f"(d[65]),"+f"(d[66]),"+f"(d[67]),"+f"(d[68]),"+f"(d[69]),"+f"(d[70]),"+f"(d[71]),"+f"(d[72]),"+f"(d[73]),"+f"(d[74]),"+f"(d[75]),"+f"(d[76]),"+f"(d[77]),"+f"(d[78]),"+f"(d[79]),"+f"(d[80]),"+f"(d[81]),"+f"(d[82]),"+f"(d[83]),"+f"(d[84]),"+f"(d[85]),"+f"(d[86]),"+f"(d[87]),"+f"(d[88]),"+f"(d[89]),"+f"(d[90]),"+f"(d[91]),"+f"(d[92]),"+f"(d[93]),"+f"(d[94]),"+f"(d[95]),"+f"(d[96]),"+f"(d[97]),"+f"(d[98]),"+f"(d[99]),"+f"(d[100]),"+f"(d[101]),"+f"(d[102]),"+f"(d[103]),"+f"(d[104]),"+f"(d[105]),"+f"(d[106]),"+f"(d[107]),"+f"(d[108]),"+f"(d[109]),"+f"(d[110]),"+f"(d[111])
   : "r"(a0),"r"(a1),"r"(a2),"r"(a3),"r"(db.lo),"r"(sd),"r"(db.hi));
}
__device__ __forceinline__ void wgmma_ss64(float (&d)[32], Desc da, Desc db, int sd) {
  asm volatile("{.reg .pred p; .reg .b64 da, db; setp.ne.b32 p, %34, 0; mov.b64 da, {%32, %35}; mov.b64 db, {%33, %35};\n wgmma.mma_async.sync.aligned.m64n64k16.f32.bf16.bf16 {%0,%1,%2,%3,%4,%5,%6,%7,%8,%9,%10,%11,%12,%13,%14,%15,%16,%17,%18,%19,%20,%21,%22,%23,%24,%25,%26,%27,%28,%29,%30,%31}, da, db, p, 1, 1, 1, 1;}"
   : "+f"(d[0]),"+f"(d[1]),"+f"(d[2]),"+f"(d[3]),"+f"(d[4]),"+f"(d[5]),"+f"(d[6]),"+f"(d[7]),"+f"(d[8]),"+f"(d[9]),"+f"(d[10]),"+f"(d[11]),"+f"(d[12]),"+f"(d[13]),"+f"(d[14]),"+f"(d[15]),"+f"(d[16]),"+f"(d[17]),"+f"(d[18]),"+f"(d[19]),"+f"(d[20]),"+f"(d[21]),"+f"(d[22]),"+f"(d[23]),"+f"(d[24]),"+f"(d[25]),"+f"(d[26]),"+f"(d[27]),"+f"(d[28]),"+f"(d[29]),"+f"(d[30]),"+f"(d[31])
   : "r"(da.lo),"r"(db.lo),"r"(sd),"r"(db.hi));
}

template <int S, int N, bool SPL = false, int T> __device__ __forceinline__ void ll_issue(uint4 (&v)[T], const uint4* p, int stride, const uint2* p2 = nullptr) {
#pragma unroll
  for (int i = S; i < S + N; i++) {
    if (SPL && i % 7 == 3) { const uint2 lo = ldll2(p2 + i * 64), hi = ldll2(p2 + i * 64 + 32); v[i] = make_uint4(lo.x, lo.y, hi.x, hi.y); }
    else v[i] = ldll(p + i * stride);
  }
}
template <int S, int N, bool SPL, int T> __device__ __forceinline__ void ll_check(uint4 (&v)[T], const uint4* p, int stride, uint32_t tag, const uint2* p2 = nullptr) {
#pragma unroll 1
  for (int it = 0; it < SPIN; it++) {
    uint32_t bad = 0;
#pragma unroll
    for (int i = S; i < S + N; i++) bad |= (v[i].x ^ tag) | ((SPL && i % 7 == 3) ? (v[i].z ^ tag) : 0u);
    if (!__any_sync(~0u, bad & 1)) break;
    ll_issue<S, N, SPL>(v, p, stride, p2);
  }
}
__device__ __forceinline__ void hint_post(uint32_t* p, uint32_t v, int lane) {
  if (lane == 0) asm volatile("st.relaxed.gpu.global.u32 [%0], %1;" ::"l"(p), "r"(v) : "memory");
}
__device__ __forceinline__ void hint_wait(const uint32_t* p, uint32_t s) {
#pragma unroll 1
  for (int it = 0; it < SPIN; it++) {
    uint32_t v; asm volatile("ld.relaxed.gpu.global.u32 %0, [%1];" : "=r"(v) : "l"(p) : "memory");
    if (__all_sync(~0u, v - s < 10u)) break;
  }
}
__device__ __forceinline__ void slice_store(uint4* pf, uint2* ph, const uint32_t (&w)[14], bool odd) {
#pragma unroll
  for (int u = 0; u < 3; u++)
    stll(pf + u * 32, odd ? w[4 * u + 2] : w[4 * u], odd ? w[4 * u + 3] : w[4 * u + 1], odd ? w[4 * u + 4] : w[4 * u + 2], odd ? w[4 * u + 5] : w[4 * u + 3]);
  stll2(ph, odd ? w[0] : w[12], odd ? w[1] : w[13]);
}
template <int R0, int R1, class F> __device__ __forceinline__ void hedgehog(const float (&d)[28], F sink) {
  const float L2E = 1.4426950408889634f;
#pragma unroll
  for (int r = R0; r < R1; r++)
#pragma unroll
    for (int h = 0; h < 2; h++) {
      float x[7];
#pragma unroll
      for (int p = 0; p < 6; p++) x[p] = d[h * 16 + (p >> 1) * 4 + (p & 1) + 2 * r] * L2E;
      x[6] = d[12 + h + 2 * r] * L2E;
      float mx = x[0], mn = x[0];
#pragma unroll
      for (int p = 1; p < 7; p++) { mx = fmaxf(mx, x[p]); mn = fminf(mn, x[p]); }
      mx = fmaxf(mx, __shfl_xor_sync(~0u, mx, 1)); mn = fminf(mn, __shfl_xor_sync(~0u, mn, 1));
      mx = fmaxf(mx, __shfl_xor_sync(~0u, mx, 2)); mn = fminf(mn, __shfl_xor_sync(~0u, mn, 2));
      float ep[7], en[7], sp = 0.f, sn = 0.f;
#pragma unroll
      for (int p = 0; p < 7; p++) { ep[p] = ex2(x[p] - mx); en[p] = ex2(mn - x[p]); sp += ep[p]; sn += en[p]; }
      sp = rcp(qsum(sp)); sn = rcp(qsum(sn));
#pragma unroll
      for (int p = 0; p < 7; p++) sink(r, h, p, pack(ep[p] * sp, en[p] * sn));
    }
}
__device__ __forceinline__ void phi_gemm(const float (&x)[28], float (&y)[28], uint32_t wphi) {
  uint32_t f[14];
#pragma unroll
  for (int j = 0; j < 14; j++) f[j] = pack(x[2 * j], x[2 * j + 1]);
  wg_fence();
#pragma unroll
  for (int ks = 0; ks < 3; ks++) wgmma_rs56(y, f[4 * ks], f[4 * ks + 1], f[4 * ks + 2], f[4 * ks + 3], mkdesc(wphi >> 4, ks * 2048, 1024, 1024, 1), ks);
  wgmma_rs56(y, f[12], f[13], 0u, 0u, mkdesc(wphi >> 4, 3 * 2048, 1024, 1024, 1), 1);
  wg_commit();
}
__device__ __forceinline__ void ln_publish(uint32_t (&xw)[4][4], float* sLN, int warp, int lane, uint4* fb, uint32_t tag) {
  const int g = lane >> 2; const bool full = warp < 4;
  float s0 = 0.f, s1 = 0.f;
#pragma unroll
  for (int u = 0; u < 4; u++) {
    s0 += (blo(xw[u][0]) + bhi(xw[u][0])) + (blo(xw[u][2]) + bhi(xw[u][2]));
    s1 += (blo(xw[u][1]) + bhi(xw[u][1])) + (blo(xw[u][3]) + bhi(xw[u][3]));
  }
  const float rc = full ? 1.f / 64 : 1.f / 48;
  s0 = qsum(s0); s1 = qsum(s1);
  const float a0 = s0 * rc, a1 = s1 * rc;
  float v0 = 0.f, v1 = 0.f;
#pragma unroll
  for (int u = 0; u < 4; u++)
    if (u < 3 || full) {
#pragma unroll
      for (int k = 0; k < 4; k += 2) {
        float a = blo(xw[u][k]) - a0, b = bhi(xw[u][k]) - a0, c2 = blo(xw[u][k + 1]) - a1, d2 = bhi(xw[u][k + 1]) - a1;
        v0 += a * a + b * b; v1 += c2 * c2 + d2 * d2;
      }
    }
  v0 = qsum(v0); v1 = qsum(v1);
  if ((lane & 3) == 0) *(float4*)(sLN + (g * 8 + warp) * 4) = make_float4(s0, v0, s1, v1);
  bar_cons();
  const float4 ea = *(const float4*)(sLN + (g * 8 + (lane & 3)) * 4), eb = *(const float4*)(sLN + (g * 8 + 4 + (lane & 3)) * 4);
  const float m0 = qsum(ea.x + eb.x) * (1.f / 448), m1 = qsum(ea.z + eb.z) * (1.f / 448);
  const float d0 = ea.x * (1.f / 64) - m0, d1 = eb.x * (1.f / 48) - m0, d2 = ea.z * (1.f / 64) - m1, d3 = eb.z * (1.f / 48) - m1;
  v0 = qsum(ea.y + eb.y + 64.f * d0 * d0 + 48.f * d1 * d1); v1 = qsum(ea.w + eb.w + 64.f * d2 * d2 + 48.f * d3 * d3);
  const float r0 = rsqrtf(v0 * (1.f / 448) + 1e-5f), r1 = rsqrtf(v1 * (1.f / 448) + 1e-5f), n0 = -m0 * r0, n1 = -m1 * r1;
#pragma unroll
  for (int u = 0; u < 4; u++)
    if (u < 3 || full)
      stll(fb + XN + u * 256, tg(pack(fmaf(blo(xw[u][0]), r0, n0), fmaf(bhi(xw[u][0]), r0, n0)), tag), pack(fmaf(blo(xw[u][1]), r1, n1), fmaf(bhi(xw[u][1]), r1, n1)),
           pack(fmaf(blo(xw[u][2]), r0, n0), fmaf(bhi(xw[u][2]), r0, n0)), pack(fmaf(blo(xw[u][3]), r1, n1), fmaf(bhi(xw[u][3]), r1, n1)));
}

__global__ void __launch_bounds__(384, 1)
fused_kernel(const __grid_constant__ CUtensorMap mQKV, const __grid_constant__ CUtensorMap mWO, const __grid_constant__ CUtensorMap mW1,
             const __grid_constant__ CUtensorMap mW2, const __nv_bfloat16* __restrict__ x, const __nv_bfloat16* __restrict__ wphi,
             const __nv_bfloat16* __restrict__ wo, const __nv_bfloat16* __restrict__ w1, const __nv_bfloat16* __restrict__ b1,
             const __nv_bfloat16* __restrict__ w2, const __nv_bfloat16* __restrict__ b2, __nv_bfloat16* __restrict__ out) {
  extern __shared__ __align__(1024) uint8_t sm[];
  const uint32_t sb = s2u(sm);
  const int tid = threadIdx.x, warp = __shfl_sync(~0u, tid >> 5, 0), lane = tid & 31, t = blockIdx.x >> 3, c = blockIdx.x & 7;
  const uint32_t bfull = sb + OFF_BAR, bempty = bfull + 8 * NST;

  if (tid == 256) {
    for (int s = 0; s < NST; s++) { mbar_init(bfull + 8 * s, 1); mbar_init(bempty + 8 * s, 8); }
    asm volatile("fence.mbarrier_init.release.cluster;" ::: "memory");
    fence_async();
  }
  __syncthreads();
  if (warp >= 8) {
    asm volatile("setmaxnreg.dec.sync.aligned.u32 24;");
    auto issue = [&](int i, int s) {
      const uint32_t dst = sb + s * STAGE, bar = bfull + 8 * s;
      mbar_expect(bar, STAGE);
      if (i < 4) {
        tma2d(dst, &mQKV, 448 + 56 * c, 112 * i, bar); tma2d(dst + 7168, &mQKV, 480 + 56 * c, 112 * i, bar);
        tma2d(dst + 14336, &mQKV, 896 + 56 * c, 112 * i, bar); tma2d(dst + 21504, &mQKV, 928 + 56 * c, 112 * i, bar);
      } else if (i >= 8 && i < 15) {
        tma3d(dst, &mW1, 0, 64 * (i - 8), 7 * c, bar);
      } else {
        const CUtensorMap* m = i < 6 ? &mQKV : (i < 8 ? &mWO : &mW2);
        const int n0 = i < 8 ? 56 * c : 64 * (i - 15), k0 = i < 8 ? 224 * (i & 1) : 224 * c;
        tma2d(dst, m, n0, k0, bar); tma2d(dst + 7168, m, n0, k0 + 112, bar);
        tma2d(dst + 14336, m, n0 + 32, k0, bar); tma2d(dst + 21504, m, n0 + 32, k0 + 112, bar);
      }
    };
    if (tid == 256) {
      int s = 0; uint32_t ph = 1;
      for (int n = 0; n < 44; n++) {
        mbar_wait(bempty + 8 * s, ph);
        issue(n >= 22 ? n - 22 : n, s);
        if (++s == NST) { s = 0; ph ^= 1; }
      }
    } else if (warp == 9) {
      mbar_wait(bfull + 8 * 3, 0);
      if (lane == 0) {
        l2pf((const uint8_t*)wo + blockIdx.x * 3136, 3136);
        l2pf((const uint8_t*)w1 + blockIdx.x * 12544, 12544);
        l2pf((const uint8_t*)w2 + blockIdx.x * 12544, 12544);
      }
      if (blockIdx.x < 112) {
        const uint2* wp = (const uint2*)(w1 + (size_t)(lane >> 2) * 1792 + blockIdx.x * 16 + (lane & 3) * 4);
        float s0 = 0.f, s1 = 0.f, s2 = 0.f, s3 = 0.f;
#pragma unroll 8
        for (int i = 0; i < 56; i++) { const uint2 v = __ldg(wp + i * 8 * 448); s0 += blo(v.x); s1 += bhi(v.x); s2 += blo(v.y); s3 += bhi(v.y); }
#pragma unroll 1
        for (int o = 4; o < 32; o <<= 1) { s0 += __shfl_xor_sync(~0u, s0, o); s1 += __shfl_xor_sync(~0u, s1, o); s2 += __shfl_xor_sync(~0u, s2, o); s3 += __shfl_xor_sync(~0u, s3, o); }
        if (lane < 4) stll(g_CS + blockIdx.x * 4 + lane, tg(__float_as_uint(s0), 1), __float_as_uint(s1), __float_as_uint(s2), __float_as_uint(s3));
      }
      asm volatile("bar.sync 6, 96;" ::: "memory");
#pragma unroll 1
      for (int i = 0; i < 2; i++) {
        const int e = lane < 28 ? lane + 28 * i : 0;
        uint4 cv[1];
        ll_issue<0, 1>(cv, g_CS + 56 * c + e, 0); ll_check<0, 1, false>(cv, g_CS + 56 * c + e, 0, 1u);
        const uint2 bb = __ldg((const uint2*)(b1 + 224 * c + 4 * e));
        const uint32_t h0 = pack(__uint_as_float(cv[0].x), __uint_as_float(cv[0].y)), h1 = pack(__uint_as_float(cv[0].z), __uint_as_float(cv[0].w));
        const uint32_t l0 = pack(__uint_as_float(cv[0].x) - blo(h0), __uint_as_float(cv[0].y) - bhi(h0)), l1 = pack(__uint_as_float(cv[0].z) - blo(h1), __uint_as_float(cv[0].w) - bhi(h1));
#pragma unroll 1
        for (int r = 0; r < 8; r++) {
          const uint32_t ad = sb + OFF_CB + (e >> 3) * 512 + r * 64 + ((((e >> 1) ^ (r >> 1)) & 3) << 4) + (e & 1) * 8;
          sts32(ad, r < 2 ? h0 : r == 2 ? l0 : r < 5 ? bb.x : 0u); sts32(ad + 4, r < 2 ? h1 : r == 2 ? l1 : r < 5 ? bb.y : 0u);
        }
      }
      fence_async();
      asm volatile("bar.arrive 4, 288;" ::: "memory");
    } else if (warp >= 10) {
      const int h = warp - 10;
      uint32_t wv[13];
#pragma unroll
      for (int i = 0; i < 13; i++) { const int e = lane + 32 * i; wv[i] = e < 392 ? __ldg((const uint32_t*)wphi + (2 * c + h) * 392 + e) : 0u; }
#pragma unroll 1
      for (int i = 0; i < 8; i++) sts128(sb + OFF_WPHI + (h * 256 + i * 32 + lane) * 16, 0, 0, 0, 0);
      asm volatile("bar.arrive 6, 96;" ::: "memory");
#pragma unroll 1
      for (int i = 0; i < 4; i++) sts128(sb + OFF_PHIK + sw128(h * 128 + i * 32 + lane, 56), 0, 0, 0, 0);
      asm volatile("bar.sync 5, 64;" ::: "memory");
#pragma unroll
      for (int i = 0; i < 13; i++) {
        const int e = lane + 32 * i, d = e / 14, f2 = 2 * (e - 14 * d), k = 28 * h + d;
        if (e < 392) {
          if (f2 < 24) sts32(sb + OFF_WPHI + sw128(k, 32 * h + f2), wv[i]);
          else { sts16(sb + OFF_WPHI + sw128(k, 2 * f2 - 24 + h), wv[i]); sts16(sb + OFF_WPHI + sw128(k, 2 * f2 - 22 + h), wv[i] >> 16); }
        }
      }
      fence_async();
      asm volatile("bar.arrive 3, 320;" ::: "memory");
    }
  } else {
  asm volatile("setmaxnreg.inc.sync.aligned.u32 240;");

  const int wg = warp >> 2, g = lane >> 2, q = lane & 3;
  const int row0 = warp * 16 + g;
#define PTRS const int ln_ = laneid(); \
  uint4* const fm = g_F + ((t * 8 + warp) * 28) * 32 + ln_;            \
  uint4* const fr = g_F + ((t * 8 + c) * 28 + warp) * 32 + ln_;        \
  uint2* const fe = (uint2*)(fm + ((7 * c) >> 1) * 32) + (c & 1);       \
  uint2* const fo = (uint2*)(fm + ((7 * c + 1) >> 1) * 32) + ((c + 1) & 1); \
  uint4* const sf = fm + (7 * (c >> 1) + 4 * (c & 1)) * 32;             \
  uint2* const f2 = (uint2*)(fm - ln_) + ln_;                           \
  uint2* const sh = f2 + (7 * (c >> 1) + 3) * 64 + 32 * (c & 1);        \
  uint32_t* const hme = g_H + (t * 8 + warp) * 8 + c; \
  const uint32_t* const hrow = g_H + (t * 8 + warp) * 8 + (ln_ & 7); \
  (void)fm; (void)fr; (void)fe; (void)fo; (void)sf; (void)f2; (void)sh; (void)hme; (void)hrow;
#define SL(j, B) (((j) & 1 ? fo : fe) + ((j) >> 1) * 64 + 2 * (B))
  float* sLN = (float*)(sm + OFF_V);
  const uint32_t sPK = sb + OFF_PHIK, sV = sb + OFF_V, sW = sb + OFF_WPHI;
  #define XOFF(l) ((t * 128 + c * 16 + ((l) >> 2)) * 448 + warp * 16 + 2 * ((l) & 3))
  MARK(0);
  uint32_t xw[4][4];
  {
    const uint32_t* xp = (const uint32_t*)(x + XOFF(lane));
#pragma unroll
    for (int u = 0; u < 4; u++) {
      if (u < 3 || wg == 0) { xw[u][0] = __ldg(xp + u * 64); xw[u][1] = __ldg(xp + u * 64 + 1792); xw[u][2] = __ldg(xp + u * 64 + 4); xw[u][3] = __ldg(xp + u * 64 + 1796); }
      else { xw[u][0] = xw[u][1] = xw[u][2] = xw[u][3] = 0; }
    }
  }
  int cs = 0, rs = 0; uint32_t cph = 0;
  auto acquire = [&]() -> uint32_t { mbar_wait(bfull + 8 * cs, cph); const uint32_t a = (sb >> 4) + cs * (STAGE >> 4); if (++cs == NST) { cs = 0; cph ^= 1; } return a; };
  auto release = [&]() { if (lane == 0) mbar_arrive(bempty + 8 * rs); if (++rs == NST) rs = 0; };

#pragma unroll 1
  for (int L = 0; L < 2; L++) {
    const uint32_t tag = 1 - L;
    uint32_t phq[2][2][7];
    const uint32_t hs = 10 * L;
    {
      PTRS
      ln_publish(xw, sLN, warp, lane, fr, tag);
      hint_post(hme, hs + 1, lane);
#pragma unroll
      for (int u = 0; u < 4; u++) if (u < 3 || wg == 0) stll(fr + XR + u * 256, tg(xw[u][0], tag), xw[u][1], tg(xw[u][2], tag), xw[u][3]);
    }
    MARK(1 + L * 19);
    {
      PTRS
      uint4 a[28];
      const uint4* pa = fm + XN;
      hint_wait(g_H + (t * 8 + (ln_ & 7)) * 8 + warp, hs + 1); ll_issue<0, 28>(a, pa, 32);
      MARK(2 + L * 19);
      float ak[28], av[28], aq[28], pp[28];
#define KVSTAGE(i) { ll_check<7 * i, 7, false>(a, pa, 32, tag); const uint32_t st = acquire(); wg_fence(); \
      _Pragma("unroll") for (int ks = 0; ks < 7; ks++) { const uint4 f = a[7 * i + ks]; \
        wgmma_rs56(ak, f.x, f.y, f.z, f.w, mkdesc(st, ks * 1024, 7168, 512, 2), i | ks); \
        wgmma_rs56(av, f.x, f.y, f.z, f.w, mkdesc(st, 14336 + ks * 1024, 7168, 512, 2), i | ks); } \
      wg_commit(); if (i > 0) { wg_wait<1>(); release(); } }
      KVSTAGE(0) KVSTAGE(1) KVSTAGE(2) KVSTAGE(3)
      wg_wait<0>(); release(); regfence(ak); regfence(av);
      MARK(3 + L * 19);
      if (L == 0) asm volatile("bar.sync 3, 320;" ::: "memory");
      phi_gemm(ak, pp, sW);
#pragma unroll
      for (int j = 0; j < 7; j++) {
        const int n = 8 * j + 2 * q, n2 = n < 28 ? n : n + 4;
        sts32(sV + sw128(row0, n2), pack(av[4 * j], av[4 * j + 1])); sts32(sV + sw128(row0 + 8, n2), pack(av[4 * j + 2], av[4 * j + 3]));
      }
      { const int n2 = 28 + 2 * (q & 1) + 32 * (q >> 1); const uint32_t v = (q & 1) ? 0u : 0x3F80u; sts32(sV + sw128(row0, n2), v); sts32(sV + sw128(row0 + 8, n2), v); }
      wg_wait<0>(); regfence(pp);
      hedgehog<0, 2>(pp, [&](int r, int h, int p, uint32_t v) { sts32(sPK + h * 16384 + sw128(row0 + 8 * r, 8 * p + 2 * q), v); });
      fence_async();
      bar_cons();
      MARK(4 + L * 19);
      float kv[32];
      wg_fence();
#pragma unroll
      for (int ks = 0; ks < 8; ks++) wgmma_ss64(kv, mkdesc((sPK + wg * 16384) >> 4, ks * 2048, 1024, 1024, 1), mkdesc(sV >> 4, ks * 2048, 1024, 1024, 1), ks);
      wg_commit(); wg_wait<0>(); regfence(kv);
      const int ln2 = laneid();
#pragma unroll
      for (int u = 0; u < 4; u++) {
        float e[4];
#pragma unroll
        for (int i = 0; i < 4; i++) e[i] = wg ? kv[16 + 4 * u + i] : kv[4 * u + i];
        stll(g_KVP + (c * 16 + t) * 1024 + wg * 512 + u * 128 + (warp & 3) * 32 + ln2, tg(__float_as_uint(e[0]), tag), __float_as_uint(e[1]), __float_as_uint(e[2]), __float_as_uint(e[3]));
      }
      MARK(5 + L * 19);
      uint4 k4[4];
      const uint4* pk = g_KVP + (c * 16 + 4 * (ln2 & 3)) * 1024 + 64 * t + warp * 8 + (ln2 >> 2);
#pragma unroll
      for (int i = 0; i < 2; i++) {
        const uint32_t st = acquire(); wg_fence();
#pragma unroll
        for (int ks = 0; ks < 14; ks++) { const uint4 f = a[14 * i + ks]; wgmma_rs56(aq, f.x, f.y, f.z, f.w, mkdesc(st, ks * 1024, 14336, 512, 2), i | ks); }
        wg_commit();
        if (i == 0) ll_issue<0, 4>(k4, pk, 1024);
      }
      ll_check<0, 4, false>(k4, pk, 1024, tag);
      float s0 = 0, s1 = 0, s2 = 0, s3 = 0;
#pragma unroll
      for (int i = 0; i < 4; i++) { s0 += __uint_as_float(k4[i].x); s1 += __uint_as_float(k4[i].y); s2 += __uint_as_float(k4[i].z); s3 += __uint_as_float(k4[i].w); }
      s0 = qsum(s0); s1 = qsum(s1); s2 = qsum(s2); s3 = qsum(s3);
      if (q == 0) stll2(g_KVR + c * 1024 + 64 * t + warp * 8 + (ln2 >> 2), tg(pack(s0, s1), tag), pack(s2, s3));
      MARK(6 + L * 19);
      wg_wait<0>(); release(); release(); regfence(aq);
      phi_gemm(aq, pp, sW);
      bar_cons();
#pragma unroll
      for (int i = 0; i < 4; i++) sts128(sV + warp * 2048 + (lane + i * 32) * 16, 0, 0, 0, 0);
      wg_wait<0>(); regfence(pp);
      hedgehog<0, 1>(pp, [&](int r, int h, int p, uint32_t v) { phq[r][h][p] = v; });
      uint2 r[4];
      const uint2* pr = g_KVR + c * 1024 + wg * 512 + (warp & 3) * 32 + ln2;
#pragma unroll
      for (int u = 0; u < 4; u++) r[u] = ldll2(pr + u * 128);
      hedgehog<1, 2>(pp, [&](int r, int h, int p, uint32_t v) { phq[r][h][p] = v; });
      MARK(7 + L * 19);
#pragma unroll 1
      for (int it = 0; it < SPIN; it++) {
        if (!__any_sync(~0u, ((r[0].x ^ tag) | (r[1].x ^ tag) | (r[2].x ^ tag) | (r[3].x ^ tag)) & 1)) break;
#pragma unroll
        for (int u = 0; u < 4; u++) r[u] = ldll2(pr + u * 128);
      }
#pragma unroll
      for (int u = 0; u < 4; u++) {
        const int d = 8 * u + 2 * q;
        if (d < 28) { sts32(sV + sw128(row0, 28 * wg + d), r[u].x); sts32(sV + sw128(row0 + 8, 28 * wg + d), r[u].y); }
        else if (d == 28) {
#pragma unroll
          for (int j = 0; j < 4; j++) { sts16(sV + sw128(row0, 56 + 2 * j + wg), r[u].x); sts16(sV + sw128(row0 + 8, 56 + 2 * j + wg), r[u].y); }
        }
      }
      fence_async();
      bar_cons();
      MARK(8 + L * 19);
      float o[32];
      wg_fence();
#pragma unroll
      for (int ks = 0; ks < 8; ks++) {
        const int h = ks >> 2, p = 2 * (ks & 3);
        wgmma_rs64(o, phq[0][h][p], phq[1][h][p], p < 6 ? phq[0][h][p < 6 ? p + 1 : 0] : 0u, p < 6 ? phq[1][h][p < 6 ? p + 1 : 0] : 0u, mkdesc(sV >> 4, ks * 2048, 1024, 1024, 1), ks);
      }
      wg_commit(); wg_wait<0>(); regfence(o);
      const float iA0 = rcp(o[28] + 1e-6f), iB0 = rcp(o[29] + 1e-6f), iA1 = rcp(o[30] + 1e-6f), iB1 = rcp(o[31] + 1e-6f);
      uint32_t w[14];
      { PTRS
#pragma unroll
      for (int j = 0; j < 7; j++) {
        const bool hb = 8 * j + 2 * q >= 28; const float i0 = hb ? iB0 : iA0, i1 = hb ? iB1 : iA1;
        w[2 * j] = pack(o[4 * j] * i0, o[4 * j + 1] * i0); w[2 * j + 1] = pack(o[4 * j + 2] * i1, o[4 * j + 3] * i1);
        if (j == 0 || ((j ^ c) & 1) == 0) w[2 * j] = tg(w[2 * j], tag);
      }
      slice_store(sf + OO, sh + 2 * OO, w, c & 1);
      hint_post(hme, hs + 2, lane); }
    }
    MARK(9 + L * 19);
    {
      PTRS
      uint2 xr[7];
#pragma unroll
      for (int j = 0; j < 7; j++) xr[j] = ldll2(SL(j, XR));
      uint4 a[28];
      const uint4* pa = fm + OO;
      hint_wait(hrow, hs + 2);
      MARK(10 + L * 19);
      ll_issue<0, 28, true>(a, pa, 32, f2 + 2 * OO);
      float y[28];
      uint32_t st;
#define WOSTEP(i) { ll_check<7 * i, 7, true>(a, pa, 32, tag, f2 + 2 * OO); if (!(i & 1)) st = acquire(); wg_fence(); \
      _Pragma("unroll") for (int ks = 0; ks < 7; ks++) { const uint4 f = a[7 * i + ks]; \
        wgmma_rs56(y, f.x, f.y, f.z, f.w, mkdesc(st, ((i & 1) * 7 + ks) * 1024, 14336, 512, 2), i | ks); } wg_commit(); }
      WOSTEP(0) WOSTEP(1) WOSTEP(2) WOSTEP(3)
#pragma unroll 1
      for (int it = 0; it < SPIN; it++) {
        uint32_t bad = 0;
#pragma unroll
        for (int j = 0; j < 7; j++) bad |= xr[j].x ^ tag;
        if (!__any_sync(~0u, bad & 1)) break;
#pragma unroll
        for (int j = 0; j < 7; j++) xr[j] = ldll2(SL(j, XR));
      }
      wg_wait<0>(); regfence(y);
      MARK(11 + L * 19);
      float s0 = 0.f, s1 = 0.f;
      uint32_t w[14];
#pragma unroll
      for (int j = 0; j < 7; j++) {
        w[2 * j] = pack(blo(xr[j].x) + y[4 * j], bhi(xr[j].x) + y[4 * j + 1]); w[2 * j + 1] = pack(blo(xr[j].y) + y[4 * j + 2], bhi(xr[j].y) + y[4 * j + 3]);
        if (j == 0 || ((j ^ c) & 1) == 0) w[2 * j] = tg(w[2 * j], tag);
      }
      slice_store(sf + X1, sh + 2 * X1, w, c & 1);
      hint_post(hme, hs + 3, lane);
#pragma unroll
      for (int j = 0; j < 7; j++) {
        y[4 * j] = blo(w[2 * j]); y[4 * j + 1] = bhi(w[2 * j]); y[4 * j + 2] = blo(w[2 * j + 1]); y[4 * j + 3] = bhi(w[2 * j + 1]);
        s0 += y[4 * j] + y[4 * j + 1]; s1 += y[4 * j + 2] + y[4 * j + 3];
      }
      s0 = qsum(s0) * (1.f / 56); s1 = qsum(s1) * (1.f / 56);
      float v0 = 0.f, v1 = 0.f;
#pragma unroll
      for (int j = 0; j < 7; j++) {
        const float d0 = y[4 * j] - s0, d1 = y[4 * j + 1] - s0, d2 = y[4 * j + 2] - s1, d3 = y[4 * j + 3] - s1;
        v0 += d0 * d0 + d1 * d1; v1 += d2 * d2 + d3 * d3;
      }
      v0 = qsum(v0); v1 = qsum(v1);
      if (q == 0) stll(g_ST + ((t * 8 + warp) * 8 + c) * 8 + (ln_ >> 2), tg(__float_as_uint(s0), tag), __float_as_uint(v0), __float_as_uint(s1), __float_as_uint(v1));
    }
    uint32_t hf[56];
    float rr0, rr1;
    {
      PTRS
      uint4 a[28];
      const uint4* pa = fm + X1;
      hint_wait(hrow, hs + 3);
      MARK(12 + L * 19);
      ll_issue<0, 4, true>(a, pa, 32, f2 + 2 * X1); ll_check<0, 4, true>(a, pa, 32, tag, f2 + 2 * X1); ll_issue<4, 12, true>(a, pa, 32, f2 + 2 * X1);
      release(); release();
      float y[112];
#define F1STAGE(i) { if (i > 0) ll_check<4 * i, 4, true>(a, pa, 32, tag, f2 + 2 * X1); const uint32_t st = acquire(); wg_fence(); \
      _Pragma("unroll") for (int ks = 0; ks < 4; ks++) { const uint4 f = a[4 * i + ks]; \
        wgmma_rs224(y, f.x, f.y, f.z, f.w, mkdesc(st, ks * 1024, 4096, 512, 2), i | ks); } \
      wg_commit(); if (i > 0) { wg_wait<1>(); release(); if (i < 4) ll_issue<(i < 4 ? 4 * i + 12 : 0), 4, true>(a, pa, 32, f2 + 2 * X1); } }
      F1STAGE(0) MARK(13 + L * 19); F1STAGE(1) F1STAGE(2) F1STAGE(3) F1STAGE(4) F1STAGE(5)
      uint4 sv[2];
      const uint4* ps = g_ST + ((t * 8 + warp) * 8 + 2 * (laneid() & 3)) * 8 + (laneid() >> 2);
      ll_issue<0, 2>(sv, ps, 8);
      F1STAGE(6)
      ll_check<0, 2, false>(sv, ps, 8, tag);
      const float ma = __uint_as_float(sv[0].x), mb = __uint_as_float(sv[1].x), mc = __uint_as_float(sv[0].z), md = __uint_as_float(sv[1].z);
      const float m0 = qsum(ma + mb) * 0.125f, m1 = qsum(mc + md) * 0.125f;
      const float v0 = qsum(__uint_as_float(sv[0].y) + __uint_as_float(sv[1].y) + 56.f * ((ma - m0) * (ma - m0) + (mb - m0) * (mb - m0)));
      const float v1 = qsum(__uint_as_float(sv[0].w) + __uint_as_float(sv[1].w) + 56.f * ((mc - m1) * (mc - m1) + (md - m1) * (md - m1)));
      const float e0 = v0 * (1.f / 448) + 1e-5f, e1 = v1 * (1.f / 448) + 1e-5f;
      rr0 = 1.f / e0; rr1 = 1.f / e1;
      auto fold = [&](float m, float sd) -> uint32_t {
        const float mh = blo(pack(-m, 0.f)), sh_ = blo(pack(sd, 0.f));
        return q == 0 ? pack(mh, -m - mh) : q == 1 ? pack(mh, sh_) : q == 2 ? pack(sd - sh_, 0.f) : 0u;
      };
      const uint32_t fa = fold(m0, sqrtf(e0)), fb = fold(m1, sqrtf(e1));
      if (L == 0) asm volatile("bar.sync 4, 288;" ::: "memory");
      wg_fence();
      wgmma_rs224(y, fa, fb, 0u, 0u, mkdesc((sb + OFF_CB) >> 4, 0, 512, 0, 2), 1);
      wg_commit();
      wg_wait<0>(); release(); regfence(y);
      MARK(14 + L * 19);
#pragma unroll
      for (int j = 0; j < 56; j++) {
        uint32_t r; asm("cvt.rn.relu.bf16x2.f32 %0, %1, %2;" : "=r"(r) : "f"(y[2 * j + 1]), "f"(y[2 * j]));
        asm("mul.bf16x2 %0, %1, %1;" : "=r"(hf[j]) : "r"(r));
      }
    }
    MARK(15 + L * 19);
    {
      PTRS
      float ya[32], yb[32];
      uint4* pp = g_P + ((t * 8 + warp) * 8 + c) * 28 * 32 + ln_;
#define F2STORE(j, Y) { regfence(Y); _Pragma("unroll") for (int u = 0; u < 4; u++) \
      stll(pp + (4 * (j) + u) * 32, tg(pack(Y[8 * u] * rr0, Y[8 * u + 1] * rr0), tag), pack(Y[8 * u + 2] * rr1, Y[8 * u + 3] * rr1), \
           pack(Y[8 * u + 4] * rr0, Y[8 * u + 5] * rr0), pack(Y[8 * u + 6] * rr1, Y[8 * u + 7] * rr1)); if ((j) >= 5) hint_post(hme, hs + (4 + (j)), lane); }
#define F2PASS(j, Y, Z) { const uint32_t st = acquire(); wg_fence(); \
      _Pragma("unroll") for (int ks = 0; ks < 14; ks++) wgmma_rs64(Y, hf[4 * ks], hf[4 * ks + 1], hf[4 * ks + 2], hf[4 * ks + 3], mkdesc(st, ks * 1024, 14336, 512, 2), ks); \
      wg_commit(); if (j > 0) { wg_wait<1>(); release(); F2STORE(j - 1, Z) } }
      const uint4* pr = g_P + ((t * 8 + c) * 8 * 28 + warp) * 32 + ln_;
      uint4 p[8], p2[8]; uint2 xa, xb, xc, xd; uint32_t ba, bb, bc, bd;
#define RISSUE(m, P, XA, XB, BA, BB) { ll_issue<0, 8>(P, pr + (m) * 256, 896); const bool spl = (8 * (m) + warp) % 7 == 3; \
      const uint2* p0 = (const uint2*)(fr + X1 + (m) * 256) - (spl ? ln_ : 0); XA = ldll2(p0); XB = ldll2(p0 + (spl ? 32 : 1)); \
      const uint32_t* bp = (const uint32_t*)(b2 + 128 * (m) + 16 * warp) + (ln_ & 3); BA = __ldg(bp); BB = __ldg(bp + 4); }
#define REDU(m, P, XA, XB, BA, BB) { ll_check<0, 8, false>(P, pr + (m) * 256, 896, tag); \
      float e[8] = {blo(XA.x) + blo(BA), bhi(XA.x) + bhi(BA), blo(XA.y) + blo(BA), bhi(XA.y) + bhi(BA), blo(XB.x) + blo(BB), bhi(XB.x) + bhi(BB), blo(XB.y) + blo(BB), bhi(XB.y) + bhi(BB)}; \
      _Pragma("unroll") for (int i = 0; i < 8; i++) { e[0] += blo(P[i].x); e[1] += bhi(P[i].x); e[2] += blo(P[i].y); e[3] += bhi(P[i].y); \
        e[4] += blo(P[i].z); e[5] += bhi(P[i].z); e[6] += blo(P[i].w); e[7] += bhi(P[i].w); } \
      xw[m][0] = pack(e[0], e[1]); xw[m][1] = pack(e[2], e[3]); xw[m][2] = pack(e[4], e[5]); xw[m][3] = pack(e[6], e[7]); }
      F2PASS(0, ya, yb) F2PASS(1, yb, ya) F2PASS(2, ya, yb) F2PASS(3, yb, ya) F2PASS(4, ya, yb)
      RISSUE(0, p, xa, xb, ba, bb)
      F2PASS(5, yb, ya)
      REDU(0, p, xa, xb, ba, bb)
      F2PASS(6, ya, yb)
      RISSUE(1, p, xa, xb, ba, bb)
      wg_wait<0>(); release(); F2STORE(6, ya)
      MARK(16 + L * 19);
      const uint32_t* hred = g_H + (t * 8 + c) * 8 + (ln_ & 7);
      if (wg) hint_wait(hred, hs + 9);
      RISSUE(2, p2, xc, xd, bc, bd)
      REDU(1, p, xa, xb, ba, bb)
      if (wg == 0) { hint_wait(hred, hs + 10); RISSUE(3, p, xa, xb, ba, bb) }
      MARK(17 + L * 19);
      REDU(2, p2, xc, xd, bc, bd)
      if (wg == 0) REDU(3, p, xa, xb, ba, bb) else { xw[3][0] = xw[3][1] = xw[3][2] = xw[3][3] = 0; }
    }
    MARK(18 + L * 19);
  }
  {
    uint32_t* op = (uint32_t*)(out + XOFF(laneid()));
#pragma unroll
    for (int u = 0; u < 4; u++) if (u < 3 || wg == 0) { op[u * 64] = xw[u][0]; op[u * 64 + 1792] = xw[u][1]; op[u * 64 + 4] = xw[u][2]; op[u * 64 + 1796] = xw[u][3]; }
    if (warp == 7 && blockIdx.x < 112 && lane < 4) stll(g_CS + blockIdx.x * 4 + lane, 0, 0, 0, 0);
  }
  MARK(38);
  }
}

typedef CUresult (*EncFn)(CUtensorMap*, CUtensorMapDataType, cuuint32_t, void*, const cuuint64_t*, const cuuint64_t*, const cuuint32_t*, const cuuint32_t*,
                          CUtensorMapInterleave, CUtensorMapSwizzle, CUtensorMapL2promotion, CUtensorMapFloatOOBfill);

extern "C" void kernel_launch(void* const* d_in, const int* in_sizes, int n_in, void* d_out, int out_size) {
  static EncFn enc = nullptr;
  if (!enc) {
    void* fn = nullptr; cudaDriverEntryPointQueryResult qr;
    cudaGetDriverEntryPoint("cuTensorMapEncodeTiled", &fn, cudaEnableDefault, &qr);
    enc = (EncFn)fn;
    cudaFuncSetAttribute(fused_kernel, cudaFuncAttributeMaxDynamicSharedMemorySize, SMEM_BYTES);
  }
  CUtensorMap mQKV, mWO, mW1, mW2;
  const cuuint32_t es[3] = {1, 1, 1};
  auto enc2 = [&](CUtensorMap* m, void* p, cuuint64_t cols, cuuint64_t rows) {
    const cuuint64_t dims[2] = {cols, rows}, str[1] = {cols * 2}; const cuuint32_t box[2] = {32, 112};
    enc(m, CU_TENSOR_MAP_DATA_TYPE_BFLOAT16, 2, p, dims, str, box, es, CU_TENSOR_MAP_INTERLEAVE_NONE, CU_TENSOR_MAP_SWIZZLE_64B,
        CU_TENSOR_MAP_L2_PROMOTION_L2_128B, CU_TENSOR_MAP_FLOAT_OOB_FILL_NONE);
  };
  enc2(&mQKV, d_in[1], 1344, 448); enc2(&mWO, d_in[3], 448, 448); enc2(&mW2, d_in[7], 448, 1792);
  {
    const cuuint64_t dims[3] = {32, 448, 56}, str[2] = {3584, 64}; const cuuint32_t box[3] = {32, 64, 7};
    enc(&mW1, CU_TENSOR_MAP_DATA_TYPE_BFLOAT16, 3, d_in[5], dims, str, box, es, CU_TENSOR_MAP_INTERLEAVE_NONE, CU_TENSOR_MAP_SWIZZLE_64B,
        CU_TENSOR_MAP_L2_PROMOTION_L2_128B, CU_TENSOR_MAP_FLOAT_OOB_FILL_NONE);
  }
  typedef const __nv_bfloat16* BP;
  fused_kernel<<<128, 384, SMEM_BYTES>>>(mQKV, mWO, mW1, mW2, (BP)d_in[0], (BP)d_in[2], (BP)d_in[3], (BP)d_in[5], (BP)d_in[6], (BP)d_in[7], (BP)d_in[8],
                                         (__nv_bfloat16*)d_out);
}
```

```cpp
#include <cuda_runtime.h>
#include <cuda_bf16.h>
#include <cuda.h>
#include <stdint.h>

constexpr int NST = 6, STAGE = 28672;
constexpr int OFF_PHIK = NST * STAGE;
constexpr int OFF_V = OFF_PHIK + 32768;
constexpr int OFF_WPHI = OFF_V + 16384;
constexpr int OFF_CB = OFF_WPHI + 7168;
constexpr int OFF_BAR = OFF_CB + 3584;
constexpr int SMEM_BYTES = OFF_BAR + 16 * NST;
constexpr int FR = 16 * 8 * 28 * 32;
constexpr int SPIN = 1 << 18;

__device__ uint4 g_F[4 * FR];
constexpr int XN = 0, XR = FR, OO = 2 * FR, X1 = 3 * FR;
__device__ uint4 g_P[8 * FR];
__device__ uint4 g_ST[16 * 8 * 8 * 8];
__device__ uint4 g_KVP[8 * 16 * 1024];
__device__ uint2 g_KVR[8 * 1024];
__device__ uint4 g_CS[448];
__device__ uint32_t g_H[16 * 8 * 8];
#define MARK(i)

__device__ __forceinline__ uint32_t s2u(const void* p) { return (uint32_t)__cvta_generic_to_shared(p); }
__device__ __forceinline__ void mbar_init(uint32_t b, uint32_t c) { asm volatile("mbarrier.init.shared::cta.b64 [%0], %1;" ::"r"(b), "r"(c)); }
__device__ __forceinline__ void mbar_expect(uint32_t b, uint32_t tx) { asm volatile("mbarrier.arrive.expect_tx.shared::cta.b64 _, [%0], %1;" ::"r"(b), "r"(tx) : "memory"); }
__device__ __forceinline__ void mbar_arrive(uint32_t b) { asm volatile("mbarrier.arrive.shared::cta.b64 _, [%0];" ::"r"(b) : "memory"); }
__device__ __forceinline__ void mbar_wait(uint32_t b, uint32_t ph) {
  uint32_t ok = 0;
#pragma unroll 1
  for (int it = 0; it < SPIN && !ok; it++)
    asm volatile("{.reg .pred p; mbarrier.try_wait.parity.shared::cta.b64 p,[%1],%2; selp.u32 %0,1,0,p;}" : "=r"(ok) : "r"(b), "r"(ph) : "memory");
}
__device__ __forceinline__ void tma2d(uint32_t dst, const CUtensorMap* m, int c0, int c1, uint32_t bar) {
  asm volatile("cp.async.bulk.tensor.2d.shared::cluster.global.mbarrier::complete_tx::bytes [%0], [%1, {%3, %4}], [%2];"
               ::"r"(dst), "l"(m), "r"(bar), "r"(c0), "r"(c1) : "memory");
}
__device__ __forceinline__ void tma3d(uint32_t dst, const CUtensorMap* m, int c0, int c1, int c2, uint32_t bar) {
  asm volatile("cp.async.bulk.tensor.3d.shared::cluster.global.mbarrier::complete_tx::bytes [%0], [%1, {%3, %4, %5}], [%2];"
               ::"r"(dst), "l"(m), "r"(bar), "r"(c0), "r"(c1), "r"(c2) : "memory");
}
__device__ __forceinline__ void l2pf(const void* p, uint32_t bytes) { asm volatile("cp.async.bulk.prefetch.L2.global [%0], %1;" ::"l"(p), "r"(bytes) : "memory"); }
__device__ __forceinline__ void wg_fence() { asm volatile("wgmma.fence.sync.aligned;" ::: "memory"); }
__device__ __forceinline__ void wg_commit() { asm volatile("wgmma.commit_group.sync.aligned;" ::: "memory"); }
template <int N> __device__ __forceinline__ void wg_wait() { asm volatile("wgmma.wait_group.sync.aligned %0;" ::"n"(N) : "memory"); }
template <int N> __device__ __forceinline__ void regfence(float (&d)[N]) {
#pragma unroll
  for (int i = 0; i < N; i++) asm volatile("" : "+f"(d[i])::"memory");
}
__device__ __forceinline__ void bar_cons() { asm volatile("bar.sync 1, 256;" ::: "memory"); }
__device__ __forceinline__ void fence_async() { asm volatile("fence.proxy.async.shared::cta;" ::: "memory"); }
struct Desc { uint32_t lo, hi; };
__device__ __forceinline__ Desc mkdesc(uint32_t base16, uint32_t off, uint32_t lbo, uint32_t sbo, uint32_t swz) {
  return Desc{base16 + ((off >> 4) | ((lbo >> 4) << 16)), (sbo >> 4) | (swz << 30)};
}
__device__ __forceinline__ uint4 ldll(const uint4* p) {
  uint4 v; asm volatile("ld.relaxed.gpu.global.v4.u32 {%0,%1,%2,%3}, [%4];" : "=r"(v.x), "=r"(v.y), "=r"(v.z), "=r"(v.w) : "l"(p) : "memory"); return v;
}
__device__ __forceinline__ uint2 ldll2(const uint2* p) {
  uint2 v; asm volatile("ld.relaxed.gpu.global.v2.u32 {%0,%1}, [%2];" : "=r"(v.x), "=r"(v.y) : "l"(p) : "memory"); return v;
}
__device__ __forceinline__ void stll(uint4* p, uint32_t x, uint32_t y, uint32_t z, uint32_t w) {
  asm volatile("st.relaxed.gpu.global.v4.u32 [%0], {%1,%2,%3,%4};" ::"l"(p), "r"(x), "r"(y), "r"(z), "r"(w) : "memory");
}
__device__ __forceinline__ void stll2(void* p, uint32_t x, uint32_t y) {
  asm volatile("st.relaxed.gpu.global.v2.u32 [%0], {%1,%2};" ::"l"(p), "r"(x), "r"(y) : "memory");
}
__device__ __forceinline__ int laneid() { int l; asm volatile("mov.u32 %0, %%laneid;" : "=r"(l)); return l; }
__device__ __forceinline__ uint32_t tg(uint32_t w, uint32_t tag) { return (w & ~1u) | tag; }
__device__ __forceinline__ uint32_t pack(float lo, float hi) {
  uint32_t r; asm("cvt.rn.bf16x2.f32 %0, %1, %2;" : "=r"(r) : "f"(hi), "f"(lo)); return r;
}
__device__ __forceinline__ float blo(uint32_t w) { return __uint_as_float(w << 16); }
__device__ __forceinline__ float bhi(uint32_t w) { return __uint_as_float(w & 0xffff0000u); }
__device__ __forceinline__ float ex2(float x) { float r; asm("ex2.approx.ftz.f32 %0, %1;" : "=f"(r) : "f"(x)); return r; }
__device__ __forceinline__ float rcp(float x) { float r; asm("rcp.approx.ftz.f32 %0, %1;" : "=f"(r) : "f"(x)); return r; }
__device__ __forceinline__ float qsum(float v) { v += __shfl_xor_sync(~0u, v, 1); v += __shfl_xor_sync(~0u, v, 2); return v; }
__device__ __forceinline__ void sts32(uint32_t a, uint32_t v) { asm volatile("st.shared.u32 [%0], %1;" ::"r"(a), "r"(v) : "memory"); }
__device__ __forceinline__ void sts16(uint32_t a, uint32_t v) { asm volatile("st.shared.u16 [%0], %1;" ::"r"(a), "h"((uint16_t)v) : "memory"); }
__device__ __forceinline__ void sts128(uint32_t a, uint32_t x, uint32_t y, uint32_t z, uint32_t w) {
  asm volatile("st.shared.v4.u32 [%0], {%1,%2,%3,%4};" ::"r"(a), "r"(x), "r"(y), "r"(z), "r"(w) : "memory");
}
__device__ __forceinline__ uint32_t sw128(int row, int col) { return row * 128 + ((((col >> 3) ^ row) & 7) << 4) + (col & 7) * 2; }

__device__ __forceinline__ void wgmma_rs56(float (&d)[28], const uint32_t a0, const uint32_t a1, const uint32_t a2, const uint32_t a3, Desc db, int sd) {
  asm volatile("{.reg .pred p; .reg .b64 da, db; setp.ne.b32 p, %33, 0; mov.b64 db, {%32, %34};\n wgmma.mma_async.sync.aligned.m64n56k16.f32.bf16.bf16 {%0,%1,%2,%3,%4,%5,%6,%7,%8,%9,%10,%11,%12,%13,%14,%15,%16,%17,%18,%19,%20,%21,%22,%23,%24,%25,%26,%27}, {%28,%29,%30,%31}, db, p, 1, 1, 1;}"
   : "+f"(d[0]),"+f"(d[1]),"+f"(d[2]),"+f"(d[3]),"+f"(d[4]),"+f"(d[5]),"+f"(d[6]),"+f"(d[7]),"+f"(d[8]),"+f"(d[9]),"+f"(d[10]),"+f"(d[11]),"+f"(d[12]),"+f"(d[13]),"+f"(d[14]),"+f"(d[15]),"+f"(d[16]),"+f"(d[17]),"+f"(d[18]),"+f"(d[19]),"+f"(d[20]),"+f"(d[21]),"+f"(d[22]),"+f"(d[23]),"+f"(d[24]),"+f"(d[25]),"+f"(d[26]),"+f"(d[27])
   : "r"(a0),"r"(a1),"r"(a2),"r"(a3),"r"(db.lo),"r"(sd),"r"(db.hi));
}
__device__ __forceinline__ void wgmma_rs64(float (&d)[32], const uint32_t a0, const uint32_t a1, const uint32_t a2, const uint32_t a3, Desc db, int sd) {
  asm volatile("{.reg .pred p; .reg .b64 da, db; setp.ne.b32 p, %37, 0; mov.b64 db, {%36, %38};\n wgmma.mma_async.sync.aligned.m64n64k16.f32.bf16.bf16 {%0,%1,%2,%3,%4,%5,%6,%7,%8,%9,%10,%11,%12,%13,%14,%15,%16,%17,%18,%19,%20,%21,%22,%23,%24,%25,%26,%27,%28,%29,%30,%31}, {%32,%33,%34,%35}, db, p, 1, 1, 1;}"
   : "+f"(d[0]),"+f"(d[1]),"+f"(d[2]),"+f"(d[3]),"+f"(d[4]),"+f"(d[5]),"+f"(d[6]),"+f"(d[7]),"+f"(d[8]),"+f"(d[9]),"+f"(d[10]),"+f"(d[11]),"+f"(d[12]),"+f"(d[13]),"+f"(d[14]),"+f"(d[15]),"+f"(d[16]),"+f"(d[17]),"+f"(d[18]),"+f"(d[19]),"+f"(d[20]),"+f"(d[21]),"+f"(d[22]),"+f"(d[23]),"+f"(d[24]),"+f"(d[25]),"+f"(d[26]),"+f"(d[27]),"+f"(d[28]),"+f"(d[29]),"+f"(d[30]),"+f"(d[31])
   : "r"(a0),"r"(a1),"r"(a2),"r"(a3),"r"(db.lo),"r"(sd),"r"(db.hi));
}
__device__ __forceinline__ void wgmma_rs192(float (&d)[96], const uint32_t a0, const uint32_t a1, const uint32_t a2, const uint32_t a3, Desc db, int sd) {
  asm volatile("{.reg .pred p; .reg .b64 db; setp.ne.b32 p, %101, 0; mov.b64 db, {%100, %102};\n wgmma.mma_async.sync.aligned.m64n192k16.f32.bf16.bf16 {%0,%1,%2,%3,%4,%5,%6,%7,%8,%9,%10,%11,%12,%13,%14,%15,%16,%17,%18,%19,%20,%21,%22,%23,%24,%25,%26,%27,%28,%29,%30,%31,%32,%33,%34,%35,%36,%37,%38,%39,%40,%41,%42,%43,%44,%45,%46,%47,%48,%49,%50,%51,%52,%53,%54,%55,%56,%57,%58,%59,%60,%61,%62,%63,%64,%65,%66,%67,%68,%69,%70,%71,%72,%73,%74,%75,%76,%77,%78,%79,%80,%81,%82,%83,%84,%85,%86,%87,%88,%89,%90,%91,%92,%93,%94,%95}, {%96,%97,%98,%99}, db, p, 1, 1, 1;}"
   : "+f"(d[0]),"+f"(d[1]),"+f"(d[2]),"+f"(d[3]),"+f"(d[4]),"+f"(d[5]),"+f"(d[6]),"+f"(d[7]),"+f"(d[8]),"+f"(d[9]),"+f"(d[10]),"+f"(d[11]),"+f"(d[12]),"+f"(d[13]),"+f"(d[14]),"+f"(d[15]),"+f"(d[16]),"+f"(d[17]),"+f"(d[18]),"+f"(d[19]),"+f"(d[20]),"+f"(d[21]),"+f"(d[22]),"+f"(d[23]),"+f"(d[24]),"+f"(d[25]),"+f"(d[26]),"+f"(d[27]),"+f"(d[28]),"+f"(d[29]),"+f"(d[30]),"+f"(d[31]),"+f"(d[32]),"+f"(d[33]),"+f"(d[34]),"+f"(d[35]),"+f"(d[36]),"+f"(d[37]),"+f"(d[38]),"+f"(d[39]),"+f"(d[40]),"+f"(d[41]),"+f"(d[42]),"+f"(d[43]),"+f"(d[44]),"+f"(d[45]),"+f"(d[46]),"+f"(d[47]),"+f"(d[48]),"+f"(d[49]),"+f"(d[50]),"+f"(d[51]),"+f"(d[52]),"+f"(d[53]),"+f"(d[54]),"+f"(d[55]),"+f"(d[56]),"+f"(d[57]),"+f"(d[58]),"+f"(d[59]),"+f"(d[60]),"+f"(d[61]),"+f"(d[62]),"+f"(d[63]),"+f"(d[64]),"+f"(d[65]),"+f"(d[66]),"+f"(d[67]),"+f"(d[68]),"+f"(d[69]),"+f"(d[70]),"+f"(d[71]),"+f"(d[72]),"+f"(d[73]),"+f"(d[74]),"+f"(d[75]),"+f"(d[76]),"+f"(d[77]),"+f"(d[78]),"+f"(d[79]),"+f"(d[80]),"+f"(d[81]),"+f"(d[82]),"+f"(d[83]),"+f"(d[84]),"+f"(d[85]),"+f"(d[86]),"+f"(d[87]),"+f"(d[88]),"+f"(d[89]),"+f"(d[90]),"+f"(d[91]),"+f"(d[92]),"+f"(d[93]),"+f"(d[94]),"+f"(d[95])
   : "r"(a0),"r"(a1),"r"(a2),"r"(a3),"r"(db.lo),"r"(sd),"r"(db.hi));
}
__device__ __forceinline__ void wgmma_rs32(float (&d)[16], const uint32_t a0, const uint32_t a1, const uint32_t a2, const uint32_t a3, Desc db, int sd) {
  asm volatile("{.reg .pred p; .reg .b64 db; setp.ne.b32 p, %21, 0; mov.b64 db, {%20, %22};\n wgmma.mma_async.sync.aligned.m64n32k16.f32.bf16.bf16 {%0,%1,%2,%3,%4,%5,%6,%7,%8,%9,%10,%11,%12,%13,%14,%15}, {%16,%17,%18,%19}, db, p, 1, 1, 1;}"
   : "+f"(d[0]),"+f"(d[1]),"+f"(d[2]),"+f"(d[3]),"+f"(d[4]),"+f"(d[5]),"+f"(d[6]),"+f"(d[7]),"+f"(d[8]),"+f"(d[9]),"+f"(d[10]),"+f"(d[11]),"+f"(d[12]),"+f"(d[13]),"+f"(d[14]),"+f"(d[15])
   : "r"(a0),"r"(a1),"r"(a2),"r"(a3),"r"(db.lo),"r"(sd),"r"(db.hi));
}
__device__ __forceinline__ void wgmma_ss64(float (&d)[32], Desc da, Desc db, int sd) {
  asm volatile("{.reg .pred p; .reg .b64 da, db; setp.ne.b32 p, %34, 0; mov.b64 da, {%32, %35}; mov.b64 db, {%33, %35};\n wgmma.mma_async.sync.aligned.m64n64k16.f32.bf16.bf16 {%0,%1,%2,%3,%4,%5,%6,%7,%8,%9,%10,%11,%12,%13,%14,%15,%16,%17,%18,%19,%20,%21,%22,%23,%24,%25,%26,%27,%28,%29,%30,%31}, da, db, p, 1, 1, 1, 1;}"
   : "+f"(d[0]),"+f"(d[1]),"+f"(d[2]),"+f"(d[3]),"+f"(d[4]),"+f"(d[5]),"+f"(d[6]),"+f"(d[7]),"+f"(d[8]),"+f"(d[9]),"+f"(d[10]),"+f"(d[11]),"+f"(d[12]),"+f"(d[13]),"+f"(d[14]),"+f"(d[15]),"+f"(d[16]),"+f"(d[17]),"+f"(d[18]),"+f"(d[19]),"+f"(d[20]),"+f"(d[21]),"+f"(d[22]),"+f"(d[23]),"+f"(d[24]),"+f"(d[25]),"+f"(d[26]),"+f"(d[27]),"+f"(d[28]),"+f"(d[29]),"+f"(d[30]),"+f"(d[31])
   : "r"(da.lo),"r"(db.lo),"r"(sd),"r"(db.hi));
}

template <int S, int N, bool SPL = false, int T> __device__ __forceinline__ void ll_issue(uint4 (&v)[T], const uint4* p, int stride, const uint2* p2 = nullptr) {
#pragma unroll
  for (int i = S; i < S + N; i++) {
    if (SPL && i % 7 == 3) { const uint2 lo = ldll2(p2 + i * 64), hi = ldll2(p2 + i * 64 + 32); v[i] = make_uint4(lo.x, lo.y, hi.x, hi.y); }
    else v[i] = ldll(p + i * stride);
  }
}
template <int S, int N, bool SPL, int T> __device__ __forceinline__ void ll_check(uint4 (&v)[T], const uint4* p, int stride, uint32_t tag, const uint2* p2 = nullptr) {
#pragma unroll 1
  for (int it = 0; it < SPIN; it++) {
    uint32_t bad = 0;
#pragma unroll
    for (int i = S; i < S + N; i++) bad |= (v[i].x ^ tag) | ((SPL && i % 7 == 3) ? (v[i].z ^ tag) : 0u);
    if (!__any_sync(~0u, bad & 1)) break;
    ll_issue<S, N, SPL>(v, p, stride, p2);
  }
}
__device__ __forceinline__ void hint_post(uint32_t* p, uint32_t v, int lane) {
  if (lane == 0) asm volatile("st.relaxed.gpu.global.u32 [%0], %1;" ::"l"(p), "r"(v) : "memory");
}
__device__ __forceinline__ void hint_wait(const uint32_t* p, uint32_t s) {
#pragma unroll 1
  for (int it = 0; it < SPIN; it++) {
    uint32_t v; asm volatile("ld.relaxed.gpu.global.u32 %0, [%1];" : "=r"(v) : "l"(p) : "memory");
    if (__all_sync(~0u, v - s < 10u)) break;
  }
}
__device__ __forceinline__ void slice_store(uint4* pf, uint2* ph, const uint32_t (&w)[14], bool odd) {
#pragma unroll
  for (int u = 0; u < 3; u++)
    stll(pf + u * 32, odd ? w[4 * u + 2] : w[4 * u], odd ? w[4 * u + 3] : w[4 * u + 1], odd ? w[4 * u + 4] : w[4 * u + 2], odd ? w[4 * u + 5] : w[4 * u + 3]);
  stll2(ph, odd ? w[0] : w[12], odd ? w[1] : w[13]);
}
template <int R0, int R1, class F> __device__ __forceinline__ void hedgehog(const float (&d)[28], F sink) {
  const float L2E = 1.4426950408889634f;
#pragma unroll
  for (int r = R0; r < R1; r++)
#pragma unroll
    for (int h = 0; h < 2; h++) {
      float x[7];
#pragma unroll
      for (int p = 0; p < 6; p++) x[p] = d[h * 16 + (p >> 1) * 4 + (p & 1) + 2 * r] * L2E;
      x[6] = d[12 + h + 2 * r] * L2E;
      float mx = x[0], mn = x[0];
#pragma unroll
      for (int p = 1; p < 7; p++) { mx = fmaxf(mx, x[p]); mn = fminf(mn, x[p]); }
      mx = fmaxf(mx, __shfl_xor_sync(~0u, mx, 1)); mn = fminf(mn, __shfl_xor_sync(~0u, mn, 1));
      mx = fmaxf(mx, __shfl_xor_sync(~0u, mx, 2)); mn = fminf(mn, __shfl_xor_sync(~0u, mn, 2));
      float ep[7], en[7], sp = 0.f, sn = 0.f;
#pragma unroll
      for (int p = 0; p < 7; p++) { ep[p] = ex2(x[p] - mx); en[p] = ex2(mn - x[p]); sp += ep[p]; sn += en[p]; }
      sp = rcp(qsum(sp)); sn = rcp(qsum(sn));
#pragma unroll
      for (int p = 0; p < 7; p++) sink(r, h, p, pack(ep[p] * sp, en[p] * sn));
    }
}
__device__ __forceinline__ void phi_gemm(const float (&x)[28], float (&y)[28], uint32_t wphi) {
  uint32_t f[14];
#pragma unroll
  for (int j = 0; j < 14; j++) f[j] = pack(x[2 * j], x[2 * j + 1]);
  wg_fence();
#pragma unroll
  for (int ks = 0; ks < 3; ks++) wgmma_rs56(y, f[4 * ks], f[4 * ks + 1], f[4 * ks + 2], f[4 * ks + 3], mkdesc(wphi >> 4, ks * 2048, 1024, 1024, 1), ks);
  wgmma_rs56(y, f[12], f[13], 0u, 0u, mkdesc(wphi >> 4, 3 * 2048, 1024, 1024, 1), 1);
  wg_commit();
}
__device__ __forceinline__ void ln_publish(uint32_t (&xw)[4][4], float* sLN, int warp, int lane, uint4* fb, uint32_t tag) {
  const int g = lane >> 2; const bool full = warp < 4;
  float s0 = 0.f, s1 = 0.f;
#pragma unroll
  for (int u = 0; u < 4; u++) {
    s0 += (blo(xw[u][0]) + bhi(xw[u][0])) + (blo(xw[u][2]) + bhi(xw[u][2]));
    s1 += (blo(xw[u][1]) + bhi(xw[u][1])) + (blo(xw[u][3]) + bhi(xw[u][3]));
  }
  const float rc = full ? 1.f / 64 : 1.f / 48;
  s0 = qsum(s0); s1 = qsum(s1);
  const float a0 = s0 * rc, a1 = s1 * rc;
  float v0 = 0.f, v1 = 0.f;
#pragma unroll
  for (int u = 0; u < 4; u++)
    if (u < 3 || full) {
#pragma unroll
      for (int k = 0; k < 4; k += 2) {
        float a = blo(xw[u][k]) - a0, b = bhi(xw[u][k]) - a0, c2 = blo(xw[u][k + 1]) - a1, d2 = bhi(xw[u][k + 1]) - a1;
        v0 += a * a + b * b; v1 += c2 * c2 + d2 * d2;
      }
    }
  v0 = qsum(v0); v1 = qsum(v1);
  if ((lane & 3) == 0) *(float4*)(sLN + (g * 8 + warp) * 4) = make_float4(s0, v0, s1, v1);
  bar_cons();
  const float4 ea = *(const float4*)(sLN + (g * 8 + (lane & 3)) * 4), eb = *(const float4*)(sLN + (g * 8 + 4 + (lane & 3)) * 4);
  const float m0 = qsum(ea.x + eb.x) * (1.f / 448), m1 = qsum(ea.z + eb.z) * (1.f / 448);
  const float d0 = ea.x * (1.f / 64) - m0, d1 = eb.x * (1.f / 48) - m0, d2 = ea.z * (1.f / 64) - m1, d3 = eb.z * (1.f / 48) - m1;
  v0 = qsum(ea.y + eb.y + 64.f * d0 * d0 + 48.f * d1 * d1); v1 = qsum(ea.w + eb.w + 64.f * d2 * d2 + 48.f * d3 * d3);
  const float r0 = rsqrtf(v0 * (1.f / 448) + 1e-5f), r1 = rsqrtf(v1 * (1.f / 448) + 1e-5f), n0 = -m0 * r0, n1 = -m1 * r1;
#pragma unroll
  for (int u = 0; u < 4; u++)
    if (u < 3 || full)
      stll(fb + XN + u * 256, tg(pack(fmaf(blo(xw[u][0]), r0, n0), fmaf(bhi(xw[u][0]), r0, n0)), tag), pack(fmaf(blo(xw[u][1]), r1, n1), fmaf(bhi(xw[u][1]), r1, n1)),
           pack(fmaf(blo(xw[u][2]), r0, n0), fmaf(bhi(xw[u][2]), r0, n0)), pack(fmaf(blo(xw[u][3]), r1, n1), fmaf(bhi(xw[u][3]), r1, n1)));
}

__global__ void __launch_bounds__(384, 1)
fused_kernel(const __grid_constant__ CUtensorMap mQKV, const __grid_constant__ CUtensorMap mWO, const __grid_constant__ CUtensorMap mW1,
             const __grid_constant__ CUtensorMap mW1b, const __grid_constant__ CUtensorMap mW2, const __grid_constant__ CUtensorMap mW2b, const __nv_bfloat16* __restrict__ x, const __nv_bfloat16* __restrict__ wphi,
             const __nv_bfloat16* __restrict__ wo, const __nv_bfloat16* __restrict__ w1, const __nv_bfloat16* __restrict__ b1,
             const __nv_bfloat16* __restrict__ w2, const __nv_bfloat16* __restrict__ b2, __nv_bfloat16* __restrict__ out) {
  extern __shared__ __align__(1024) uint8_t sm[];
  const uint32_t sb = s2u(sm);
  const int tid = threadIdx.x, warp = __shfl_sync(~0u, tid >> 5, 0), lane = tid & 31, t = blockIdx.x >> 3, c = blockIdx.x & 7;
  const uint32_t bfull = sb + OFF_BAR, bempty = bfull + 8 * NST;

  if (tid == 256) {
    for (int s = 0; s < NST; s++) { mbar_init(bfull + 8 * s, 1); mbar_init(bempty + 8 * s, 8); }
    asm volatile("fence.mbarrier_init.release.cluster;" ::: "memory");
    fence_async();
  }
  __syncthreads();
  if (warp >= 8) {
    asm volatile("setmaxnreg.dec.sync.aligned.u32 24;");
    auto issue = [&](int i, int s) {
      const uint32_t dst = sb + s * STAGE, bar = bfull + 8 * s;
      mbar_expect(bar, STAGE);
      if (i < 4) { tma2d(dst, &mQKV, 448 + 56 * c, 112 * i, bar); tma2d(dst + 14336, &mQKV, 896 + 56 * c, 112 * i, bar); }
      else if (i < 6) { tma2d(dst, &mQKV, 56 * c, 224 * (i & 1), bar); tma2d(dst + 14336, &mQKV, 56 * c, 224 * (i & 1) + 112, bar); }
      else if (i < 8) tma2d(dst, &mWO, 64 * c, 224 * (i & 1), bar);
      else if (i < 15) { tma3d(dst, &mW1, 0, 64 * (i - 8), 3 * c, bar); tma2d(dst + 24576, &mW1b, 1536 + 32 * c, 64 * (i - 8), bar); }
      else { tma2d(dst, &mW2, 64 * (i - 15), 192 * c, bar); tma2d(dst + 24576, &mW2b, 64 * (i - 15), 1536 + 32 * c, bar); }
    };
    if (tid == 256) {
      int s = 0; uint32_t ph = 1;
      for (int n = 0; n < 44; n++) {
        mbar_wait(bempty + 8 * s, ph);
        issue(n >= 22 ? n - 22 : n, s);
        if (++s == NST) { s = 0; ph ^= 1; }
      }
    } else if (warp == 9) {
      mbar_wait(bfull + 8 * 3, 0);
      if (lane == 0) {
        l2pf((const uint8_t*)wo + blockIdx.x * 3136, 3136);
        l2pf((const uint8_t*)w1 + blockIdx.x * 12544, 12544);
        l2pf((const uint8_t*)w2 + blockIdx.x * 12544, 12544);
      }
      if (blockIdx.x < 112) {
        const uint2* wp = (const uint2*)(w1 + (size_t)(lane >> 2) * 1792 + blockIdx.x * 16 + (lane & 3) * 4);
        float s0 = 0.f, s1 = 0.f, s2 = 0.f, s3 = 0.f;
#pragma unroll 8
        for (int i = 0; i < 56; i++) { const uint2 v = __ldg(wp + i * 8 * 448); s0 += blo(v.x); s1 += bhi(v.x); s2 += blo(v.y); s3 += bhi(v.y); }
#pragma unroll 1
        for (int o = 4; o < 32; o <<= 1) { s0 += __shfl_xor_sync(~0u, s0, o); s1 += __shfl_xor_sync(~0u, s1, o); s2 += __shfl_xor_sync(~0u, s2, o); s3 += __shfl_xor_sync(~0u, s3, o); }
        if (lane < 4) stll(g_CS + blockIdx.x * 4 + lane, tg(__float_as_uint(s0), 1), __float_as_uint(s1), __float_as_uint(s2), __float_as_uint(s3));
      }
      asm volatile("bar.sync 6, 96;" ::: "memory");
#pragma unroll 1
      for (int i = 0; i < 2; i++) {
        const int e = lane < 28 ? lane + 28 * i : 0;
        uint4 cv[1];
        const int e4 = e < 48 ? 48 * c + e : 336 + 8 * c + e;
        ll_issue<0, 1>(cv, g_CS + e4, 0); ll_check<0, 1, false>(cv, g_CS + e4, 0, 1u);
        const uint2 bb = __ldg((const uint2*)b1 + e4);
        const uint32_t h0 = pack(__uint_as_float(cv[0].x), __uint_as_float(cv[0].y)), h1 = pack(__uint_as_float(cv[0].z), __uint_as_float(cv[0].w));
        const uint32_t l0 = pack(__uint_as_float(cv[0].x) - blo(h0), __uint_as_float(cv[0].y) - bhi(h0)), l1 = pack(__uint_as_float(cv[0].z) - blo(h1), __uint_as_float(cv[0].w) - bhi(h1));
#pragma unroll 1
        for (int r = 0; r < 8; r++) {
          const uint32_t ad = sb + OFF_CB + (e >> 3) * 512 + r * 64 + ((((e >> 1) ^ (r >> 1)) & 3) << 4) + (e & 1) * 8;
          sts32(ad, r < 2 ? h0 : r == 2 ? l0 : r < 5 ? bb.x : 0u); sts32(ad + 4, r < 2 ? h1 : r == 2 ? l1 : r < 5 ? bb.y : 0u);
        }
      }
      fence_async();
      asm volatile("bar.arrive 4, 288;" ::: "memory");
    } else if (warp >= 10) {
      const int h = warp - 10;
      uint32_t wv[13];
#pragma unroll
      for (int i = 0; i < 13; i++) { const int e = lane + 32 * i; wv[i] = e < 392 ? __ldg((const uint32_t*)wphi + (2 * c + h) * 392 + e) : 0u; }
#pragma unroll 1
      for (int i = 0; i < 8; i++) sts128(sb + OFF_WPHI + (h * 256 + i * 32 + lane) * 16, 0, 0, 0, 0);
      asm volatile("bar.arrive 6, 96;" ::: "memory");
#pragma unroll 1
      for (int i = 0; i < 4; i++) sts128(sb + OFF_PHIK + sw128(h * 128 + i * 32 + lane, 56), 0, 0, 0, 0);
      asm volatile("bar.sync 5, 64;" ::: "memory");
#pragma unroll
      for (int i = 0; i < 13; i++) {
        const int e = lane + 32 * i, d = e / 14, f2 = 2 * (e - 14 * d), k = 28 * h + d;
        if (e < 392) {
          if (f2 < 24) sts32(sb + OFF_WPHI + sw128(k, 32 * h + f2), wv[i]);
          else { sts16(sb + OFF_WPHI + sw128(k, 2 * f2 - 24 + h), wv[i]); sts16(sb + OFF_WPHI + sw128(k, 2 * f2 - 22 + h), wv[i] >> 16); }
        }
      }
      fence_async();
      asm volatile("bar.arrive 3, 320;" ::: "memory");
    }
  } else {
  asm volatile("setmaxnreg.inc.sync.aligned.u32 240;");

  const int wg = warp >> 2, g = lane >> 2, q = lane & 3;
  const int row0 = warp * 16 + g;
#define PTRS const int ln_ = laneid(); \
  uint4* const fm = g_F + ((t * 8 + warp) * 28) * 32 + ln_;            \
  uint4* const fr = g_F + ((t * 8 + c) * 28 + warp) * 32 + ln_;        \
  uint4* const sf = fm + (7 * (c >> 1) + 4 * (c & 1)) * 32;             \
  uint2* const f2 = (uint2*)(fm - ln_) + ln_;                           \
  uint2* const sh = f2 + (7 * (c >> 1) + 3) * 64 + 32 * (c & 1);        \
  uint32_t* const hme = g_H + (t * 8 + warp) * 8 + c; \
  const uint32_t* const hrow = g_H + (t * 8 + warp) * 8 + (ln_ & 7); \
  (void)fm; (void)fr; (void)sf; (void)f2; (void)sh; (void)hme; (void)hrow;
  float* sLN = (float*)(sm + OFF_V);
  const uint32_t sPK = sb + OFF_PHIK, sV = sb + OFF_V, sW = sb + OFF_WPHI;
  #define XOFF(l) ((t * 128 + c * 16 + ((l) >> 2)) * 448 + warp * 16 + 2 * ((l) & 3))
  MARK(0);
  uint32_t xw[4][4];
  {
    const uint32_t* xp = (const uint32_t*)(x + XOFF(lane));
#pragma unroll
    for (int u = 0; u < 4; u++) {
      if (u < 3 || wg == 0) { xw[u][0] = __ldg(xp + u * 64); xw[u][1] = __ldg(xp + u * 64 + 1792); xw[u][2] = __ldg(xp + u * 64 + 4); xw[u][3] = __ldg(xp + u * 64 + 1796); }
      else { xw[u][0] = xw[u][1] = xw[u][2] = xw[u][3] = 0; }
    }
  }
  int cs = 0, rs = 0; uint32_t cph = 0;
  auto acquire = [&]() -> uint32_t { mbar_wait(bfull + 8 * cs, cph); const uint32_t a = (sb >> 4) + cs * (STAGE >> 4); if (++cs == NST) { cs = 0; cph ^= 1; } return a; };
  auto release = [&]() { if (lane == 0) mbar_arrive(bempty + 8 * rs); if (++rs == NST) rs = 0; };

#pragma unroll 1
  for (int L = 0; L < 2; L++) {
    const uint32_t tag = 1 - L;
    uint32_t phq[2][2][7];
    const uint32_t hs = 10 * L;
    {
      PTRS
      ln_publish(xw, sLN, warp, lane, fr, tag);
      hint_post(hme, hs + 1, lane);
#pragma unroll
      for (int u = 0; u < 4; u++) if (u < 3 || wg == 0) stll(fr + XR + u * 256, tg(xw[u][0], tag), xw[u][1], xw[u][2], xw[u][3]);
    }
    MARK(1 + L * 19);
    {
      PTRS
      uint4 a[28];
      const uint4* pa = fm + XN;
      hint_wait(g_H + (t * 8 + (ln_ & 7)) * 8 + warp, hs + 1); ll_issue<0, 28>(a, pa, 32);
      MARK(2 + L * 19);
      float ak[28], av[28], aq[28], pp[28];
#define KVSTAGE(i) { ll_check<7 * i, 7, false>(a, pa, 32, tag); const uint32_t st = acquire(); wg_fence(); \
      _Pragma("unroll") for (int ks = 0; ks < 7; ks++) { const uint4 f = a[7 * i + ks]; \
        wgmma_rs56(ak, f.x, f.y, f.z, f.w, mkdesc(st, ks * 2048, 1024, 1024, 1), i | ks); \
        wgmma_rs56(av, f.x, f.y, f.z, f.w, mkdesc(st, 14336 + ks * 2048, 1024, 1024, 1), i | ks); } \
      wg_commit(); if (i > 0) { wg_wait<1>(); release(); } }
      KVSTAGE(0) KVSTAGE(1) KVSTAGE(2) KVSTAGE(3)
      wg_wait<0>(); release(); regfence(ak); regfence(av);
      MARK(3 + L * 19);
      if (L == 0) asm volatile("bar.sync 3, 320;" ::: "memory");
      phi_gemm(ak, pp, sW);
#pragma unroll
      for (int j = 0; j < 7; j++) {
        const int n = 8 * j + 2 * q, n2 = n < 28 ? n : n + 4;
        sts32(sV + sw128(row0, n2), pack(av[4 * j], av[4 * j + 1])); sts32(sV + sw128(row0 + 8, n2), pack(av[4 * j + 2], av[4 * j + 3]));
      }
      { const int n2 = 28 + 2 * (q & 1) + 32 * (q >> 1); const uint32_t v = (q & 1) ? 0u : 0x3F80u; sts32(sV + sw128(row0, n2), v); sts32(sV + sw128(row0 + 8, n2), v); }
      wg_wait<0>(); regfence(pp);
      hedgehog<0, 2>(pp, [&](int r, int h, int p, uint32_t v) { sts32(sPK + h * 16384 + sw128(row0 + 8 * r, 8 * p + 2 * q), v); });
      fence_async();
      bar_cons();
      MARK(4 + L * 19);
      float kv[32];
      wg_fence();
#pragma unroll
      for (int ks = 0; ks < 8; ks++) wgmma_ss64(kv, mkdesc((sPK + wg * 16384) >> 4, ks * 2048, 1024, 1024, 1), mkdesc(sV >> 4, ks * 2048, 1024, 1024, 1), ks);
      wg_commit(); wg_wait<0>(); regfence(kv);
      const int ln2 = laneid();
#pragma unroll
      for (int u = 0; u < 4; u++) {
        float e[4];
#pragma unroll
        for (int i = 0; i < 4; i++) e[i] = wg ? kv[16 + 4 * u + i] : kv[4 * u + i];
        stll(g_KVP + (c * 16 + t) * 1024 + wg * 512 + u * 128 + (warp & 3) * 32 + ln2, tg(__float_as_uint(e[0]), tag), __float_as_uint(e[1]), __float_as_uint(e[2]), __float_as_uint(e[3]));
      }
      MARK(5 + L * 19);
      uint4 k4[4];
      const uint4* pk = g_KVP + (c * 16 + 4 * (ln2 & 3)) * 1024 + 64 * t + warp * 8 + (ln2 >> 2);
#pragma unroll
      for (int i = 0; i < 2; i++) {
        const uint32_t st = acquire(); wg_fence();
#pragma unroll
        for (int ks = 0; ks < 14; ks++) { const uint4 f = a[14 * i + ks]; wgmma_rs56(aq, f.x, f.y, f.z, f.w, mkdesc(st, ks * 2048, 1024, 1024, 1), i | ks); }
        wg_commit();
        if (i == 0) ll_issue<0, 4>(k4, pk, 1024);
      }
      ll_check<0, 4, false>(k4, pk, 1024, tag);
      float s0 = 0, s1 = 0, s2 = 0, s3 = 0;
#pragma unroll
      for (int i = 0; i < 4; i++) { s0 += __uint_as_float(k4[i].x); s1 += __uint_as_float(k4[i].y); s2 += __uint_as_float(k4[i].z); s3 += __uint_as_float(k4[i].w); }
      s0 = qsum(s0); s1 = qsum(s1); s2 = qsum(s2); s3 = qsum(s3);
      if (q == 0) stll2(g_KVR + c * 1024 + 64 * t + warp * 8 + (ln2 >> 2), tg(pack(s0, s1), tag), pack(s2, s3));
      MARK(6 + L * 19);
      wg_wait<0>(); release(); release(); regfence(aq);
      phi_gemm(aq, pp, sW);
      bar_cons();
#pragma unroll
      for (int i = 0; i < 4; i++) sts128(sV + warp * 2048 + (lane + i * 32) * 16, 0, 0, 0, 0);
      wg_wait<0>(); regfence(pp);
      hedgehog<0, 1>(pp, [&](int r, int h, int p, uint32_t v) { phq[r][h][p] = v; });
      uint2 r[4];
      const uint2* pr = g_KVR + c * 1024 + wg * 512 + (warp & 3) * 32 + ln2;
#pragma unroll
      for (int u = 0; u < 4; u++) r[u] = ldll2(pr + u * 128);
      hedgehog<1, 2>(pp, [&](int r, int h, int p, uint32_t v) { phq[r][h][p] = v; });
      MARK(7 + L * 19);
#pragma unroll 1
      for (int it = 0; it < SPIN; it++) {
        if (!__any_sync(~0u, ((r[0].x ^ tag) | (r[1].x ^ tag) | (r[2].x ^ tag) | (r[3].x ^ tag)) & 1)) break;
#pragma unroll
        for (int u = 0; u < 4; u++) r[u] = ldll2(pr + u * 128);
      }
#pragma unroll
      for (int u = 0; u < 4; u++) {
        const int d = 8 * u + 2 * q;
        if (d < 28) { sts32(sV + sw128(row0, 28 * wg + d), r[u].x); sts32(sV + sw128(row0 + 8, 28 * wg + d), r[u].y); }
        else if (d == 28) {
#pragma unroll
          for (int j = 0; j < 4; j++) { sts16(sV + sw128(row0, 56 + 2 * j + wg), r[u].x); sts16(sV + sw128(row0 + 8, 56 + 2 * j + wg), r[u].y); }
        }
      }
      fence_async();
      bar_cons();
      MARK(8 + L * 19);
      float o[32];
      wg_fence();
#pragma unroll
      for (int ks = 0; ks < 8; ks++) {
        const int h = ks >> 2, p = 2 * (ks & 3);
        wgmma_rs64(o, phq[0][h][p], phq[1][h][p], p < 6 ? phq[0][h][p < 6 ? p + 1 : 0] : 0u, p < 6 ? phq[1][h][p < 6 ? p + 1 : 0] : 0u, mkdesc(sV >> 4, ks * 2048, 1024, 1024, 1), ks);
      }
      wg_commit(); wg_wait<0>(); regfence(o);
      const float iA0 = rcp(o[28] + 1e-6f), iB0 = rcp(o[29] + 1e-6f), iA1 = rcp(o[30] + 1e-6f), iB1 = rcp(o[31] + 1e-6f);
      uint32_t w[14];
      { PTRS
#pragma unroll
      for (int j = 0; j < 7; j++) {
        const bool hb = 8 * j + 2 * q >= 28; const float i0 = hb ? iB0 : iA0, i1 = hb ? iB1 : iA1;
        w[2 * j] = pack(o[4 * j] * i0, o[4 * j + 1] * i0); w[2 * j + 1] = pack(o[4 * j + 2] * i1, o[4 * j + 3] * i1);
        if (j == 0 || ((j ^ c) & 1) == 0) w[2 * j] = tg(w[2 * j], tag);
      }
      slice_store(sf + OO, sh + 2 * OO, w, c & 1);
      hint_post(hme, hs + 2, lane); }
    }
    MARK(9 + L * 19);
    if (c < 7) {
      PTRS
      uint4 xr[4];
      ll_issue<0, 4>(xr, fm + XR + 128 * c, 32);
      uint4 a[28];
      const uint4* pa = fm + OO;
      hint_wait(hrow, hs + 2);
      MARK(10 + L * 19);
      ll_issue<0, 28, true>(a, pa, 32, f2 + 2 * OO);
      float y[32];
      uint32_t st;
#define WOSTEP(i) { ll_check<7 * i, 7, true>(a, pa, 32, tag, f2 + 2 * OO); if (!(i & 1)) st = acquire(); wg_fence(); \
      _Pragma("unroll") for (int ks = 0; ks < 7; ks++) { const uint4 f = a[7 * i + ks]; \
        wgmma_rs64(y, f.x, f.y, f.z, f.w, mkdesc(st, ((i & 1) * 7 + ks) * 2048, 1024, 1024, 1), i | ks); } wg_commit(); }
      WOSTEP(0) WOSTEP(1) WOSTEP(2) WOSTEP(3)
      ll_check<0, 4, false>(xr, fm + XR + 128 * c, 32, tag);
      wg_wait<0>(); regfence(y);
      MARK(11 + L * 19);
      float s0 = 0.f, s1 = 0.f;
#pragma unroll
      for (int u = 0; u < 4; u++) {
        xr[u].x = tg(pack(blo(xr[u].x) + y[8 * u], bhi(xr[u].x) + y[8 * u + 1]), tag); xr[u].y = pack(blo(xr[u].y) + y[8 * u + 2], bhi(xr[u].y) + y[8 * u + 3]);
        xr[u].z = pack(blo(xr[u].z) + y[8 * u + 4], bhi(xr[u].z) + y[8 * u + 5]); xr[u].w = pack(blo(xr[u].w) + y[8 * u + 6], bhi(xr[u].w) + y[8 * u + 7]);
        stll(fm + X1 + 128 * c + u * 32, xr[u].x, xr[u].y, xr[u].z, xr[u].w);
      }
      hint_post(hme, hs + 3, lane);
#pragma unroll
      for (int u = 0; u < 4; u++) {
        y[8 * u] = blo(xr[u].x); y[8 * u + 1] = bhi(xr[u].x); y[8 * u + 2] = blo(xr[u].y); y[8 * u + 3] = bhi(xr[u].y);
        y[8 * u + 4] = blo(xr[u].z); y[8 * u + 5] = bhi(xr[u].z); y[8 * u + 6] = blo(xr[u].w); y[8 * u + 7] = bhi(xr[u].w);
        s0 += (y[8 * u] + y[8 * u + 1]) + (y[8 * u + 4] + y[8 * u + 5]); s1 += (y[8 * u + 2] + y[8 * u + 3]) + (y[8 * u + 6] + y[8 * u + 7]);
      }
      s0 = qsum(s0) * (1.f / 64); s1 = qsum(s1) * (1.f / 64);
      float v0 = 0.f, v1 = 0.f;
#pragma unroll
      for (int j = 0; j < 8; j++) {
        const float d0 = y[4 * j] - s0, d1 = y[4 * j + 1] - s0, d2 = y[4 * j + 2] - s1, d3 = y[4 * j + 3] - s1;
        v0 += d0 * d0 + d1 * d1; v1 += d2 * d2 + d3 * d3;
      }
      v0 = qsum(v0); v1 = qsum(v1);
      if (q == 0) stll(g_ST + ((t * 8 + warp) * 8 + c) * 8 + (ln_ >> 2), tg(__float_as_uint(s0), tag), __float_as_uint(v0), __float_as_uint(s1), __float_as_uint(v1));
    } else {
      PTRS
      hint_post(hme, hs + 3, lane);
      acquire(); acquire();
      MARK(10 + L * 19); MARK(11 + L * 19);
    }
    uint32_t hf[56];
    float rr0, rr1;
    {
      PTRS
      uint4 a[28];
      const uint4* pa = fm + X1;
      hint_wait(hrow, hs + 3);
      MARK(12 + L * 19);
      ll_issue<0, 4>(a, pa, 32); ll_check<0, 4, false>(a, pa, 32, tag); ll_issue<4, 12>(a, pa, 32);
      release(); release();
      float y[96], z[16];
#define F1STAGE(i) { if (i > 0) ll_check<4 * i, 4, false>(a, pa, 32, tag); const uint32_t st = acquire(); wg_fence(); \
      _Pragma("unroll") for (int ks = 0; ks < 4; ks++) { const uint4 f = a[4 * i + ks]; \
        wgmma_rs192(y, f.x, f.y, f.z, f.w, mkdesc(st, ks * 2048, 8192, 1024, 1), i | ks); \
        wgmma_rs32(z, f.x, f.y, f.z, f.w, mkdesc(st, 24576 + ks * 1024, 512, 512, 2), i | ks); } \
      wg_commit(); if (i > 0) { wg_wait<1>(); release(); if (i < 4) ll_issue<(i < 4 ? 4 * i + 12 : 0), 4>(a, pa, 32); } }
      F1STAGE(0) MARK(13 + L * 19); F1STAGE(1) F1STAGE(2) F1STAGE(3)
      uint4 sv[2];
      const uint4* ps = g_ST + ((t * 8 + warp) * 8 + 2 * (laneid() & 3)) * 8 + (laneid() >> 2);
      ll_issue<0, 2>(sv, ps, q < 3 ? 8 : 0);
      F1STAGE(4)
      ll_check<0, 2, false>(sv, ps, q < 3 ? 8 : 0, tag);
      const float wb = q < 3 ? 1.f : 0.f;
      const float ma = __uint_as_float(sv[0].x), mb = __uint_as_float(sv[1].x), mc = __uint_as_float(sv[0].z), md = __uint_as_float(sv[1].z);
      const float m0 = qsum(ma + wb * mb) * (1.f / 7), m1 = qsum(mc + wb * md) * (1.f / 7);
      const float v0 = qsum(__uint_as_float(sv[0].y) + 64.f * (ma - m0) * (ma - m0) + wb * (__uint_as_float(sv[1].y) + 64.f * (mb - m0) * (mb - m0)));
      const float v1 = qsum(__uint_as_float(sv[0].w) + 64.f * (mc - m1) * (mc - m1) + wb * (__uint_as_float(sv[1].w) + 64.f * (md - m1) * (md - m1)));
      const float e0 = v0 * (1.f / 448) + 1e-5f, e1 = v1 * (1.f / 448) + 1e-5f;
      rr0 = 1.f / e0; rr1 = 1.f / e1;
      auto fold = [&](float m, float sd) -> uint32_t {
        const float mh = blo(pack(-m, 0.f)), sh_ = blo(pack(sd, 0.f));
        return q == 0 ? pack(mh, -m - mh) : q == 1 ? pack(mh, sh_) : q == 2 ? pack(sd - sh_, 0.f) : 0u;
      };
      const uint32_t fa = fold(m0, sqrtf(e0)), fb = fold(m1, sqrtf(e1));
      if (L == 0) asm volatile("bar.sync 4, 288;" ::: "memory");
      wg_fence();
      wgmma_rs192(y, fa, fb, 0u, 0u, mkdesc((sb + OFF_CB) >> 4, 0, 512, 0, 2), 1);
      wgmma_rs32(z, fa, fb, 0u, 0u, mkdesc((sb + OFF_CB) >> 4, 3072, 512, 0, 2), 1);
      F1STAGE(5) F1STAGE(6)
      wg_wait<0>(); release(); regfence(y); regfence(z);
      MARK(14 + L * 19);
#pragma unroll
      for (int j = 0; j < 56; j++) {
        uint32_t r; asm("cvt.rn.relu.bf16x2.f32 %0, %1, %2;" : "=r"(r) : "f"(j < 48 ? y[j < 48 ? 2 * j + 1 : 0] : z[j < 48 ? 0 : 2 * j - 95]), "f"(j < 48 ? y[j < 48 ? 2 * j : 0] : z[j < 48 ? 0 : 2 * j - 96]));
        asm("mul.bf16x2 %0, %1, %1;" : "=r"(hf[j]) : "r"(r));
      }
    }
    MARK(15 + L * 19);
    {
      PTRS
      float ya[32], yb[32];
      uint4* pp = g_P + ((t * 8 + warp) * 8 + c) * 28 * 32 + ln_;
#define F2STORE(j, Y) { regfence(Y); _Pragma("unroll") for (int u = 0; u < 4; u++) \
      stll(pp + (4 * (j) + u) * 32, tg(pack(Y[8 * u] * rr0, Y[8 * u + 1] * rr0), tag), pack(Y[8 * u + 2] * rr1, Y[8 * u + 3] * rr1), \
           pack(Y[8 * u + 4] * rr0, Y[8 * u + 5] * rr0), pack(Y[8 * u + 6] * rr1, Y[8 * u + 7] * rr1)); if ((j) >= 5) hint_post(hme, hs + (4 + (j)), lane); }
#define F2PASS(j, Y, Z) { const uint32_t st = acquire(); wg_fence(); \
      _Pragma("unroll") for (int ks = 0; ks < 14; ks++) wgmma_rs64(Y, hf[4 * ks], hf[4 * ks + 1], hf[4 * ks + 2], hf[4 * ks + 3], mkdesc(st, ks * 2048, 1024, 1024, 1), ks); \
      wg_commit(); if (j > 0) { wg_wait<1>(); release(); F2STORE(j - 1, Z) } }
      const uint4* pr = g_P + ((t * 8 + c) * 8 * 28 + warp) * 32 + ln_;
      uint4 p[8], p2[8]; uint2 xa, xb, xc, xd; uint32_t ba, bb, bc, bd;
#define RISSUE(m, P, XA, XB, BA, BB) { ll_issue<0, 8>(P, pr + (m) * 256, 896); \
      { const uint4 v_ = ldll(fr + X1 + (m) * 256); XA = make_uint2(v_.x, v_.y); XB = make_uint2(v_.z, v_.w); } \
      const uint32_t* bp = (const uint32_t*)(b2 + 128 * (m) + 16 * warp) + (ln_ & 3); BA = __ldg(bp); BB = __ldg(bp + 4); }
#define REDU(m, P, XA, XB, BA, BB) { ll_check<0, 8, false>(P, pr + (m) * 256, 896, tag); \
      float e[8] = {blo(XA.x) + blo(BA), bhi(XA.x) + bhi(BA), blo(XA.y) + blo(BA), bhi(XA.y) + bhi(BA), blo(XB.x) + blo(BB), bhi(XB.x) + bhi(BB), blo(XB.y) + blo(BB), bhi(XB.y) + bhi(BB)}; \
      _Pragma("unroll") for (int i = 0; i < 8; i++) { e[0] += blo(P[i].x); e[1] += bhi(P[i].x); e[2] += blo(P[i].y); e[3] += bhi(P[i].y); \
        e[4] += blo(P[i].z); e[5] += bhi(P[i].z); e[6] += blo(P[i].w); e[7] += bhi(P[i].w); } \
      xw[m][0] = pack(e[0], e[1]); xw[m][1] = pack(e[2], e[3]); xw[m][2] = pack(e[4], e[5]); xw[m][3] = pack(e[6], e[7]); }
      F2PASS(0, ya, yb) F2PASS(1, yb, ya) F2PASS(2, ya, yb) F2PASS(3, yb, ya) F2PASS(4, ya, yb)
      RISSUE(0, p, xa, xb, ba, bb)
      F2PASS(5, yb, ya)
      REDU(0, p, xa, xb, ba, bb)
      F2PASS(6, ya, yb)
      RISSUE(1, p, xa, xb, ba, bb)
      wg_wait<0>(); release(); F2STORE(6, ya)
      MARK(16 + L * 19);
      const uint32_t* hred = g_H + (t * 8 + c) * 8 + (ln_ & 7);
      if (wg) hint_wait(hred, hs + 9);
      RISSUE(2, p2, xc, xd, bc, bd)
      REDU(1, p, xa, xb, ba, bb)
      if (wg == 0) { hint_wait(hred, hs + 10); RISSUE(3, p, xa, xb, ba, bb) }
      MARK(17 + L * 19);
      REDU(2, p2, xc, xd, bc, bd)
      if (wg == 0) REDU(3, p, xa, xb, ba, bb) else { xw[3][0] = xw[3][1] = xw[3][2] = xw[3][3] = 0; }
    }
    MARK(18 + L * 19);
  }
  {
    uint32_t* op = (uint32_t*)(out + XOFF(laneid()));
#pragma unroll
    for (int u = 0; u < 4; u++) if (u < 3 || wg == 0) { op[u * 64] = xw[u][0]; op[u * 64 + 1792] = xw[u][1]; op[u * 64 + 4] = xw[u][2]; op[u * 64 + 1796] = xw[u][3]; }
    if (warp == 7 && blockIdx.x < 112 && lane < 4) stll(g_CS + blockIdx.x * 4 + lane, 0, 0, 0, 0);
  }
  MARK(38);
  }
}

typedef CUresult (*EncFn)(CUtensorMap*, CUtensorMapDataType, cuuint32_t, void*, const cuuint64_t*, const cuuint64_t*, const cuuint32_t*, const cuuint32_t*,
                          CUtensorMapInterleave, CUtensorMapSwizzle, CUtensorMapL2promotion, CUtensorMapFloatOOBfill);

extern "C" void kernel_launch(void* const* d_in, const int* in_sizes, int n_in, void* d_out, int out_size) {
  static EncFn enc = nullptr;
  if (!enc) {
    void* fn = nullptr; cudaDriverEntryPointQueryResult qr;
    cudaGetDriverEntryPoint("cuTensorMapEncodeTiled", &fn, cudaEnableDefault, &qr);
    enc = (EncFn)fn;
    cudaFuncSetAttribute(fused_kernel, cudaFuncAttributeMaxDynamicSharedMemorySize, SMEM_BYTES);
  }
  CUtensorMap mQKV, mWO, mW1, mW1b, mW2, mW2b;
  const cuuint32_t es[3] = {1, 1, 1};
  auto enc2 = [&](CUtensorMap* m, void* p, cuuint64_t cols, cuuint64_t rows, cuuint32_t bc, cuuint32_t br) {
    const cuuint64_t dims[2] = {cols, rows}, str[1] = {cols * 2}; const cuuint32_t box[2] = {bc, br};
    enc(m, CU_TENSOR_MAP_DATA_TYPE_BFLOAT16, 2, p, dims, str, box, es, CU_TENSOR_MAP_INTERLEAVE_NONE,
        bc == 64 ? CU_TENSOR_MAP_SWIZZLE_128B : CU_TENSOR_MAP_SWIZZLE_64B, CU_TENSOR_MAP_L2_PROMOTION_L2_128B, CU_TENSOR_MAP_FLOAT_OOB_FILL_NONE);
  };
  enc2(&mQKV, d_in[1], 1344, 448, 64, 112); enc2(&mWO, d_in[3], 448, 448, 64, 224); enc2(&mW1b, d_in[5], 1792, 448, 32, 64);
  enc2(&mW2, d_in[7], 448, 1792, 64, 192); enc2(&mW2b, d_in[7], 448, 1792, 64, 32);
  {
    const cuuint64_t dims[3] = {64, 448, 28}, str[2] = {3584, 128}; const cuuint32_t box[3] = {64, 64, 3};
    enc(&mW1, CU_TENSOR_MAP_DATA_TYPE_BFLOAT16, 3, d_in[5], dims, str, box, es, CU_TENSOR_MAP_INTERLEAVE_NONE, CU_TENSOR_MAP_SWIZZLE_128B,
        CU_TENSOR_MAP_L2_PROMOTION_L2_128B, CU_TENSOR_MAP_FLOAT_OOB_FILL_NONE);
  }
  typedef const __nv_bfloat16* BP;
  fused_kernel<<<128, 384, SMEM_BYTES>>>(mQKV, mWO, mW1, mW1b, mW2, mW2b, (BP)d_in[0], (BP)d_in[2], (BP)d_in[3], (BP)d_in[5], (BP)d_in[6], (BP)d_in[7], (BP)d_in[8],
                                         (__nv_bfloat16*)d_out);
}
```

```cpp
#include <cuda_runtime.h>
#include <cuda_bf16.h>
#include <cuda.h>
#include <stdint.h>

constexpr int NST = 6, STAGE = 28672;
constexpr int OFF_PHIK = NST * STAGE;
constexpr int OFF_V = OFF_PHIK + 32768;
constexpr int OFF_WPHI = OFF_V + 16384;
constexpr int OFF_CB = OFF_WPHI + 7168;
constexpr int OFF_BAR = OFF_CB + 3584;
constexpr int SMEM_BYTES = OFF_BAR + 16 * NST;
constexpr int FR = 16 * 8 * 28 * 32;
constexpr int SPIN = 1 << 18;
#define PACE 2

__device__ uint4 g_F[4 * FR];
constexpr int XN = 0, XR = FR, OO = 2 * FR, X1 = 3 * FR;
__device__ uint4 g_P[8 * FR];
__device__ uint4 g_ST[16 * 8 * 8 * 8];
__device__ uint4 g_KVP[8 * 16 * 1024];
__device__ uint2 g_KVR[8 * 1024];
__device__ uint4 g_CS[448];
__device__ uint32_t g_H[16 * 8 * 8];
#define MARK(i)

__device__ __forceinline__ uint32_t s2u(const void* p) { return (uint32_t)__cvta_generic_to_shared(p); }
__device__ __forceinline__ void mbar_init(uint32_t b, uint32_t c) { asm volatile("mbarrier.init.shared::cta.b64 [%0], %1;" ::"r"(b), "r"(c)); }
__device__ __forceinline__ void mbar_expect(uint32_t b, uint32_t tx) { asm volatile("mbarrier.arrive.expect_tx.shared::cta.b64 _, [%0], %1;" ::"r"(b), "r"(tx) : "memory"); }
__device__ __forceinline__ void mbar_arrive_cl(uint32_t b, uint32_t rank) {
  asm volatile("{.reg .b32 r; mapa.shared::cluster.u32 r, %0, %1; mbarrier.arrive.shared::cluster.b64 _, [r];}" ::"r"(b), "r"(rank) : "memory");
}
__device__ __forceinline__ void mbar_wait(uint32_t b, uint32_t ph) {
  uint32_t ok = 0;
#pragma unroll 1
  for (int it = 0; it < SPIN && !ok; it++)
    asm volatile("{.reg .pred p; mbarrier.try_wait.parity.shared::cta.b64 p,[%1],%2; selp.u32 %0,1,0,p;}" : "=r"(ok) : "r"(b), "r"(ph) : "memory");
}
__device__ __forceinline__ void tma2d(uint32_t dst, const CUtensorMap* m, int c0, int c1, uint32_t bar) {
  asm volatile("cp.async.bulk.tensor.2d.shared::cluster.global.mbarrier::complete_tx::bytes.multicast::cluster [%0], [%1, {%3, %4}], [%2], %5;"
               ::"r"(dst), "l"(m), "r"(bar), "r"(c0), "r"(c1), "h"((uint16_t)3) : "memory");
}
__device__ __forceinline__ void tma3d(uint32_t dst, const CUtensorMap* m, int c0, int c1, int c2, uint32_t bar) {
  asm volatile("cp.async.bulk.tensor.3d.shared::cluster.global.mbarrier::complete_tx::bytes.multicast::cluster [%0], [%1, {%3, %4, %5}], [%2], %6;"
               ::"r"(dst), "l"(m), "r"(bar), "r"(c0), "r"(c1), "r"(c2), "h"((uint16_t)3) : "memory");
}
__device__ __forceinline__ void l2pf(const void* p, uint32_t bytes) { asm volatile("cp.async.bulk.prefetch.L2.global [%0], %1;" ::"l"(p), "r"(bytes) : "memory"); }
__device__ __forceinline__ void wg_fence() { asm volatile("wgmma.fence.sync.aligned;" ::: "memory"); }
__device__ __forceinline__ void wg_commit() { asm volatile("wgmma.commit_group.sync.aligned;" ::: "memory"); }
template <int N> __device__ __forceinline__ void wg_wait() { asm volatile("wgmma.wait_group.sync.aligned %0;" ::"n"(N) : "memory"); }
template <int N> __device__ __forceinline__ void regfence(float (&d)[N]) {
#pragma unroll
  for (int i = 0; i < N; i++) asm volatile("" : "+f"(d[i])::"memory");
}
__device__ __forceinline__ void bar_cons() { asm volatile("bar.sync 1, 256;" ::: "memory"); }
__device__ __forceinline__ void fence_async() { asm volatile("fence.proxy.async.shared::cta;" ::: "memory"); }
struct Desc { uint32_t lo, hi; };
__device__ __forceinline__ Desc mkdesc(uint32_t base16, uint32_t off, uint32_t lbo, uint32_t sbo, uint32_t swz) {
  return Desc{base16 + ((off >> 4) | ((lbo >> 4) << 16)), (sbo >> 4) | (swz << 30)};
}
__device__ __forceinline__ uint4 ldll(const uint4* p) {
  uint4 v; asm volatile("ld.relaxed.gpu.global.v4.u32 {%0,%1,%2,%3}, [%4];" : "=r"(v.x), "=r"(v.y), "=r"(v.z), "=r"(v.w) : "l"(p) : "memory"); return v;
}
__device__ __forceinline__ uint2 ldll2(const uint2* p) {
  uint2 v; asm volatile("ld.relaxed.gpu.global.v2.u32 {%0,%1}, [%2];" : "=r"(v.x), "=r"(v.y) : "l"(p) : "memory"); return v;
}
__device__ __forceinline__ void stll(uint4* p, uint32_t x, uint32_t y, uint32_t z, uint32_t w) {
  asm volatile("st.relaxed.gpu.global.v4.u32 [%0], {%1,%2,%3,%4};" ::"l"(p), "r"(x), "r"(y), "r"(z), "r"(w) : "memory");
}
__device__ __forceinline__ void stll2(void* p, uint32_t x, uint32_t y) {
  asm volatile("st.relaxed.gpu.global.v2.u32 [%0], {%1,%2};" ::"l"(p), "r"(x), "r"(y) : "memory");
}
__device__ __forceinline__ int laneid() { int l; asm volatile("mov.u32 %0, %%laneid;" : "=r"(l)); return l; }
__device__ __forceinline__ uint32_t tg(uint32_t w, uint32_t tag) { return (w & ~1u) | tag; }
__device__ __forceinline__ uint32_t pack(float lo, float hi) {
  uint32_t r; asm("cvt.rn.bf16x2.f32 %0, %1, %2;" : "=r"(r) : "f"(hi), "f"(lo)); return r;
}
__device__ __forceinline__ float blo(uint32_t w) { return __uint_as_float(w << 16); }
__device__ __forceinline__ float bhi(uint32_t w) { return __uint_as_float(w & 0xffff0000u); }
__device__ __forceinline__ float ex2(float x) { float r; asm("ex2.approx.ftz.f32 %0, %1;" : "=f"(r) : "f"(x)); return r; }
__device__ __forceinline__ float rcp(float x) { float r; asm("rcp.approx.ftz.f32 %0, %1;" : "=f"(r) : "f"(x)); return r; }
__device__ __forceinline__ float qsum(float v) { v += __shfl_xor_sync(~0u, v, 1); v += __shfl_xor_sync(~0u, v, 2); return v; }
__device__ __forceinline__ void sts32(uint32_t a, uint32_t v) { asm volatile("st.shared.u32 [%0], %1;" ::"r"(a), "r"(v) : "memory"); }
__device__ __forceinline__ void sts16(uint32_t a, uint32_t v) { asm volatile("st.shared.u16 [%0], %1;" ::"r"(a), "h"((uint16_t)v) : "memory"); }
__device__ __forceinline__ void sts128(uint32_t a, uint32_t x, uint32_t y, uint32_t z, uint32_t w) {
  asm volatile("st.shared.v4.u32 [%0], {%1,%2,%3,%4};" ::"r"(a), "r"(x), "r"(y), "r"(z), "r"(w) : "memory");
}
__device__ __forceinline__ uint32_t sw128(int row, int col) { return row * 128 + ((((col >> 3) ^ row) & 7) << 4) + (col & 7) * 2; }

__device__ __forceinline__ void wgmma_rs56(float (&d)[28], const uint32_t a0, const uint32_t a1, const uint32_t a2, const uint32_t a3, Desc db, int sd) {
  asm volatile("{.reg .pred p; .reg .b64 da, db; setp.ne.b32 p, %33, 0; mov.b64 db, {%32, %34};\n wgmma.mma_async.sync.aligned.m64n56k16.f32.bf16.bf16 {%0,%1,%2,%3,%4,%5,%6,%7,%8,%9,%10,%11,%12,%13,%14,%15,%16,%17,%18,%19,%20,%21,%22,%23,%24,%25,%26,%27}, {%28,%29,%30,%31}, db, p, 1, 1, 1;}"
   : "+f"(d[0]),"+f"(d[1]),"+f"(d[2]),"+f"(d[3]),"+f"(d[4]),"+f"(d[5]),"+f"(d[6]),"+f"(d[7]),"+f"(d[8]),"+f"(d[9]),"+f"(d[10]),"+f"(d[11]),"+f"(d[12]),"+f"(d[13]),"+f"(d[14]),"+f"(d[15]),"+f"(d[16]),"+f"(d[17]),"+f"(d[18]),"+f"(d[19]),"+f"(d[20]),"+f"(d[21]),"+f"(d[22]),"+f"(d[23]),"+f"(d[24]),"+f"(d[25]),"+f"(d[26]),"+f"(d[27])
   : "r"(a0),"r"(a1),"r"(a2),"r"(a3),"r"(db.lo),"r"(sd),"r"(db.hi));
}
__device__ __forceinline__ void wgmma_rs64(float (&d)[32], const uint32_t a0, const uint32_t a1, const uint32_t a2, const uint32_t a3, Desc db, int sd) {
  asm volatile("{.reg .pred p; .reg .b64 da, db; setp.ne.b32 p, %37, 0; mov.b64 db, {%36, %38};\n wgmma.mma_async.sync.aligned.m64n64k16.f32.bf16.bf16 {%0,%1,%2,%3,%4,%5,%6,%7,%8,%9,%10,%11,%12,%13,%14,%15,%16,%17,%18,%19,%20,%21,%22,%23,%24,%25,%26,%27,%28,%29,%30,%31}, {%32,%33,%34,%35}, db, p, 1, 1, 1;}"
   : "+f"(d[0]),"+f"(d[1]),"+f"(d[2]),"+f"(d[3]),"+f"(d[4]),"+f"(d[5]),"+f"(d[6]),"+f"(d[7]),"+f"(d[8]),"+f"(d[9]),"+f"(d[10]),"+f"(d[11]),"+f"(d[12]),"+f"(d[13]),"+f"(d[14]),"+f"(d[15]),"+f"(d[16]),"+f"(d[17]),"+f"(d[18]),"+f"(d[19]),"+f"(d[20]),"+f"(d[21]),"+f"(d[22]),"+f"(d[23]),"+f"(d[24]),"+f"(d[25]),"+f"(d[26]),"+f"(d[27]),"+f"(d[28]),"+f"(d[29]),"+f"(d[30]),"+f"(d[31])
   : "r"(a0),"r"(a1),"r"(a2),"r"(a3),"r"(db.lo),"r"(sd),"r"(db.hi));
}
__device__ __forceinline__ void wgmma_rs192(float (&d)[96], const uint32_t a0, const uint32_t a1, const uint32_t a2, const uint32_t a3, Desc db, int sd) {
  asm volatile("{.reg .pred p; .reg .b64 db; setp.ne.b32 p, %101, 0; mov.b64 db, {%100, %102};\n wgmma.mma_async.sync.aligned.m64n192k16.f32.bf16.bf16 {%0,%1,%2,%3,%4,%5,%6,%7,%8,%9,%10,%11,%12,%13,%14,%15,%16,%17,%18,%19,%20,%21,%22,%23,%24,%25,%26,%27,%28,%29,%30,%31,%32,%33,%34,%35,%36,%37,%38,%39,%40,%41,%42,%43,%44,%45,%46,%47,%48,%49,%50,%51,%52,%53,%54,%55,%56,%57,%58,%59,%60,%61,%62,%63,%64,%65,%66,%67,%68,%69,%70,%71,%72,%73,%74,%75,%76,%77,%78,%79,%80,%81,%82,%83,%84,%85,%86,%87,%88,%89,%90,%91,%92,%93,%94,%95}, {%96,%97,%98,%99}, db, p, 1, 1, 1;}"
   : "+f"(d[0]),"+f"(d[1]),"+f"(d[2]),"+f"(d[3]),"+f"(d[4]),"+f"(d[5]),"+f"(d[6]),"+f"(d[7]),"+f"(d[8]),"+f"(d[9]),"+f"(d[10]),"+f"(d[11]),"+f"(d[12]),"+f"(d[13]),"+f"(d[14]),"+f"(d[15]),"+f"(d[16]),"+f"(d[17]),"+f"(d[18]),"+f"(d[19]),"+f"(d[20]),"+f"(d[21]),"+f"(d[22]),"+f"(d[23]),"+f"(d[24]),"+f"(d[25]),"+f"(d[26]),"+f"(d[27]),"+f"(d[28]),"+f"(d[29]),"+f"(d[30]),"+f"(d[31]),"+f"(d[32]),"+f"(d[33]),"+f"(d[34]),"+f"(d[35]),"+f"(d[36]),"+f"(d[37]),"+f"(d[38]),"+f"(d[39]),"+f"(d[40]),"+f"(d[41]),"+f"(d[42]),"+f"(d[43]),"+f"(d[44]),"+f"(d[45]),"+f"(d[46]),"+f"(d[47]),"+f"(d[48]),"+f"(d[49]),"+f"(d[50]),"+f"(d[51]),"+f"(d[52]),"+f"(d[53]),"+f"(d[54]),"+f"(d[55]),"+f"(d[56]),"+f"(d[57]),"+f"(d[58]),"+f"(d[59]),"+f"(d[60]),"+f"(d[61]),"+f"(d[62]),"+f"(d[63]),"+f"(d[64]),"+f"(d[65]),"+f"(d[66]),"+f"(d[67]),"+f"(d[68]),"+f"(d[69]),"+f"(d[70]),"+f"(d[71]),"+f"(d[72]),"+f"(d[73]),"+f"(d[74]),"+f"(d[75]),"+f"(d[76]),"+f"(d[77]),"+f"(d[78]),"+f"(d[79]),"+f"(d[80]),"+f"(d[81]),"+f"(d[82]),"+f"(d[83]),"+f"(d[84]),"+f"(d[85]),"+f"(d[86]),"+f"(d[87]),"+f"(d[88]),"+f"(d[89]),"+f"(d[90]),"+f"(d[91]),"+f"(d[92]),"+f"(d[93]),"+f"(d[94]),"+f"(d[95])
   : "r"(a0),"r"(a1),"r"(a2),"r"(a3),"r"(db.lo),"r"(sd),"r"(db.hi));
}
__device__ __forceinline__ void wgmma_rs32(float (&d)[16], const uint32_t a0, const uint32_t a1, const uint32_t a2, const uint32_t a3, Desc db, int sd) {
  asm volatile("{.reg .pred p; .reg .b64 db; setp.ne.b32 p, %21, 0; mov.b64 db, {%20, %22};\n wgmma.mma_async.sync.aligned.m64n32k16.f32.bf16.bf16 {%0,%1,%2,%3,%4,%5,%6,%7,%8,%9,%10,%11,%12,%13,%14,%15}, {%16,%17,%18,%19}, db, p, 1, 1, 1;}"
   : "+f"(d[0]),"+f"(d[1]),"+f"(d[2]),"+f"(d[3]),"+f"(d[4]),"+f"(d[5]),"+f"(d[6]),"+f"(d[7]),"+f"(d[8]),"+f"(d[9]),"+f"(d[10]),"+f"(d[11]),"+f"(d[12]),"+f"(d[13]),"+f"(d[14]),"+f"(d[15])
   : "r"(a0),"r"(a1),"r"(a2),"r"(a3),"r"(db.lo),"r"(sd),"r"(db.hi));
}
__device__ __forceinline__ void wgmma_ss64(float (&d)[32], Desc da, Desc db, int sd) {
  asm volatile("{.reg .pred p; .reg .b64 da, db; setp.ne.b32 p, %34, 0; mov.b64 da, {%32, %35}; mov.b64 db, {%33, %35};\n wgmma.mma_async.sync.aligned.m64n64k16.f32.bf16.bf16 {%0,%1,%2,%3,%4,%5,%6,%7,%8,%9,%10,%11,%12,%13,%14,%15,%16,%17,%18,%19,%20,%21,%22,%23,%24,%25,%26,%27,%28,%29,%30,%31}, da, db, p, 1, 1, 1, 1;}"
   : "+f"(d[0]),"+f"(d[1]),"+f"(d[2]),"+f"(d[3]),"+f"(d[4]),"+f"(d[5]),"+f"(d[6]),"+f"(d[7]),"+f"(d[8]),"+f"(d[9]),"+f"(d[10]),"+f"(d[11]),"+f"(d[12]),"+f"(d[13]),"+f"(d[14]),"+f"(d[15]),"+f"(d[16]),"+f"(d[17]),"+f"(d[18]),"+f"(d[19]),"+f"(d[20]),"+f"(d[21]),"+f"(d[22]),"+f"(d[23]),"+f"(d[24]),"+f"(d[25]),"+f"(d[26]),"+f"(d[27]),"+f"(d[28]),"+f"(d[29]),"+f"(d[30]),"+f"(d[31])
   : "r"(da.lo),"r"(db.lo),"r"(sd),"r"(db.hi));
}

template <int S, int N, bool SPL = false, int T> __device__ __forceinline__ void ll_issue(uint4 (&v)[T], const uint4* p, int stride, const uint2* p2 = nullptr) {
#pragma unroll
  for (int i = S; i < S + N; i++) {
    if (SPL && i % 7 == 3) { const uint2 lo = ldll2(p2 + i * 64), hi = ldll2(p2 + i * 64 + 32); v[i] = make_uint4(lo.x, lo.y, hi.x, hi.y); }
    else v[i] = ldll(p + i * stride);
  }
}
template <int S, int N, bool SPL, int T> __device__ __forceinline__ void ll_check(uint4 (&v)[T], const uint4* p, int stride, uint32_t tag, const uint2* p2 = nullptr) {
#pragma unroll 1
  for (int it = 0; it < SPIN; it++) {
    uint32_t bad = 0;
#pragma unroll
    for (int i = S; i < S + N; i++) bad |= (v[i].x ^ tag) | ((SPL && i % 7 == 3) ? (v[i].z ^ tag) : 0u);
    if (!__any_sync(~0u, bad & 1)) break;
    ll_issue<S, N, SPL>(v, p, stride, p2);
  }
}
__device__ __forceinline__ void hint_post(uint32_t* p, uint32_t v, int lane) {
  if (lane == 0) asm volatile("st.relaxed.gpu.global.u32 [%0], %1;" ::"l"(p), "r"(v) : "memory");
}
__device__ __forceinline__ void hint_wait(const uint32_t* p, uint32_t s) {
#pragma unroll 1
  for (int it = 0; it < SPIN; it++) {
    uint32_t v; asm volatile("ld.relaxed.gpu.global.u32 %0, [%1];" : "=r"(v) : "l"(p) : "memory");
    if (__all_sync(~0u, v - s < 10u)) break;
  }
}
__device__ __forceinline__ void slice_store(uint4* pf, uint2* ph, const uint32_t (&w)[14], bool odd) {
#pragma unroll
  for (int u = 0; u < 3; u++)
    stll(pf + u * 32, odd ? w[4 * u + 2] : w[4 * u], odd ? w[4 * u + 3] : w[4 * u + 1], odd ? w[4 * u + 4] : w[4 * u + 2], odd ? w[4 * u + 5] : w[4 * u + 3]);
  stll2(ph, odd ? w[0] : w[12], odd ? w[1] : w[13]);
}
template <int R0, int R1, class F> __device__ __forceinline__ void hedgehog(const float (&d)[28], F sink) {
  const float L2E = 1.4426950408889634f;
#pragma unroll
  for (int r = R0; r < R1; r++)
#pragma unroll
    for (int h = 0; h < 2; h++) {
      float x[7];
#pragma unroll
      for (int p = 0; p < 6; p++) x[p] = d[h * 16 + (p >> 1) * 4 + (p & 1) + 2 * r] * L2E;
      x[6] = d[12 + h + 2 * r] * L2E;
      float mx = x[0], mn = x[0];
#pragma unroll
      for (int p = 1; p < 7; p++) { mx = fmaxf(mx, x[p]); mn = fminf(mn, x[p]); }
      mx = fmaxf(mx, __shfl_xor_sync(~0u, mx, 1)); mn = fminf(mn, __shfl_xor_sync(~0u, mn, 1));
      mx = fmaxf(mx, __shfl_xor_sync(~0u, mx, 2)); mn = fminf(mn, __shfl_xor_sync(~0u, mn, 2));
      float ep[7], en[7], sp = 0.f, sn = 0.f;
#pragma unroll
      for (int p = 0; p < 7; p++) { ep[p] = ex2(x[p] - mx); en[p] = ex2(mn - x[p]); sp += ep[p]; sn += en[p]; }
      sp = rcp(qsum(sp)); sn = rcp(qsum(sn));
#pragma unroll
      for (int p = 0; p < 7; p++) sink(r, h, p, pack(ep[p] * sp, en[p] * sn));
    }
}
__device__ __forceinline__ void phi_gemm(const float (&x)[28], float (&y)[28], uint32_t wphi) {
  uint32_t f[14];
#pragma unroll
  for (int j = 0; j < 14; j++) f[j] = pack(x[2 * j], x[2 * j + 1]);
  wg_fence();
#pragma unroll
  for (int ks = 0; ks < 3; ks++) wgmma_rs56(y, f[4 * ks], f[4 * ks + 1], f[4 * ks + 2], f[4 * ks + 3], mkdesc(wphi, ks * 2048, 1024, 1024, 1), ks);
  wgmma_rs56(y, f[12], f[13], 0u, 0u, mkdesc(wphi, 3 * 2048, 1024, 1024, 1), 1);
  wg_commit();
}
__device__ __forceinline__ void ln_publish(uint32_t (&xw)[4][4], float* sLN, int warp, int lane, uint4* fb, uint32_t tag) {
  const int g = lane >> 2; const bool full = warp < 4;
  float s0 = 0.f, s1 = 0.f;
#pragma unroll
  for (int u = 0; u < 4; u++) {
    s0 += (blo(xw[u][0]) + bhi(xw[u][0])) + (blo(xw[u][2]) + bhi(xw[u][2]));
    s1 += (blo(xw[u][1]) + bhi(xw[u][1])) + (blo(xw[u][3]) + bhi(xw[u][3]));
  }
  const float rc = full ? 1.f / 64 : 1.f / 48;
  s0 = qsum(s0); s1 = qsum(s1);
  const float a0 = s0 * rc, a1 = s1 * rc;
  float v0 = 0.f, v1 = 0.f;
#pragma unroll
  for (int u = 0; u < 4; u++)
    if (u < 3 || full) {
#pragma unroll
      for (int k = 0; k < 4; k += 2) {
        float a = blo(xw[u][k]) - a0, b = bhi(xw[u][k]) - a0, c2 = blo(xw[u][k + 1]) - a1, d2 = bhi(xw[u][k + 1]) - a1;
        v0 += a * a + b * b; v1 += c2 * c2 + d2 * d2;
      }
    }
  v0 = qsum(v0); v1 = qsum(v1);
  if ((lane & 3) == 0) *(float4*)(sLN + (g * 8 + warp) * 4) = make_float4(s0, v0, s1, v1);
  bar_cons();
  const float4 ea = *(const float4*)(sLN + (g * 8 + (lane & 3)) * 4), eb = *(const float4*)(sLN + (g * 8 + 4 + (lane & 3)) * 4);
  const float m0 = qsum(ea.x + eb.x) * (1.f / 448), m1 = qsum(ea.z + eb.z) * (1.f / 448);
  const float d0 = ea.x * (1.f / 64) - m0, d1 = eb.x * (1.f / 48) - m0, d2 = ea.z * (1.f / 64) - m1, d3 = eb.z * (1.f / 48) - m1;
  v0 = qsum(ea.y + eb.y + 64.f * d0 * d0 + 48.f * d1 * d1); v1 = qsum(ea.w + eb.w + 64.f * d2 * d2 + 48.f * d3 * d3);
  const float r0 = rsqrtf(v0 * (1.f / 448) + 1e-5f), r1 = rsqrtf(v1 * (1.f / 448) + 1e-5f), n0 = -m0 * r0, n1 = -m1 * r1;
#pragma unroll
  for (int u = 0; u < 4; u++)
    if (u < 3 || full)
      stll(fb + XN + u * 256, tg(pack(fmaf(blo(xw[u][0]), r0, n0), fmaf(bhi(xw[u][0]), r0, n0)), tag), pack(fmaf(blo(xw[u][1]), r1, n1), fmaf(bhi(xw[u][1]), r1, n1)),
           pack(fmaf(blo(xw[u][2]), r0, n0), fmaf(bhi(xw[u][2]), r0, n0)), pack(fmaf(blo(xw[u][3]), r1, n1), fmaf(bhi(xw[u][3]), r1, n1)));
}

__global__ void __cluster_dims__(2, 1, 1) __launch_bounds__(384, 1)
fused_kernel(const __grid_constant__ CUtensorMap mQKV, const __grid_constant__ CUtensorMap mWO, const __grid_constant__ CUtensorMap mW1,
             const __grid_constant__ CUtensorMap mW1b, const __grid_constant__ CUtensorMap mW2, const __grid_constant__ CUtensorMap mW2b, const __nv_bfloat16* __restrict__ x, const __nv_bfloat16* __restrict__ wphi,
             const __nv_bfloat16* __restrict__ wo, const __nv_bfloat16* __restrict__ w1, const __nv_bfloat16* __restrict__ b1,
             const __nv_bfloat16* __restrict__ w2, const __nv_bfloat16* __restrict__ b2, __nv_bfloat16* __restrict__ out) {
  extern __shared__ __align__(1024) uint8_t sm[];
  const uint32_t sb = s2u(sm);
  const int tid = threadIdx.x, warp = __shfl_sync(~0u, tid >> 5, 0), lane = tid & 31, rk = blockIdx.x & 1, t = (blockIdx.x >> 4) * 2 + rk, c = (blockIdx.x >> 1) & 7;
  const uint32_t bfull = sb + OFF_BAR, bempty = bfull + 8 * NST;

#define XOFF(l) ((t * 128 + c * 16 + ((l) >> 2)) * 448 + warp * 16 + 2 * ((l) & 3))
  if (warp < 8) MARK(0);
  uint32_t xw[4][4];
  if (warp < 8) {
    const uint32_t* xp = (const uint32_t*)(x + XOFF(lane));
#pragma unroll
    for (int u = 0; u < 4; u++) {
      if (u < 3 || warp < 4) { xw[u][0] = __ldg(xp + u * 64); xw[u][1] = __ldg(xp + u * 64 + 1792); xw[u][2] = __ldg(xp + u * 64 + 4); xw[u][3] = __ldg(xp + u * 64 + 1796); }
      else { xw[u][0] = xw[u][1] = xw[u][2] = xw[u][3] = 0; }
    }
  }
  if (tid == 256) {
    for (int s = 0; s < NST; s++) { mbar_init(bfull + 8 * s, 1); mbar_init(bempty + 8 * s, 16); }
    asm volatile("fence.mbarrier_init.release.cluster;" ::: "memory");
    fence_async();
  }
  asm volatile("barrier.cluster.arrive.release.aligned; barrier.cluster.wait.acquire.aligned;" ::: "memory");
  if (warp >= 8) {
    asm volatile("setmaxnreg.dec.sync.aligned.u32 24;");
    auto issue = [&](int i, int s) {
      const uint32_t dst = sb + s * STAGE, bar = bfull + 8 * s;
      mbar_expect(bar, STAGE);
      if (i < 4) tma2d(dst + rk * 14336, &mQKV, 448 + 448 * rk + 56 * c, 112 * i, bar);
      else if (i < 8) tma2d(dst + rk * 14336, i < 6 ? &mQKV : &mWO, (i < 6 ? 56 : 64) * c, 224 * (i & 1) + 112 * rk, bar);
      else if (i < 15) { tma3d(dst + rk * 12288, &mW1, 0, 64 * (i - 8) + 32 * rk, 3 * c, bar); tma2d(dst + 24576 + rk * 2048, &mW1b, 1536 + 32 * c, 64 * (i - 8) + 32 * rk, bar); }
      else { tma2d(dst + rk * 12288, &mW2, 64 * (i - 15), 192 * c + 96 * rk, bar); tma2d(dst + 24576 + rk * 2048, &mW2b, 64 * (i - 15), 1536 + 32 * c + 16 * rk, bar); }
    };
    if (warp == 8) {
      int s = 0; uint32_t ph = 1;
      for (int n = 0; n < 44; n++) {
        if (n == PACE) asm volatile("bar.sync 2, 288;" ::: "memory");
        mbar_wait(bempty + 8 * s, ph);
        if (lane == 0) issue(n >= 22 ? n - 22 : n, s);
        __syncwarp();
        if (++s == NST) { s = 0; ph ^= 1; }
      }
    } else if (warp == 9) {
      mbar_wait(bfull + 8 * 3, 0);
      if (lane == 0) {
        l2pf((const uint8_t*)wo + blockIdx.x * 3136, 3136);
        l2pf((const uint8_t*)w1 + blockIdx.x * 12544, 12544);
        l2pf((const uint8_t*)w2 + blockIdx.x * 12544, 12544);
      }
      if (blockIdx.x < 112) {
        const uint2* wp = (const uint2*)(w1 + (size_t)(lane >> 2) * 1792 + blockIdx.x * 16 + (lane & 3) * 4);
        float s0 = 0.f, s1 = 0.f, s2 = 0.f, s3 = 0.f;
#pragma unroll 8
        for (int i = 0; i < 56; i++) { const uint2 v = __ldg(wp + i * 8 * 448); s0 += blo(v.x); s1 += bhi(v.x); s2 += blo(v.y); s3 += bhi(v.y); }
#pragma unroll 1
        for (int o = 4; o < 32; o <<= 1) { s0 += __shfl_xor_sync(~0u, s0, o); s1 += __shfl_xor_sync(~0u, s1, o); s2 += __shfl_xor_sync(~0u, s2, o); s3 += __shfl_xor_sync(~0u, s3, o); }
        if (lane < 4) stll(g_CS + blockIdx.x * 4 + lane, tg(__float_as_uint(s0), 1), __float_as_uint(s1), __float_as_uint(s2), __float_as_uint(s3));
      }
      asm volatile("bar.sync 6, 96;" ::: "memory");
#pragma unroll 1
      for (int i = 0; i < 2; i++) {
        const int e = lane < 28 ? lane + 28 * i : 0;
        uint4 cv[1];
        const int e4 = e < 48 ? 48 * c + e : 336 + 8 * c + e;
        ll_issue<0, 1>(cv, g_CS + e4, 0); ll_check<0, 1, false>(cv, g_CS + e4, 0, 1u);
        const uint2 bb = __ldg((const uint2*)b1 + e4);
        const uint32_t h0 = pack(__uint_as_float(cv[0].x), __uint_as_float(cv[0].y)), h1 = pack(__uint_as_float(cv[0].z), __uint_as_float(cv[0].w));
        const uint32_t l0 = pack(__uint_as_float(cv[0].x) - blo(h0), __uint_as_float(cv[0].y) - bhi(h0)), l1 = pack(__uint_as_float(cv[0].z) - blo(h1), __uint_as_float(cv[0].w) - bhi(h1));
#pragma unroll 1
        for (int r = 0; r < 8; r++) {
          const uint32_t ad = sb + OFF_CB + (e >> 3) * 512 + r * 64 + ((((e >> 1) ^ (r >> 1)) & 3) << 4) + (e & 1) * 8;
          sts32(ad, r < 2 ? h0 : r == 2 ? l0 : r < 5 ? bb.x : 0u); sts32(ad + 4, r < 2 ? h1 : r == 2 ? l1 : r < 5 ? bb.y : 0u);
        }
      }
      fence_async();
      asm volatile("bar.arrive 4, 288;" ::: "memory");
    } else if (warp >= 10) {
      const int h = warp - 10;
      uint32_t wv[13];
#pragma unroll
      for (int i = 0; i < 13; i++) { const int e = lane + 32 * i; wv[i] = e < 392 ? __ldg((const uint32_t*)wphi + (2 * c + h) * 392 + e) : 0u; }
#pragma unroll 1
      for (int i = 0; i < 8; i++) sts128(sb + OFF_WPHI + (h * 256 + i * 32 + lane) * 16, 0, 0, 0, 0);
      asm volatile("bar.arrive 6, 96;" ::: "memory");
#pragma unroll 1
      for (int i = 0; i < 4; i++) sts128(sb + OFF_PHIK + sw128(h * 128 + i * 32 + lane, 56), 0, 0, 0, 0);
      asm volatile("bar.sync 5, 64;" ::: "memory");
#pragma unroll
      for (int i = 0; i < 13; i++) {
        const int e = lane + 32 * i, d = e / 14, f2 = 2 * (e - 14 * d), k = 28 * h + d;
        if (e < 392) {
          if (f2 < 24) sts32(sb + OFF_WPHI + sw128(k, 32 * h + f2), wv[i]);
          else { sts16(sb + OFF_WPHI + sw128(k, 2 * f2 - 24 + h), wv[i]); sts16(sb + OFF_WPHI + sw128(k, 2 * f2 - 22 + h), wv[i] >> 16); }
        }
      }
      fence_async();
      asm volatile("bar.arrive 3, 320;" ::: "memory");
    }
  } else {
  asm volatile("setmaxnreg.inc.sync.aligned.u32 240;");

  const int wg = warp >> 2, g = lane >> 2, q = lane & 3;
  const int row0 = warp * 16 + g;
#define PTRS const int ln_ = laneid(); \
  uint4* const fm = g_F + ((t * 8 + warp) * 28) * 32 + ln_;            \
  uint4* const fr = g_F + ((t * 8 + c) * 28 + warp) * 32 + ln_;        \
  uint4* const sf = fm + (7 * (c >> 1) + 4 * (c & 1)) * 32;             \
  uint2* const f2 = (uint2*)(fm - ln_) + ln_;                           \
  uint2* const sh = f2 + (7 * (c >> 1) + 3) * 64 + 32 * (c & 1);        \
  uint32_t* const hme = g_H + (t * 8 + warp) * 8 + c; \
  const uint32_t* const hrow = g_H + (t * 8 + warp) * 8 + (ln_ & 7); \
  (void)fm; (void)fr; (void)sf; (void)f2; (void)sh; (void)hme; (void)hrow;
  float* sLN = (float*)(sm + OFF_V);
  const uint32_t sPK = sb + OFF_PHIK, sV = sb + OFF_V, d16 = (sb & 0x3FFFF) >> 4;
    int cs = 0, rs = 0; uint32_t cph = 0;
  auto acquire = [&]() -> uint32_t { mbar_wait(bfull + 8 * cs, cph); const uint32_t a = d16 + cs * (STAGE >> 4); if (++cs == NST) { cs = 0; cph ^= 1; } return a; };
  int nrel = 44 - NST;
  auto release = [&]() { if (lane < 2 && nrel > 0) mbar_arrive_cl(bempty + 8 * rs, lane); nrel--; if (++rs == NST) rs = 0; };

#pragma unroll 1
  for (int L = 0; L < 2; L++) {
    const uint32_t tag = 1 - L;
    uint32_t phq[2][2][7];
    const uint32_t hs = 10 * L;
    {
      PTRS
      ln_publish(xw, sLN, warp, lane, fr, tag);
      hint_post(hme, hs + 1, lane);
#pragma unroll
      for (int u = 0; u < 4; u++) if (u < 3 || wg == 0) stll(fr + XR + u * 256, tg(xw[u][0], tag), xw[u][1], xw[u][2], xw[u][3]);
    }
    MARK(1 + L * 19);
    {
      PTRS
      uint4 a[28];
      const uint4* pa = fm + XN;
      hint_wait(g_H + (t * 8 + (ln_ & 7)) * 8 + warp, hs + 1); ll_issue<0, 28>(a, pa, 32);
      if (L == 0) asm volatile("bar.arrive 2, 288;" ::: "memory");
      MARK(2 + L * 19);
      float ak[28], av[28], aq[28], pp[28];
#define KVSTAGE(i) { ll_check<7 * i, 7, false>(a, pa, 32, tag); const uint32_t st = acquire(); wg_fence(); \
      _Pragma("unroll") for (int ks = 0; ks < 7; ks++) { const uint4 f = a[7 * i + ks]; \
        wgmma_rs56(ak, f.x, f.y, f.z, f.w, mkdesc(st, ks * 2048, 1024, 1024, 1), i | ks); \
        wgmma_rs56(av, f.x, f.y, f.z, f.w, mkdesc(st, 14336 + ks * 2048, 1024, 1024, 1), i | ks); } \
      wg_commit(); if (i > 0) { wg_wait<1>(); release(); } }
      KVSTAGE(0) KVSTAGE(1) KVSTAGE(2) KVSTAGE(3)
      wg_wait<0>(); release(); regfence(ak); regfence(av);
      MARK(3 + L * 19);
      if (L == 0) asm volatile("bar.sync 3, 320;" ::: "memory");
      phi_gemm(ak, pp, d16 + (OFF_WPHI >> 4));
#pragma unroll
      for (int j = 0; j < 7; j++) {
        const int n = 8 * j + 2 * q, n2 = n < 28 ? n : n + 4;
        sts32(sV + sw128(row0, n2), pack(av[4 * j], av[4 * j + 1])); sts32(sV + sw128(row0 + 8, n2), pack(av[4 * j + 2], av[4 * j + 3]));
      }
      { const int n2 = 28 + 2 * (q & 1) + 32 * (q >> 1); const uint32_t v = (q & 1) ? 0u : 0x3F80u; sts32(sV + sw128(row0, n2), v); sts32(sV + sw128(row0 + 8, n2), v); }
      wg_wait<0>(); regfence(pp);
      hedgehog<0, 2>(pp, [&](int r, int h, int p, uint32_t v) { sts32(sPK + h * 16384 + sw128(row0 + 8 * r, 8 * p + 2 * q), v); });
      fence_async();
      bar_cons();
      MARK(4 + L * 19);
      float kv[32];
      wg_fence();
#pragma unroll
      for (int ks = 0; ks < 8; ks++) wgmma_ss64(kv, mkdesc(d16 + wg * 1024, OFF_PHIK + ks * 2048, 1024, 1024, 1), mkdesc(d16, OFF_V + ks * 2048, 1024, 1024, 1), ks);
      wg_commit(); wg_wait<0>(); regfence(kv);
      const int ln2 = laneid();
#pragma unroll
      for (int u = 0; u < 4; u++) {
        float e[4];
#pragma unroll
        for (int i = 0; i < 4; i++) e[i] = wg ? kv[16 + 4 * u + i] : kv[4 * u + i];
        stll(g_KVP + (c * 16 + t) * 1024 + wg * 512 + u * 128 + (warp & 3) * 32 + ln2, tg(__float_as_uint(e[0]), tag), __float_as_uint(e[1]), __float_as_uint(e[2]), __float_as_uint(e[3]));
      }
      MARK(5 + L * 19);
      uint4 k4[4];
      const uint4* pk = g_KVP + (c * 16 + 4 * (ln2 & 3)) * 1024 + 64 * t + warp * 8 + (ln2 >> 2);
#pragma unroll
      for (int i = 0; i < 2; i++) {
        const uint32_t st = acquire(); wg_fence();
#pragma unroll
        for (int ks = 0; ks < 14; ks++) { const uint4 f = a[14 * i + ks]; wgmma_rs56(aq, f.x, f.y, f.z, f.w, mkdesc(st, ks * 2048, 1024, 1024, 1), i | ks); }
        wg_commit();
        if (i == 0) ll_issue<0, 4>(k4, pk, 1024);
      }
      ll_check<0, 4, false>(k4, pk, 1024, tag);
      float s0 = 0, s1 = 0, s2 = 0, s3 = 0;
#pragma unroll
      for (int i = 0; i < 4; i++) { s0 += __uint_as_float(k4[i].x); s1 += __uint_as_float(k4[i].y); s2 += __uint_as_float(k4[i].z); s3 += __uint_as_float(k4[i].w); }
      s0 = qsum(s0); s1 = qsum(s1); s2 = qsum(s2); s3 = qsum(s3);
      if (q == 0) stll2(g_KVR + c * 1024 + 64 * t + warp * 8 + (ln2 >> 2), tg(pack(s0, s1), tag), pack(s2, s3));
      MARK(6 + L * 19);
      wg_wait<0>(); release(); release(); regfence(aq);
      phi_gemm(aq, pp, d16 + (OFF_WPHI >> 4));
      bar_cons();
#pragma unroll
      for (int i = 0; i < 4; i++) sts128(sV + warp * 2048 + (lane + i * 32) * 16, 0, 0, 0, 0);
      wg_wait<0>(); regfence(pp);
      hedgehog<0, 1>(pp, [&](int r, int h, int p, uint32_t v) { phq[r][h][p] = v; });
      uint2 r[4];
      const uint2* pr = g_KVR + c * 1024 + wg * 512 + (warp & 3) * 32 + ln2;
#pragma unroll
      for (int u = 0; u < 4; u++) r[u] = ldll2(pr + u * 128);
      hedgehog<1, 2>(pp, [&](int r, int h, int p, uint32_t v) { phq[r][h][p] = v; });
      MARK(7 + L * 19);
#pragma unroll 1
      for (int it = 0; it < SPIN; it++) {
        if (!__any_sync(~0u, ((r[0].x ^ tag) | (r[1].x ^ tag) | (r[2].x ^ tag) | (r[3].x ^ tag)) & 1)) break;
#pragma unroll
        for (int u = 0; u < 4; u++) r[u] = ldll2(pr + u * 128);
      }
#pragma unroll
      for (int u = 0; u < 4; u++) {
        const int d = 8 * u + 2 * q;
        if (d < 28) { sts32(sV + sw128(row0, 28 * wg + d), r[u].x); sts32(sV + sw128(row0 + 8, 28 * wg + d), r[u].y); }
        else if (d == 28) {
#pragma unroll
          for (int j = 0; j < 4; j++) { sts16(sV + sw128(row0, 56 + 2 * j + wg), r[u].x); sts16(sV + sw128(row0 + 8, 56 + 2 * j + wg), r[u].y); }
        }
      }
      fence_async();
      bar_cons();
      MARK(8 + L * 19);
      float o[32];
      wg_fence();
#pragma unroll
      for (int ks = 0; ks < 8; ks++) {
        const int h = ks >> 2, p = 2 * (ks & 3);
        wgmma_rs64(o, phq[0][h][p], phq[1][h][p], p < 6 ? phq[0][h][p < 6 ? p + 1 : 0] : 0u, p < 6 ? phq[1][h][p < 6 ? p + 1 : 0] : 0u, mkdesc(d16, OFF_V + ks * 2048, 1024, 1024, 1), ks);
      }
      wg_commit(); wg_wait<0>(); regfence(o);
      const float iA0 = rcp(o[28] + 1e-6f), iB0 = rcp(o[29] + 1e-6f), iA1 = rcp(o[30] + 1e-6f), iB1 = rcp(o[31] + 1e-6f);
      uint32_t w[14];
      { PTRS
#pragma unroll
      for (int j = 0; j < 7; j++) {
        const bool hb = 8 * j + 2 * q >= 28; const float i0 = hb ? iB0 : iA0, i1 = hb ? iB1 : iA1;
        w[2 * j] = pack(o[4 * j] * i0, o[4 * j + 1] * i0); w[2 * j + 1] = pack(o[4 * j + 2] * i1, o[4 * j + 3] * i1);
        if (j == 0 || ((j ^ c) & 1) == 0) w[2 * j] = tg(w[2 * j], tag);
      }
      slice_store(sf + OO, sh + 2 * OO, w, c & 1);
      hint_post(hme, hs + 2, lane); }
    }
    MARK(9 + L * 19);
    if (c < 7) {
      PTRS
      uint4 xr[4];
      ll_issue<0, 4>(xr, fm + XR + 128 * c, 32);
      uint4 a[28];
      const uint4* pa = fm + OO;
      hint_wait(hrow, hs + 2);
      MARK(10 + L * 19);
      ll_issue<0, 28, true>(a, pa, 32, f2 + 2 * OO);
      float y[32];
      uint32_t st;
#define WOSTEP(i) { ll_check<7 * i, 7, true>(a, pa, 32, tag, f2 + 2 * OO); if (!(i & 1)) st = acquire(); wg_fence(); \
      _Pragma("unroll") for (int ks = 0; ks < 7; ks++) { const uint4 f = a[7 * i + ks]; \
        wgmma_rs64(y, f.x, f.y, f.z, f.w, mkdesc(st, ((i & 1) * 7 + ks) * 2048, 1024, 1024, 1), i | ks); } wg_commit(); }
      WOSTEP(0) WOSTEP(1) WOSTEP(2) WOSTEP(3)
      ll_check<0, 4, false>(xr, fm + XR + 128 * c, 32, tag);
      wg_wait<0>(); regfence(y);
      MARK(11 + L * 19);
      float s0 = 0.f, s1 = 0.f;
#pragma unroll
      for (int u = 0; u < 4; u++) {
        xr[u].x = tg(pack(blo(xr[u].x) + y[8 * u], bhi(xr[u].x) + y[8 * u + 1]), tag); xr[u].y = pack(blo(xr[u].y) + y[8 * u + 2], bhi(xr[u].y) + y[8 * u + 3]);
        xr[u].z = pack(blo(xr[u].z) + y[8 * u + 4], bhi(xr[u].z) + y[8 * u + 5]); xr[u].w = pack(blo(xr[u].w) + y[8 * u + 6], bhi(xr[u].w) + y[8 * u + 7]);
        stll(fm + X1 + 128 * c + u * 32, xr[u].x, xr[u].y, xr[u].z, xr[u].w);
      }
      hint_post(hme, hs + 3, lane);
#pragma unroll
      for (int u = 0; u < 4; u++) {
        y[8 * u] = blo(xr[u].x); y[8 * u + 1] = bhi(xr[u].x); y[8 * u + 2] = blo(xr[u].y); y[8 * u + 3] = bhi(xr[u].y);
        y[8 * u + 4] = blo(xr[u].z); y[8 * u + 5] = bhi(xr[u].z); y[8 * u + 6] = blo(xr[u].w); y[8 * u + 7] = bhi(xr[u].w);
        s0 += (y[8 * u] + y[8 * u + 1]) + (y[8 * u + 4] + y[8 * u + 5]); s1 += (y[8 * u + 2] + y[8 * u + 3]) + (y[8 * u + 6] + y[8 * u + 7]);
      }
      s0 = qsum(s0) * (1.f / 64); s1 = qsum(s1) * (1.f / 64);
      float v0 = 0.f, v1 = 0.f;
#pragma unroll
      for (int j = 0; j < 8; j++) {
        const float d0 = y[4 * j] - s0, d1 = y[4 * j + 1] - s0, d2 = y[4 * j + 2] - s1, d3 = y[4 * j + 3] - s1;
        v0 += d0 * d0 + d1 * d1; v1 += d2 * d2 + d3 * d3;
      }
      v0 = qsum(v0); v1 = qsum(v1);
      if (q == 0) stll(g_ST + ((t * 8 + warp) * 8 + c) * 8 + (ln_ >> 2), tg(__float_as_uint(s0), tag), __float_as_uint(v0), __float_as_uint(s1), __float_as_uint(v1));
    } else {
      PTRS
      hint_post(hme, hs + 3, lane);
      acquire(); acquire();
      MARK(10 + L * 19); MARK(11 + L * 19);
    }
    uint32_t hf[56];
    float rr0, rr1;
    {
      PTRS
      uint4 a[28];
      const uint4* pa = fm + X1;
      hint_wait(hrow, hs + 3);
      MARK(12 + L * 19);
      ll_issue<0, 4>(a, pa, 32); ll_check<0, 4, false>(a, pa, 32, tag); ll_issue<4, 12>(a, pa, 32);
      release(); release();
      float y[96], z[16];
#define F1STAGE(i) { if (i > 0) ll_check<4 * i, 4, false>(a, pa, 32, tag); const uint32_t st = acquire(); wg_fence(); \
      _Pragma("unroll") for (int ks = 0; ks < 4; ks++) { const uint4 f = a[4 * i + ks]; \
        wgmma_rs192(y, f.x, f.y, f.z, f.w, mkdesc(st, (ks >> 1) * 12288 + (ks & 1) * 2048, 4096, 1024, 1), i | ks); \
        wgmma_rs32(z, f.x, f.y, f.z, f.w, mkdesc(st, 24576 + ks * 1024, 512, 512, 2), i | ks); } \
      wg_commit(); if (i > 0) { wg_wait<1>(); release(); if (i < 4) ll_issue<(i < 4 ? 4 * i + 12 : 0), 4>(a, pa, 32); } }
      F1STAGE(0) MARK(13 + L * 19); F1STAGE(1) F1STAGE(2) F1STAGE(3)
      uint4 sv[2];
      const uint4* ps = g_ST + ((t * 8 + warp) * 8 + 2 * (laneid() & 3)) * 8 + (laneid() >> 2);
      ll_issue<0, 2>(sv, ps, q < 3 ? 8 : 0);
      F1STAGE(4)
      ll_check<0, 2, false>(sv, ps, q < 3 ? 8 : 0, tag);
      const float wb = q < 3 ? 1.f : 0.f;
      const float ma = __uint_as_float(sv[0].x), mb = __uint_as_float(sv[1].x), mc = __uint_as_float(sv[0].z), md = __uint_as_float(sv[1].z);
      const float m0 = qsum(ma + wb * mb) * (1.f / 7), m1 = qsum(mc + wb * md) * (1.f / 7);
      const float v0 = qsum(__uint_as_float(sv[0].y) + 64.f * (ma - m0) * (ma - m0) + wb * (__uint_as_float(sv[1].y) + 64.f * (mb - m0) * (mb - m0)));
      const float v1 = qsum(__uint_as_float(sv[0].w) + 64.f * (mc - m1) * (mc - m1) + wb * (__uint_as_float(sv[1].w) + 64.f * (md - m1) * (md - m1)));
      const float e0 = v0 * (1.f / 448) + 1e-5f, e1 = v1 * (1.f / 448) + 1e-5f;
      rr0 = 1.f / e0; rr1 = 1.f / e1;
      auto fold = [&](float m, float sd) -> uint32_t {
        const float mh = blo(pack(-m, 0.f)), sh_ = blo(pack(sd, 0.f));
        return q == 0 ? pack(mh, -m - mh) : q == 1 ? pack(mh, sh_) : q == 2 ? pack(sd - sh_, 0.f) : 0u;
      };
      const uint32_t fa = fold(m0, sqrtf(e0)), fb = fold(m1, sqrtf(e1));
      if (L == 0) asm volatile("bar.sync 4, 288;" ::: "memory");
      wg_fence();
      wgmma_rs192(y, fa, fb, 0u, 0u, mkdesc(d16, OFF_CB + 0, 512, 0, 2), 1);
      wgmma_rs32(z, fa, fb, 0u, 0u, mkdesc(d16, OFF_CB + 3072, 512, 0, 2), 1);
      F1STAGE(5) F1STAGE(6)
      wg_wait<0>(); release(); regfence(y); regfence(z);
      MARK(14 + L * 19);
#pragma unroll
      for (int j = 0; j < 56; j++) {
        uint32_t r; asm("cvt.rn.relu.bf16x2.f32 %0, %1, %2;" : "=r"(r) : "f"(j < 48 ? y[j < 48 ? 2 * j + 1 : 0] : z[j < 48 ? 0 : 2 * j - 95]), "f"(j < 48 ? y[j < 48 ? 2 * j : 0] : z[j < 48 ? 0 : 2 * j - 96]));
        asm("mul.bf16x2 %0, %1, %1;" : "=r"(hf[j]) : "r"(r));
      }
    }
    MARK(15 + L * 19);
    {
      PTRS
      float ya[32], yb[32];
      uint4* pp = g_P + ((t * 8 + warp) * 8 + c) * 28 * 32 + ln_;
#define F2STORE(j, Y) { regfence(Y); _Pragma("unroll") for (int u = 0; u < 4; u++) \
      stll(pp + (4 * (j) + u) * 32, tg(pack(Y[8 * u] * rr0, Y[8 * u + 1] * rr0), tag), pack(Y[8 * u + 2] * rr1, Y[8 * u + 3] * rr1), \
           pack(Y[8 * u + 4] * rr0, Y[8 * u + 5] * rr0), pack(Y[8 * u + 6] * rr1, Y[8 * u + 7] * rr1)); if ((j) >= 5) hint_post(hme, hs + (4 + (j)), lane); }
#define F2PASS(j, Y, Z) { const uint32_t st = acquire(); wg_fence(); \
      _Pragma("unroll") for (int ks = 0; ks < 14; ks++) wgmma_rs64(Y, hf[4 * ks], hf[4 * ks + 1], hf[4 * ks + 2], hf[4 * ks + 3], mkdesc(st, ks * 2048, 1024, 1024, 1), ks); \
      wg_commit(); if (j > 0) { wg_wait<1>(); release(); F2STORE(j - 1, Z) } }
      const uint4* pr = g_P + ((t * 8 + c) * 8 * 28 + warp) * 32 + ln_;
      uint4 p[8], p2[8]; uint2 xa, xb, xc, xd; uint32_t ba, bb, bc, bd;
#define RISSUE(m, P, XA, XB, BA, BB) { ll_issue<0, 8>(P, pr + (m) * 256, 896); \
      { const uint4 v_ = ldll(fr + X1 + (m) * 256); XA = make_uint2(v_.x, v_.y); XB = make_uint2(v_.z, v_.w); } \
      const uint32_t* bp = (const uint32_t*)(b2 + 128 * (m) + 16 * warp) + (ln_ & 3); BA = __ldg(bp); BB = __ldg(bp + 4); }
#define REDU(m, P, XA, XB, BA, BB) { ll_check<0, 8, false>(P, pr + (m) * 256, 896, tag); \
      float e[8] = {blo(XA.x) + blo(BA), bhi(XA.x) + bhi(BA), blo(XA.y) + blo(BA), bhi(XA.y) + bhi(BA), blo(XB.x) + blo(BB), bhi(XB.x) + bhi(BB), blo(XB.y) + blo(BB), bhi(XB.y) + bhi(BB)}; \
      _Pragma("unroll") for (int i = 0; i < 8; i++) { e[0] += blo(P[i].x); e[1] += bhi(P[i].x); e[2] += blo(P[i].y); e[3] += bhi(P[i].y); \
        e[4] += blo(P[i].z); e[5] += bhi(P[i].z); e[6] += blo(P[i].w); e[7] += bhi(P[i].w); } \
      xw[m][0] = pack(e[0], e[1]); xw[m][1] = pack(e[2], e[3]); xw[m][2] = pack(e[4], e[5]); xw[m][3] = pack(e[6], e[7]); }
      F2PASS(0, ya, yb) F2PASS(1, yb, ya) F2PASS(2, ya, yb) F2PASS(3, yb, ya) F2PASS(4, ya, yb)
      RISSUE(0, p, xa, xb, ba, bb)
      F2PASS(5, yb, ya)
      REDU(0, p, xa, xb, ba, bb)
      F2PASS(6, ya, yb)
      RISSUE(1, p, xa, xb, ba, bb)
      wg_wait<0>(); release(); F2STORE(6, ya)
      MARK(16 + L * 19);
      const uint32_t* hred = g_H + (t * 8 + c) * 8 + (ln_ & 7);
      if (wg) hint_wait(hred, hs + 9);
      RISSUE(2, p2, xc, xd, bc, bd)
      REDU(1, p, xa, xb, ba, bb)
      if (wg == 0) { hint_wait(hred, hs + 10); RISSUE(3, p, xa, xb, ba, bb) }
      MARK(17 + L * 19);
      REDU(2, p2, xc, xd, bc, bd)
      if (wg == 0) REDU(3, p, xa, xb, ba, bb) else { xw[3][0] = xw[3][1] = xw[3][2] = xw[3][3] = 0; }
    }
    MARK(18 + L * 19);
  }
  {
    uint32_t* op = (uint32_t*)(out + XOFF(laneid()));
#pragma unroll
    for (int u = 0; u < 4; u++) if (u < 3 || wg == 0) { op[u * 64] = xw[u][0]; op[u * 64 + 1792] = xw[u][1]; op[u * 64 + 4] = xw[u][2]; op[u * 64 + 1796] = xw[u][3]; }
    if (warp == 7 && blockIdx.x < 112 && lane < 4) stll(g_CS + blockIdx.x * 4 + lane, 0, 0, 0, 0);
  }
  MARK(38);
  }
}

typedef CUresult (*EncFn)(CUtensorMap*, CUtensorMapDataType, cuuint32_t, void*, const cuuint64_t*, const cuuint64_t*, const cuuint32_t*, const cuuint32_t*,
                          CUtensorMapInterleave, CUtensorMapSwizzle, CUtensorMapL2promotion, CUtensorMapFloatOOBfill);

extern "C" void kernel_launch(void* const* d_in, const int* in_sizes, int n_in, void* d_out, int out_size) {
  static EncFn enc = nullptr;
  if (!enc) {
    void* fn = nullptr; cudaDriverEntryPointQueryResult qr;
    cudaGetDriverEntryPoint("cuTensorMapEncodeTiled", &fn, cudaEnableDefault, &qr);
    enc = (EncFn)fn;
    cudaFuncSetAttribute(fused_kernel, cudaFuncAttributeMaxDynamicSharedMemorySize, SMEM_BYTES);
  }
  CUtensorMap mQKV, mWO, mW1, mW1b, mW2, mW2b;
  const cuuint32_t es[3] = {1, 1, 1};
  auto enc2 = [&](CUtensorMap* m, void* p, cuuint64_t cols, cuuint64_t rows, cuuint32_t bc, cuuint32_t br) {
    const cuuint64_t dims[2] = {cols, rows}, str[1] = {cols * 2}; const cuuint32_t box[2] = {bc, br};
    enc(m, CU_TENSOR_MAP_DATA_TYPE_BFLOAT16, 2, p, dims, str, box, es, CU_TENSOR_MAP_INTERLEAVE_NONE,
        bc == 64 ? CU_TENSOR_MAP_SWIZZLE_128B : CU_TENSOR_MAP_SWIZZLE_64B, CU_TENSOR_MAP_L2_PROMOTION_L2_128B, CU_TENSOR_MAP_FLOAT_OOB_FILL_NONE);
  };
  enc2(&mQKV, d_in[1], 1344, 448, 64, 112); enc2(&mWO, d_in[3], 448, 448, 64, 112); enc2(&mW1b, d_in[5], 1792, 448, 32, 32);
  enc2(&mW2, d_in[7], 448, 1792, 64, 96); enc2(&mW2b, d_in[7], 448, 1792, 64, 16);
  {
    const cuuint64_t dims[3] = {64, 448, 28}, str[2] = {3584, 128}; const cuuint32_t box[3] = {64, 32, 3};
    enc(&mW1, CU_TENSOR_MAP_DATA_TYPE_BFLOAT16, 3, d_in[5], dims, str, box, es, CU_TENSOR_MAP_INTERLEAVE_NONE, CU_TENSOR_MAP_SWIZZLE_128B,
        CU_TENSOR_MAP_L2_PROMOTION_L2_128B, CU_TENSOR_MAP_FLOAT_OOB_FILL_NONE);
  }
  typedef const __nv_bfloat16* BP;
  fused_kernel<<<128, 384, SMEM_BYTES>>>(mQKV, mWO, mW1, mW1b, mW2, mW2b, (BP)d_in[0], (BP)d_in[2], (BP)d_in[3], (BP)d_in[5], (BP)d_in[6], (BP)d_in[7], (BP)d_in[8],
                                         (__nv_bfloat16*)d_out);
}
```

```cpp
#include <cuda_runtime.h>
#include <cuda_bf16.h>
#include <cuda.h>
#include <stdint.h>

constexpr int NST = 6, STAGE = 28672;
constexpr int OFF_PHIK = NST * STAGE;
constexpr int OFF_V = OFF_PHIK + 32768;
constexpr int OFF_WPHI = OFF_V + 16384;
constexpr int OFF_CB = OFF_WPHI + 7168;
constexpr int OFF_BAR = OFF_CB + 3584;
constexpr int SMEM_BYTES = OFF_BAR + 16 * NST;
constexpr int FR = 16 * 8 * 28 * 32;
constexpr int SPIN = 1 << 18;
#define MC 0
#define MAPPING MC
#define MCS
#define MCA(n)
#define CLUSTER
#define PACE 2

__device__ uint4 g_F[4 * FR];
constexpr int XN = 0, XR = FR, OO = 2 * FR, X1 = 3 * FR;
__device__ uint4 g_P[8 * FR];
__device__ uint4 g_ST[16 * 8 * 8 * 8];
__device__ uint4 g_KVP[8 * 16 * 1024];
__device__ uint2 g_KVR[8 * 1024];
__device__ uint4 g_CS[448];
__device__ uint32_t g_H[16 * 8 * 8];
#define MARK(i)

__device__ __forceinline__ uint32_t s2u(const void* p) { return (uint32_t)__cvta_generic_to_shared(p); }
__device__ __forceinline__ void mbar_init(uint32_t b, uint32_t c) { asm volatile("mbarrier.init.shared::cta.b64 [%0], %1;" ::"r"(b), "r"(c)); }
__device__ __forceinline__ void mbar_expect(uint32_t b, uint32_t tx) { asm volatile("mbarrier.arrive.expect_tx.shared::cta.b64 _, [%0], %1;" ::"r"(b), "r"(tx) : "memory"); }
__device__ __forceinline__ void mbar_arrive_cl(uint32_t b, uint32_t rank) {
  asm volatile("{.reg .b32 r; mapa.shared::cluster.u32 r, %0, %1; mbarrier.arrive.shared::cluster.b64 _, [r];}" ::"r"(b), "r"(rank) : "memory");
}
__device__ __forceinline__ void mbar_wait(uint32_t b, uint32_t ph) {
  uint32_t ok = 0;
#pragma unroll 1
  for (int it = 0; it < SPIN && !ok; it++)
    asm volatile("{.reg .pred p; mbarrier.try_wait.parity.shared::cta.b64 p,[%1],%2; selp.u32 %0,1,0,p;}" : "=r"(ok) : "r"(b), "r"(ph) : "memory");
}
__device__ __forceinline__ void tma2d(uint32_t dst, const CUtensorMap* m, int c0, int c1, uint32_t bar) {
  asm volatile("cp.async.bulk.tensor.2d.shared::cluster.global.mbarrier::complete_tx::bytes" MCS " [%0], [%1, {%3, %4}], [%2]" MCA(5) ";"
               ::"r"(dst), "l"(m), "r"(bar), "r"(c0), "r"(c1), "h"((uint16_t)3) : "memory");
}
__device__ __forceinline__ void tma3d(uint32_t dst, const CUtensorMap* m, int c0, int c1, int c2, uint32_t bar) {
  asm volatile("cp.async.bulk.tensor.3d.shared::cluster.global.mbarrier::complete_tx::bytes" MCS " [%0], [%1, {%3, %4, %5}], [%2]" MCA(6) ";"
               ::"r"(dst), "l"(m), "r"(bar), "r"(c0), "r"(c1), "r"(c2), "h"((uint16_t)3) : "memory");
}
__device__ __forceinline__ void l2pf(const void* p, uint32_t bytes) { asm volatile("cp.async.bulk.prefetch.L2.global [%0], %1;" ::"l"(p), "r"(bytes) : "memory"); }
__device__ __forceinline__ void wg_fence() { asm volatile("wgmma.fence.sync.aligned;" ::: "memory"); }
__device__ __forceinline__ void wg_commit() { asm volatile("wgmma.commit_group.sync.aligned;" ::: "memory"); }
template <int N> __device__ __forceinline__ void wg_wait() { asm volatile("wgmma.wait_group.sync.aligned %0;" ::"n"(N) : "memory"); }
template <int N> __device__ __forceinline__ void regfence(float (&d)[N]) {
#pragma unroll
  for (int i = 0; i < N; i++) asm volatile("" : "+f"(d[i])::"memory");
}
__device__ __forceinline__ void bar_cons() { asm volatile("bar.sync 1, 256;" ::: "memory"); }
__device__ __forceinline__ void fence_async() { asm volatile("fence.proxy.async.shared::cta;" ::: "memory"); }
struct Desc { uint32_t lo, hi; };
__device__ __forceinline__ Desc mkdesc(uint32_t base16, uint32_t off, uint32_t lbo, uint32_t sbo, uint32_t swz) {
  return Desc{base16 + ((off >> 4) | ((lbo >> 4) << 16)), (sbo >> 4) | (swz << 30)};
}
__device__ __forceinline__ uint4 ldll(const uint4* p) {
  uint4 v; asm volatile("ld.relaxed.gpu.global.v4.u32 {%0,%1,%2,%3}, [%4];" : "=r"(v.x), "=r"(v.y), "=r"(v.z), "=r"(v.w) : "l"(p) : "memory"); return v;
}
__device__ __forceinline__ uint2 ldll2(const uint2* p) {
  uint2 v; asm volatile("ld.relaxed.gpu.global.v2.u32 {%0,%1}, [%2];" : "=r"(v.x), "=r"(v.y) : "l"(p) : "memory"); return v;
}
__device__ __forceinline__ void stll(uint4* p, uint32_t x, uint32_t y, uint32_t z, uint32_t w) {
  asm volatile("st.relaxed.gpu.global.v4.u32 [%0], {%1,%2,%3,%4};" ::"l"(p), "r"(x), "r"(y), "r"(z), "r"(w) : "memory");
}
__device__ __forceinline__ void stll2(void* p, uint32_t x, uint32_t y) {
  asm volatile("st.relaxed.gpu.global.v2.u32 [%0], {%1,%2};" ::"l"(p), "r"(x), "r"(y) : "memory");
}
__device__ __forceinline__ int laneid() { int l; asm volatile("mov.u32 %0, %%laneid;" : "=r"(l)); return l; }
__device__ __forceinline__ uint32_t tg(uint32_t w, uint32_t tag) { return (w & ~1u) | tag; }
__device__ __forceinline__ uint32_t pack(float lo, float hi) {
  uint32_t r; asm("cvt.rn.bf16x2.f32 %0, %1, %2;" : "=r"(r) : "f"(hi), "f"(lo)); return r;
}
__device__ __forceinline__ float blo(uint32_t w) { return __uint_as_float(w << 16); }
__device__ __forceinline__ float bhi(uint32_t w) { return __uint_as_float(w & 0xffff0000u); }
__device__ __forceinline__ float ex2(float x) { float r; asm("ex2.approx.ftz.f32 %0, %1;" : "=f"(r) : "f"(x)); return r; }
__device__ __forceinline__ float rcp(float x) { float r; asm("rcp.approx.ftz.f32 %0, %1;" : "=f"(r) : "f"(x)); return r; }
__device__ __forceinline__ float qsum(float v) { v += __shfl_xor_sync(~0u, v, 1); v += __shfl_xor_sync(~0u, v, 2); return v; }
__device__ __forceinline__ void sts32(uint32_t a, uint32_t v) { asm volatile("st.shared.u32 [%0], %1;" ::"r"(a), "r"(v) : "memory"); }
__device__ __forceinline__ void sts16(uint32_t a, uint32_t v) { asm volatile("st.shared.u16 [%0], %1;" ::"r"(a), "h"((uint16_t)v) : "memory"); }
__device__ __forceinline__ void sts128(uint32_t a, uint32_t x, uint32_t y, uint32_t z, uint32_t w) {
  asm volatile("st.shared.v4.u32 [%0], {%1,%2,%3,%4};" ::"r"(a), "r"(x), "r"(y), "r"(z), "r"(w) : "memory");
}
__device__ __forceinline__ uint32_t sw128(int row, int col) { return row * 128 + ((((col >> 3) ^ row) & 7) << 4) + (col & 7) * 2; }

__device__ __forceinline__ void wgmma_rs56(float (&d)[28], const uint32_t a0, const uint32_t a1, const uint32_t a2, const uint32_t a3, Desc db, int sd) {
  asm volatile("{.reg .pred p; .reg .b64 da, db; setp.ne.b32 p, %33, 0; mov.b64 db, {%32, %34};\n wgmma.mma_async.sync.aligned.m64n56k16.f32.bf16.bf16 {%0,%1,%2,%3,%4,%5,%6,%7,%8,%9,%10,%11,%12,%13,%14,%15,%16,%17,%18,%19,%20,%21,%22,%23,%24,%25,%26,%27}, {%28,%29,%30,%31}, db, p, 1, 1, 1;}"
   : "+f"(d[0]),"+f"(d[1]),"+f"(d[2]),"+f"(d[3]),"+f"(d[4]),"+f"(d[5]),"+f"(d[6]),"+f"(d[7]),"+f"(d[8]),"+f"(d[9]),"+f"(d[10]),"+f"(d[11]),"+f"(d[12]),"+f"(d[13]),"+f"(d[14]),"+f"(d[15]),"+f"(d[16]),"+f"(d[17]),"+f"(d[18]),"+f"(d[19]),"+f"(d[20]),"+f"(d[21]),"+f"(d[22]),"+f"(d[23]),"+f"(d[24]),"+f"(d[25]),"+f"(d[26]),"+f"(d[27])
   : "r"(a0),"r"(a1),"r"(a2),"r"(a3),"r"(db.lo),"r"(sd),"r"(db.hi));
}
__device__ __forceinline__ void wgmma_rs64(float (&d)[32], const uint32_t a0, const uint32_t a1, const uint32_t a2, const uint32_t a3, Desc db, int sd) {
  asm volatile("{.reg .pred p; .reg .b64 da, db; setp.ne.b32 p, %37, 0; mov.b64 db, {%36, %38};\n wgmma.mma_async.sync.aligned.m64n64k16.f32.bf16.bf16 {%0,%1,%2,%3,%4,%5,%6,%7,%8,%9,%10,%11,%12,%13,%14,%15,%16,%17,%18,%19,%20,%21,%22,%23,%24,%25,%26,%27,%28,%29,%30,%31}, {%32,%33,%34,%35}, db, p, 1, 1, 1;}"
   : "+f"(d[0]),"+f"(d[1]),"+f"(d[2]),"+f"(d[3]),"+f"(d[4]),"+f"(d[5]),"+f"(d[6]),"+f"(d[7]),"+f"(d[8]),"+f"(d[9]),"+f"(d[10]),"+f"(d[11]),"+f"(d[12]),"+f"(d[13]),"+f"(d[14]),"+f"(d[15]),"+f"(d[16]),"+f"(d[17]),"+f"(d[18]),"+f"(d[19]),"+f"(d[20]),"+f"(d[21]),"+f"(d[22]),"+f"(d[23]),"+f"(d[24]),"+f"(d[25]),"+f"(d[26]),"+f"(d[27]),"+f"(d[28]),"+f"(d[29]),"+f"(d[30]),"+f"(d[31])
   : "r"(a0),"r"(a1),"r"(a2),"r"(a3),"r"(db.lo),"r"(sd),"r"(db.hi));
}
__device__ __forceinline__ void wgmma_rs192(float (&d)[96], const uint32_t a0, const uint32_t a1, const uint32_t a2, const uint32_t a3, Desc db, int sd) {
  asm volatile("{.reg .pred p; .reg .b64 db; setp.ne.b32 p, %101, 0; mov.b64 db, {%100, %102};\n wgmma.mma_async.sync.aligned.m64n192k16.f32.bf16.bf16 {%0,%1,%2,%3,%4,%5,%6,%7,%8,%9,%10,%11,%12,%13,%14,%15,%16,%17,%18,%19,%20,%21,%22,%23,%24,%25,%26,%27,%28,%29,%30,%31,%32,%33,%34,%35,%36,%37,%38,%39,%40,%41,%42,%43,%44,%45,%46,%47,%48,%49,%50,%51,%52,%53,%54,%55,%56,%57,%58,%59,%60,%61,%62,%63,%64,%65,%66,%67,%68,%69,%70,%71,%72,%73,%74,%75,%76,%77,%78,%79,%80,%81,%82,%83,%84,%85,%86,%87,%88,%89,%90,%91,%92,%93,%94,%95}, {%96,%97,%98,%99}, db, p, 1, 1, 1;}"
   : "+f"(d[0]),"+f"(d[1]),"+f"(d[2]),"+f"(d[3]),"+f"(d[4]),"+f"(d[5]),"+f"(d[6]),"+f"(d[7]),"+f"(d[8]),"+f"(d[9]),"+f"(d[10]),"+f"(d[11]),"+f"(d[12]),"+f"(d[13]),"+f"(d[14]),"+f"(d[15]),"+f"(d[16]),"+f"(d[17]),"+f"(d[18]),"+f"(d[19]),"+f"(d[20]),"+f"(d[21]),"+f"(d[22]),"+f"(d[23]),"+f"(d[24]),"+f"(d[25]),"+f"(d[26]),"+f"(d[27]),"+f"(d[28]),"+f"(d[29]),"+f"(d[30]),"+f"(d[31]),"+f"(d[32]),"+f"(d[33]),"+f"(d[34]),"+f"(d[35]),"+f"(d[36]),"+f"(d[37]),"+f"(d[38]),"+f"(d[39]),"+f"(d[40]),"+f"(d[41]),"+f"(d[42]),"+f"(d[43]),"+f"(d[44]),"+f"(d[45]),"+f"(d[46]),"+f"(d[47]),"+f"(d[48]),"+f"(d[49]),"+f"(d[50]),"+f"(d[51]),"+f"(d[52]),"+f"(d[53]),"+f"(d[54]),"+f"(d[55]),"+f"(d[56]),"+f"(d[57]),"+f"(d[58]),"+f"(d[59]),"+f"(d[60]),"+f"(d[61]),"+f"(d[62]),"+f"(d[63]),"+f"(d[64]),"+f"(d[65]),"+f"(d[66]),"+f"(d[67]),"+f"(d[68]),"+f"(d[69]),"+f"(d[70]),"+f"(d[71]),"+f"(d[72]),"+f"(d[73]),"+f"(d[74]),"+f"(d[75]),"+f"(d[76]),"+f"(d[77]),"+f"(d[78]),"+f"(d[79]),"+f"(d[80]),"+f"(d[81]),"+f"(d[82]),"+f"(d[83]),"+f"(d[84]),"+f"(d[85]),"+f"(d[86]),"+f"(d[87]),"+f"(d[88]),"+f"(d[89]),"+f"(d[90]),"+f"(d[91]),"+f"(d[92]),"+f"(d[93]),"+f"(d[94]),"+f"(d[95])
   : "r"(a0),"r"(a1),"r"(a2),"r"(a3),"r"(db.lo),"r"(sd),"r"(db.hi));
}
__device__ __forceinline__ void wgmma_rs32(float (&d)[16], const uint32_t a0, const uint32_t a1, const uint32_t a2, const uint32_t a3, Desc db, int sd) {
  asm volatile("{.reg .pred p; .reg .b64 db; setp.ne.b32 p, %21, 0; mov.b64 db, {%20, %22};\n wgmma.mma_async.sync.aligned.m64n32k16.f32.bf16.bf16 {%0,%1,%2,%3,%4,%5,%6,%7,%8,%9,%10,%11,%12,%13,%14,%15}, {%16,%17,%18,%19}, db, p, 1, 1, 1;}"
   : "+f"(d[0]),"+f"(d[1]),"+f"(d[2]),"+f"(d[3]),"+f"(d[4]),"+f"(d[5]),"+f"(d[6]),"+f"(d[7]),"+f"(d[8]),"+f"(d[9]),"+f"(d[10]),"+f"(d[11]),"+f"(d[12]),"+f"(d[13]),"+f"(d[14]),"+f"(d[15])
   : "r"(a0),"r"(a1),"r"(a2),"r"(a3),"r"(db.lo),"r"(sd),"r"(db.hi));
}
__device__ __forceinline__ void wgmma_ss32(float (&d)[16], Desc da, Desc db, int sd) {
  asm volatile("{.reg .pred p; .reg .b64 da, db; setp.ne.b32 p, %18, 0; mov.b64 da, {%16, %19}; mov.b64 db, {%17, %19};\n wgmma.mma_async.sync.aligned.m64n32k16.f32.bf16.bf16 {%0,%1,%2,%3,%4,%5,%6,%7,%8,%9,%10,%11,%12,%13,%14,%15}, da, db, p, 1, 1, 1, 1;}"
   : "+f"(d[0]),"+f"(d[1]),"+f"(d[2]),"+f"(d[3]),"+f"(d[4]),"+f"(d[5]),"+f"(d[6]),"+f"(d[7]),"+f"(d[8]),"+f"(d[9]),"+f"(d[10]),"+f"(d[11]),"+f"(d[12]),"+f"(d[13]),"+f"(d[14]),"+f"(d[15])
   : "r"(da.lo),"r"(db.lo),"r"(sd),"r"(db.hi));
}

template <int S, int N, bool SPL = false, int T> __device__ __forceinline__ void ll_issue(uint4 (&v)[T], const uint4* p, int stride, const uint2* p2 = nullptr) {
#pragma unroll
  for (int i = S; i < S + N; i++) {
    if (SPL && i % 7 == 3) { const uint2 lo = ldll2(p2 + i * 64), hi = ldll2(p2 + i * 64 + 32); v[i] = make_uint4(lo.x, lo.y, hi.x, hi.y); }
    else v[i] = ldll(p + i * stride);
  }
}
template <int S, int N, bool SPL, int T> __device__ __forceinline__ void ll_check(uint4 (&v)[T], const uint4* p, int stride, uint32_t tag, const uint2* p2 = nullptr) {
#pragma unroll 1
  for (int it = 0; it < SPIN; it++) {
    uint32_t bad = 0;
#pragma unroll
    for (int i = S; i < S + N; i++) bad |= (v[i].x ^ tag) | ((SPL && i % 7 == 3) ? (v[i].z ^ tag) : 0u);
    if (!__any_sync(~0u, bad & 1)) break;
    ll_issue<S, N, SPL>(v, p, stride, p2);
  }
}
__device__ __forceinline__ void hint_post(uint32_t* p, uint32_t v, int lane) {
  if (lane == 0) asm volatile("st.relaxed.gpu.global.u32 [%0], %1;" ::"l"(p), "r"(v) : "memory");
}
__device__ __forceinline__ void hint_wait(const uint32_t* p, uint32_t s) {
#pragma unroll 1
  for (int it = 0; it < SPIN; it++) {
    uint32_t v; asm volatile("ld.relaxed.gpu.global.u32 %0, [%1];" : "=r"(v) : "l"(p) : "memory");
    if (__all_sync(~0u, v - s < 10u)) break;
  }
}
__device__ __forceinline__ void slice_store(uint4* pf, uint2* ph, const uint32_t (&w)[14], bool odd) {
#pragma unroll
  for (int u = 0; u < 3; u++)
    stll(pf + u * 32, odd ? w[4 * u + 2] : w[4 * u], odd ? w[4 * u + 3] : w[4 * u + 1], odd ? w[4 * u + 4] : w[4 * u + 2], odd ? w[4 * u + 5] : w[4 * u + 3]);
  stll2(ph, odd ? w[0] : w[12], odd ? w[1] : w[13]);
}
template <class F, class M> __device__ __forceinline__ void hedgehog(const float (&d)[28], F sink, M mid) {
  const float L2E = 1.4426950408889634f;
#define HX(G, p) ((p) < 6 ? d[((G) & 1) * 16 + ((p) >> 1) * 4 + ((p) & 1) + ((G) & 2)] : d[12 + (G)])
  float mx[4], mn[4], sp[4], sn[4], ep[4][7], en[4][7];
#pragma unroll
  for (int G = 0; G < 4; G++) {
    mx[G] = mn[G] = HX(G, 0);
#pragma unroll
    for (int p = 1; p < 7; p++) { mx[G] = fmaxf(mx[G], HX(G, p)); mn[G] = fminf(mn[G], HX(G, p)); }
  }
#pragma unroll
  for (int o = 1; o < 4; o <<= 1)
#pragma unroll
    for (int G = 0; G < 4; G++) { mx[G] = fmaxf(mx[G], __shfl_xor_sync(~0u, mx[G], o)); mn[G] = fminf(mn[G], __shfl_xor_sync(~0u, mn[G], o)); }
#pragma unroll
  for (int G = 0; G < 4; G++) {
    const float a = -mx[G] * L2E, b = mn[G] * L2E;
#pragma unroll
    for (int p = 0; p < 7; p++) { ep[G][p] = ex2(fmaf(HX(G, p), L2E, a)); en[G][p] = ex2(fmaf(HX(G, p), -L2E, b)); }
    sp[G] = ((ep[G][0] + ep[G][1]) + (ep[G][2] + ep[G][3])) + ((ep[G][4] + ep[G][5]) + ep[G][6]);
    sn[G] = ((en[G][0] + en[G][1]) + (en[G][2] + en[G][3])) + ((en[G][4] + en[G][5]) + en[G][6]);
    if (G == 1) mid();
  }
#pragma unroll
  for (int o = 1; o < 4; o <<= 1)
#pragma unroll
    for (int G = 0; G < 4; G++) { sp[G] += __shfl_xor_sync(~0u, sp[G], o); sn[G] += __shfl_xor_sync(~0u, sn[G], o); }
#pragma unroll
  for (int G = 0; G < 4; G++) {
    const float a = rcp(sp[G]), b = rcp(sn[G]);
#pragma unroll
    for (int p = 0; p < 7; p++) sink(G >> 1, G & 1, p, pack(ep[G][p] * a, en[G][p] * b));
  }
}
__device__ __forceinline__ void phi_gemm(const float (&x)[28], float (&y)[28], uint32_t wphi) {
  uint32_t f[14];
#pragma unroll
  for (int j = 0; j < 14; j++) f[j] = pack(x[2 * j], x[2 * j + 1]);
  wg_fence();
#pragma unroll
  for (int ks = 0; ks < 3; ks++) wgmma_rs56(y, f[4 * ks], f[4 * ks + 1], f[4 * ks + 2], f[4 * ks + 3], mkdesc(wphi, ks * 2048, 1024, 1024, 1), ks);
  wgmma_rs56(y, f[12], f[13], 0u, 0u, mkdesc(wphi, 3 * 2048, 1024, 1024, 1), 1);
  wg_commit();
}
__device__ __forceinline__ void ln_publish(uint32_t (&xw)[4][4], float* sLN, int warp, int lane, uint4* fb, uint32_t tag) {
  const int g = lane >> 2; const bool full = warp < 4;
  float s0 = 0.f, s1 = 0.f;
#pragma unroll
  for (int u = 0; u < 4; u++) {
    s0 += (blo(xw[u][0]) + bhi(xw[u][0])) + (blo(xw[u][2]) + bhi(xw[u][2]));
    s1 += (blo(xw[u][1]) + bhi(xw[u][1])) + (blo(xw[u][3]) + bhi(xw[u][3]));
  }
  const float rc = full ? 1.f / 64 : 1.f / 48;
  s0 = qsum(s0); s1 = qsum(s1);
  const float a0 = s0 * rc, a1 = s1 * rc;
  float v0 = 0.f, v1 = 0.f;
#pragma unroll
  for (int u = 0; u < 4; u++)
    if (u < 3 || full) {
#pragma unroll
      for (int k = 0; k < 4; k += 2) {
        float a = blo(xw[u][k]) - a0, b = bhi(xw[u][k]) - a0, c2 = blo(xw[u][k + 1]) - a1, d2 = bhi(xw[u][k + 1]) - a1;
        v0 += a * a + b * b; v1 += c2 * c2 + d2 * d2;
      }
    }
  v0 = qsum(v0); v1 = qsum(v1);
  if ((lane & 3) == 0) *(float4*)(sLN + (g * 8 + warp) * 4) = make_float4(s0, v0, s1, v1);
  bar_cons();
  const float4 ea = *(const float4*)(sLN + (g * 8 + (lane & 3)) * 4), eb = *(const float4*)(sLN + (g * 8 + 4 + (lane & 3)) * 4);
  const float m0 = qsum(ea.x + eb.x) * (1.f / 448), m1 = qsum(ea.z + eb.z) * (1.f / 448);
  const float d0 = ea.x * (1.f / 64) - m0, d1 = eb.x * (1.f / 48) - m0, d2 = ea.z * (1.f / 64) - m1, d3 = eb.z * (1.f / 48) - m1;
  v0 = qsum(ea.y + eb.y + 64.f * d0 * d0 + 48.f * d1 * d1); v1 = qsum(ea.w + eb.w + 64.f * d2 * d2 + 48.f * d3 * d3);
  const float r0 = rsqrtf(v0 * (1.f / 448) + 1e-5f), r1 = rsqrtf(v1 * (1.f / 448) + 1e-5f), n0 = -m0 * r0, n1 = -m1 * r1;
#pragma unroll
  for (int u = 0; u < 4; u++)
    if (u < 3 || full)
      stll(fb + XN + u * 256, tg(pack(fmaf(blo(xw[u][0]), r0, n0), fmaf(bhi(xw[u][0]), r0, n0)), tag), pack(fmaf(blo(xw[u][1]), r1, n1), fmaf(bhi(xw[u][1]), r1, n1)),
           pack(fmaf(blo(xw[u][2]), r0, n0), fmaf(bhi(xw[u][2]), r0, n0)), pack(fmaf(blo(xw[u][3]), r1, n1), fmaf(bhi(xw[u][3]), r1, n1)));
}

__global__ void CLUSTER __launch_bounds__(384, 1)
fused_kernel(const __grid_constant__ CUtensorMap mQKV, const __grid_constant__ CUtensorMap mWO, const __grid_constant__ CUtensorMap mW1,
             const __grid_constant__ CUtensorMap mW1b, const __grid_constant__ CUtensorMap mW2, const __grid_constant__ CUtensorMap mW2b, const __nv_bfloat16* __restrict__ x, const __nv_bfloat16* __restrict__ wphi,
             const __nv_bfloat16* __restrict__ wo, const __nv_bfloat16* __restrict__ w1, const __nv_bfloat16* __restrict__ b1,
             const __nv_bfloat16* __restrict__ w2, const __nv_bfloat16* __restrict__ b2, __nv_bfloat16* __restrict__ out) {
  extern __shared__ __align__(1024) uint8_t sm[];
  const uint32_t sb = s2u(sm);
  const int tid = threadIdx.x, warp = __shfl_sync(~0u, tid >> 5, 0), lane = tid & 31,
            t = MAPPING ? (blockIdx.x >> 4) * 2 + (blockIdx.x & 1) : blockIdx.x >> 3, c = MAPPING ? (blockIdx.x >> 1) & 7 : blockIdx.x & 7;
  const uint32_t bfull = sb + OFF_BAR, bempty = bfull + 8 * NST;

#define XOFF(l) ((t * 128 + c * 16 + ((l) >> 2)) * 448 + warp * 16 + 2 * ((l) & 3))
  if (warp < 8) MARK(0);
  uint32_t xw[4][4];
  if (warp < 8) {
    const uint32_t* xp = (const uint32_t*)(x + XOFF(lane));
#pragma unroll
    for (int u = 0; u < 4; u++) {
      if (u < 3 || warp < 4) { xw[u][0] = __ldg(xp + u * 64); xw[u][1] = __ldg(xp + u * 64 + 1792); xw[u][2] = __ldg(xp + u * 64 + 4); xw[u][3] = __ldg(xp + u * 64 + 1796); }
      else { xw[u][0] = xw[u][1] = xw[u][2] = xw[u][3] = 0; }
    }
  }
  if (tid == 256) {
    for (int s = 0; s < NST; s++) { mbar_init(bfull + 8 * s, 1); mbar_init(bempty + 8 * s, MC ? 16 : 8); }
    asm volatile("fence.mbarrier_init.release.cluster;" ::: "memory");
    fence_async();
  }
  asm volatile("barrier.cluster.arrive.release.aligned; barrier.cluster.wait.acquire.aligned;" ::: "memory");
  if (warp >= 8) {
    asm volatile("setmaxnreg.dec.sync.aligned.u32 24;");
    auto issue = [&](int i, int s) {
      const uint32_t dst = sb + s * STAGE, bar = bfull + 8 * s;
      mbar_expect(bar, STAGE);
#pragma unroll 1
      for (int rk = MC ? (blockIdx.x & 1) : 0; rk < (MC ? (blockIdx.x & 1) + 1 : 2); rk++)
      if (i < 4) tma2d(dst + rk * 14336, &mQKV, 448 + 448 * rk + 56 * c, 112 * i, bar);
      else if (i < 8) tma2d(dst + rk * 14336, i < 6 ? &mQKV : &mWO, (i < 6 ? 56 : 64) * c, 224 * (i & 1) + 112 * rk, bar);
      else if (i < 15) { const int k0 = 64 * ((i - 8 + c) % 7) + 32 * rk;
        tma3d(dst + rk * 12288, &mW1, 0, k0, 3 * c, bar); tma2d(dst + 24576 + rk * 2048, &mW1b, 1536 + 32 * c, k0, bar); }
      else { tma2d(dst + rk * 12288, &mW2, 64 * (i - 15), 192 * c + 96 * rk, bar); tma2d(dst + 24576 + rk * 2048, &mW2b, 64 * (i - 15), 1536 + 32 * c + 16 * rk, bar); }
    };
    if (warp == 8) {
      int s = 0; uint32_t ph = 1;
      for (int n = 0; n < 44; n++) {
        if (n == PACE) asm volatile("bar.sync 2, 288;" ::: "memory");
        mbar_wait(bempty + 8 * s, ph);
        if (lane == 0) issue(n >= 22 ? n - 22 : n, s);
        __syncwarp();
        if (++s == NST) { s = 0; ph ^= 1; }
      }
    } else if (warp == 9) {
      mbar_wait(bfull + 8 * 3, 0);
      if (lane == 0) {
        l2pf((const uint8_t*)wo + blockIdx.x * 3136, 3136);
        l2pf((const uint8_t*)w1 + blockIdx.x * 12544, 12544);
        l2pf((const uint8_t*)w2 + blockIdx.x * 12544, 12544);
      }
      if (blockIdx.x < 112) {
        const uint2* wp = (const uint2*)(w1 + (size_t)(lane >> 2) * 1792 + blockIdx.x * 16 + (lane & 3) * 4);
        float s0 = 0.f, s1 = 0.f, s2 = 0.f, s3 = 0.f;
#pragma unroll 8
        for (int i = 0; i < 56; i++) { const uint2 v = __ldg(wp + i * 8 * 448); s0 += blo(v.x); s1 += bhi(v.x); s2 += blo(v.y); s3 += bhi(v.y); }
#pragma unroll 1
        for (int o = 4; o < 32; o <<= 1) { s0 += __shfl_xor_sync(~0u, s0, o); s1 += __shfl_xor_sync(~0u, s1, o); s2 += __shfl_xor_sync(~0u, s2, o); s3 += __shfl_xor_sync(~0u, s3, o); }
        if (lane < 4) stll(g_CS + blockIdx.x * 4 + lane, tg(__float_as_uint(s0), 1), __float_as_uint(s1), __float_as_uint(s2), __float_as_uint(s3));
      }
      asm volatile("bar.sync 6, 96;" ::: "memory");
#pragma unroll 1
      for (int i = 0; i < 2; i++) {
        const int e = lane < 28 ? lane + 28 * i : 0;
        uint4 cv[1];
        const int e4 = e < 48 ? 48 * c + e : 336 + 8 * c + e;
        ll_issue<0, 1>(cv, g_CS + e4, 0); ll_check<0, 1, false>(cv, g_CS + e4, 0, 1u);
        const uint2 bb = __ldg((const uint2*)b1 + e4);
        const uint32_t h0 = pack(__uint_as_float(cv[0].x), __uint_as_float(cv[0].y)), h1 = pack(__uint_as_float(cv[0].z), __uint_as_float(cv[0].w));
        const uint32_t l0 = pack(__uint_as_float(cv[0].x) - blo(h0), __uint_as_float(cv[0].y) - bhi(h0)), l1 = pack(__uint_as_float(cv[0].z) - blo(h1), __uint_as_float(cv[0].w) - bhi(h1));
#pragma unroll 1
        for (int r = 0; r < 8; r++) {
          const uint32_t ad = sb + OFF_CB + (e >> 3) * 512 + r * 64 + ((((e >> 1) ^ (r >> 1)) & 3) << 4) + (e & 1) * 8;
          sts32(ad, r < 2 ? h0 : r == 2 ? l0 : r < 5 ? bb.x : 0u); sts32(ad + 4, r < 2 ? h1 : r == 2 ? l1 : r < 5 ? bb.y : 0u);
        }
      }
      fence_async();
      asm volatile("bar.arrive 4, 288;" ::: "memory");
    } else if (warp >= 10) {
      const int h = warp - 10;
      uint32_t wv[13];
#pragma unroll
      for (int i = 0; i < 13; i++) { const int e = lane + 32 * i; wv[i] = e < 392 ? __ldg((const uint32_t*)wphi + (2 * c + h) * 392 + e) : 0u; }
#pragma unroll 1
      for (int i = 0; i < 8; i++) sts128(sb + OFF_WPHI + (h * 256 + i * 32 + lane) * 16, 0, 0, 0, 0);
      asm volatile("bar.arrive 6, 96;" ::: "memory");
#pragma unroll 1
      for (int i = 0; i < 4; i++) sts128(sb + OFF_PHIK + sw128(h * 128 + i * 32 + lane, 56), 0, 0, 0, 0);
      asm volatile("bar.sync 5, 64;" ::: "memory");
#pragma unroll
      for (int i = 0; i < 13; i++) {
        const int e = lane + 32 * i, d = e / 14, f2 = 2 * (e - 14 * d), k = 28 * h + d;
        if (e < 392) {
          if (f2 < 24) sts32(sb + OFF_WPHI + sw128(k, 32 * h + f2), wv[i]);
          else { sts16(sb + OFF_WPHI + sw128(k, 2 * f2 - 24 + h), wv[i]); sts16(sb + OFF_WPHI + sw128(k, 2 * f2 - 22 + h), wv[i] >> 16); }
        }
      }
      fence_async();
      asm volatile("bar.arrive 3, 320;" ::: "memory");
    }
  } else {
  asm volatile("setmaxnreg.inc.sync.aligned.u32 240;");

  const int wg = warp >> 2, g = lane >> 2, q = lane & 3;
  const int row0 = warp * 16 + g;
#define PTRS const int ln_ = laneid(); \
  uint4* const fm = g_F + ((t * 8 + warp) * 28) * 32 + ln_;            \
  uint4* const fr = g_F + ((t * 8 + c) * 28 + warp) * 32 + ln_;        \
  uint4* const sf = fm + (7 * (c >> 1) + 4 * (c & 1)) * 32;             \
  uint2* const f2 = (uint2*)(fm - ln_) + ln_;                           \
  uint2* const sh = f2 + (7 * (c >> 1) + 3) * 64 + 32 * (c & 1);        \
  uint32_t* const hme = g_H + (t * 8 + warp) * 8 + c; \
  const uint32_t* const hrow = g_H + (t * 8 + warp) * 8 + (ln_ & 7); \
  (void)fm; (void)fr; (void)sf; (void)f2; (void)sh; (void)hme; (void)hrow;
  float* sLN = (float*)(sm + OFF_V);
  const uint32_t sPK = sb + OFF_PHIK, sV = sb + OFF_V, d16 = (sb & 0x3FFFF) >> 4;
    int cs = 0, rs = 0; uint32_t cph = 0;
  auto acquire = [&]() -> uint32_t { mbar_wait(bfull + 8 * cs, cph); const uint32_t a = d16 + cs * (STAGE >> 4); if (++cs == NST) { cs = 0; cph ^= 1; } return a; };
  int nrel = 44 - NST;
  auto release = [&]() { if (lane < 1 + MC && nrel > 0) mbar_arrive_cl(bempty + 8 * rs, lane); nrel--; if (++rs == NST) rs = 0; };

#pragma unroll 1
  for (int L = 0; L < 2; L++) {
    const uint32_t tag = 1 - L;
    uint32_t phq[2][2][7];
    const uint32_t hs = 10 * L;
    {
      PTRS
      ln_publish(xw, sLN, warp, lane, fr, tag);
      hint_post(hme, hs + 1, lane);
#pragma unroll
      for (int u = 0; u < 4; u++) if (u < 3 || wg == 0) stll(fr + XR + u * 256, tg(xw[u][0], tag), xw[u][1], xw[u][2], xw[u][3]);
    }
    MARK(1 + L * 19);
    {
      PTRS
      uint4 a[28];
      const uint4* pa = fm + XN;
      hint_wait(g_H + (t * 8 + (ln_ & 7)) * 8 + warp, hs + 1); ll_issue<0, 28>(a, pa, 32);
      if (L == 0) asm volatile("bar.arrive 2, 288;" ::: "memory");
      MARK(2 + L * 19);
      float ak[28], av[28], aq[28], pp[28];
#define KVSTAGE(i) { ll_check<7 * i, 7, false>(a, pa, 32, tag); const uint32_t st = acquire(); wg_fence(); \
      _Pragma("unroll") for (int ks = 0; ks < 7; ks++) { const uint4 f = a[7 * i + ks]; \
        wgmma_rs56(ak, f.x, f.y, f.z, f.w, mkdesc(st, ks * 2048, 1024, 1024, 1), i | ks); \
        wgmma_rs56(av, f.x, f.y, f.z, f.w, mkdesc(st, 14336 + ks * 2048, 1024, 1024, 1), i | ks); } \
      wg_commit(); if (i > 0) { wg_wait<1>(); release(); } }
      KVSTAGE(0) KVSTAGE(1) KVSTAGE(2) KVSTAGE(3)
      wg_wait<0>(); release(); regfence(ak); regfence(av);
      MARK(3 + L * 19);
      if (L == 0) asm volatile("bar.sync 3, 320;" ::: "memory");
      phi_gemm(ak, pp, d16 + (OFF_WPHI >> 4));
#pragma unroll
      for (int j = 0; j < 7; j++) {
        const int n = 8 * j + 2 * q, n2 = n < 28 ? n : n + 4;
        sts32(sV + sw128(row0, n2), pack(av[4 * j], av[4 * j + 1])); sts32(sV + sw128(row0 + 8, n2), pack(av[4 * j + 2], av[4 * j + 3]));
      }
      { const int n2 = 28 + 2 * (q & 1) + 32 * (q >> 1); const uint32_t v = (q & 1) ? 0u : 0x3F80u; sts32(sV + sw128(row0, n2), v); sts32(sV + sw128(row0 + 8, n2), v); }
      wg_wait<0>(); regfence(pp);
      hedgehog(pp, [&](int r, int h, int p, uint32_t v) { sts32(sPK + h * 16384 + sw128(row0 + 8 * r, 8 * p + 2 * q), v); }, [] {});
      fence_async();
      bar_cons();
      MARK(4 + L * 19);
      float kv[16];
      wg_fence();
#pragma unroll
      for (int ks = 0; ks < 8; ks++) wgmma_ss32(kv, mkdesc(d16 + wg * 1024, OFF_PHIK + ks * 2048, 1024, 1024, 1), mkdesc(d16 + wg * 4, OFF_V + ks * 2048, 1024, 1024, 1), ks);
      wg_commit(); wg_wait<0>(); regfence(kv);
      const int ln2 = laneid();
#pragma unroll
      for (int u = 0; u < 4; u++) {
        float e[4];
#pragma unroll
        for (int i = 0; i < 4; i++) e[i] = kv[4 * u + i];
        stll(g_KVP + (c * 16 + t) * 1024 + wg * 512 + u * 128 + (warp & 3) * 32 + ln2, tg(__float_as_uint(e[0]), tag), __float_as_uint(e[1]), __float_as_uint(e[2]), __float_as_uint(e[3]));
      }
      MARK(5 + L * 19);
      uint4 k4[4];
      const uint4* pk = g_KVP + (c * 16 + 4 * (ln2 & 3)) * 1024 + 64 * t + warp * 8 + (ln2 >> 2);
#pragma unroll
      for (int i = 0; i < 2; i++) {
        const uint32_t st = acquire(); wg_fence();
#pragma unroll
        for (int ks = 0; ks < 14; ks++) { const uint4 f = a[14 * i + ks]; wgmma_rs56(aq, f.x, f.y, f.z, f.w, mkdesc(st, ks * 2048, 1024, 1024, 1), i | ks); }
        wg_commit();
        if (i == 0) ll_issue<0, 4>(k4, pk, 1024);
      }
      ll_check<0, 4, false>(k4, pk, 1024, tag);
      float s0 = 0, s1 = 0, s2 = 0, s3 = 0;
#pragma unroll
      for (int i = 0; i < 4; i++) { s0 += __uint_as_float(k4[i].x); s1 += __uint_as_float(k4[i].y); s2 += __uint_as_float(k4[i].z); s3 += __uint_as_float(k4[i].w); }
      s0 = qsum(s0); s1 = qsum(s1); s2 = qsum(s2); s3 = qsum(s3);
      if (q == 0) stll2(g_KVR + c * 1024 + 64 * t + warp * 8 + (ln2 >> 2), tg(pack(s0, s1), tag), pack(s2, s3));
      MARK(6 + L * 19);
      wg_wait<0>(); release(); release(); regfence(aq);
      phi_gemm(aq, pp, d16 + (OFF_WPHI >> 4));
      bar_cons();
#pragma unroll
      for (int i = 0; i < 4; i++) sts128(sV + warp * 2048 + (lane + i * 32) * 16, 0, 0, 0, 0);
      wg_wait<0>(); regfence(pp);
      uint2 r[4];
      const uint2* pr = g_KVR + c * 1024 + wg * 512 + (warp & 3) * 32 + ln2;
      hedgehog(pp, [&](int r, int h, int p, uint32_t v) { phq[r][h][p] = v; }, [&] {
#pragma unroll
        for (int u = 0; u < 4; u++) r[u] = ldll2(pr + u * 128); });
      MARK(7 + L * 19);
#pragma unroll 1
      for (int it = 0; it < SPIN; it++) {
        if (!__any_sync(~0u, ((r[0].x ^ tag) | (r[1].x ^ tag) | (r[2].x ^ tag) | (r[3].x ^ tag)) & 1)) break;
#pragma unroll
        for (int u = 0; u < 4; u++) r[u] = ldll2(pr + u * 128);
      }
#pragma unroll
      for (int u = 0; u < 4; u++) {
        const int d = 8 * u + 2 * q;
        if (d < 28) { sts32(sV + sw128(row0, 28 * wg + d), r[u].x); sts32(sV + sw128(row0 + 8, 28 * wg + d), r[u].y); }
        else if (d == 28) {
#pragma unroll
          for (int j = 0; j < 4; j++) { sts16(sV + sw128(row0, 56 + 2 * j + wg), r[u].x); sts16(sV + sw128(row0 + 8, 56 + 2 * j + wg), r[u].y); }
        }
      }
      fence_async();
      bar_cons();
      MARK(8 + L * 19);
      float o[32];
      wg_fence();
#pragma unroll
      for (int ks = 0; ks < 8; ks++) {
        const int h = ks >> 2, p = 2 * (ks & 3);
        wgmma_rs64(o, phq[0][h][p], phq[1][h][p], p < 6 ? phq[0][h][p < 6 ? p + 1 : 0] : 0u, p < 6 ? phq[1][h][p < 6 ? p + 1 : 0] : 0u, mkdesc(d16, OFF_V + ks * 2048, 1024, 1024, 1), ks);
      }
      wg_commit(); wg_wait<0>(); regfence(o);
      const float iA0 = rcp(o[28] + 1e-6f), iB0 = rcp(o[29] + 1e-6f), iA1 = rcp(o[30] + 1e-6f), iB1 = rcp(o[31] + 1e-6f);
      uint32_t w[14];
      { PTRS
#pragma unroll
      for (int j = 0; j < 7; j++) {
        const bool hb = 8 * j + 2 * q >= 28; const float i0 = hb ? iB0 : iA0, i1 = hb ? iB1 : iA1;
        w[2 * j] = pack(o[4 * j] * i0, o[4 * j + 1] * i0); w[2 * j + 1] = pack(o[4 * j + 2] * i1, o[4 * j + 3] * i1);
        if (j == 0 || ((j ^ c) & 1) == 0) w[2 * j] = tg(w[2 * j], tag);
      }
      slice_store(sf + OO, sh + 2 * OO, w, c & 1);
      hint_post(hme, hs + 2, lane); }
    }
    MARK(9 + L * 19);
    uint4 xr[4];
    if (c < 7) {
      PTRS
      ll_issue<0, 4>(xr, fm + XR + 128 * c, 32);
      uint4 a[28];
      const uint4* pa = fm + OO;
      hint_wait(hrow, hs + 2);
      MARK(10 + L * 19);
      ll_issue<0, 28, true>(a, pa, 32, f2 + 2 * OO);
      float y[32];
      uint32_t st;
#define WOSTEP(i) { ll_check<7 * i, 7, true>(a, pa, 32, tag, f2 + 2 * OO); if (!(i & 1)) st = acquire(); wg_fence(); \
      _Pragma("unroll") for (int ks = 0; ks < 7; ks++) { const uint4 f = a[7 * i + ks]; \
        wgmma_rs64(y, f.x, f.y, f.z, f.w, mkdesc(st, ((i & 1) * 7 + ks) * 2048, 1024, 1024, 1), i | ks); } wg_commit(); }
      WOSTEP(0) WOSTEP(1) WOSTEP(2) WOSTEP(3)
      ll_check<0, 4, false>(xr, fm + XR + 128 * c, 32, tag);
      wg_wait<0>(); regfence(y);
      MARK(11 + L * 19);
#pragma unroll
      for (int u = 0; u < 4; u++) {
        xr[u].x = tg(pack(blo(xr[u].x) + y[8 * u], bhi(xr[u].x) + y[8 * u + 1]), tag); xr[u].y = pack(blo(xr[u].y) + y[8 * u + 2], bhi(xr[u].y) + y[8 * u + 3]);
        xr[u].z = pack(blo(xr[u].z) + y[8 * u + 4], bhi(xr[u].z) + y[8 * u + 5]); xr[u].w = pack(blo(xr[u].w) + y[8 * u + 6], bhi(xr[u].w) + y[8 * u + 7]);
        stll(fm + X1 + 128 * c + u * 32, xr[u].x, xr[u].y, xr[u].z, xr[u].w);
      }
      if (c == 0) hint_post(hme, hs + 3, lane);
    } else {
      PTRS
      acquire(); acquire();
      hint_wait(g_H + (t * 8 + warp) * 8, hs + 3);
      ll_issue<0, 4>(xr, fm + X1, 32); ll_check<0, 4, false>(xr, fm + X1, 32, tag);
      MARK(10 + L * 19); MARK(11 + L * 19);
    }
    uint32_t hf[56];
    float rr0, rr1;
    {
      PTRS
      uint4 a[28];
      const uint4* pa = fm + X1;
      auto grp = [&](int i) -> const uint4* { const int k = i + c; return pa + ((k >= 7 ? k - 7 : k) - i) * 128; };
#pragma unroll
      for (int u = 0; u < 4; u++) a[u] = xr[u];
      float y[96], z[16];
#define F1STAGE(i) { if (i > 0) ll_check<4 * i, 4, false>(a, grp(i), 32, tag); const uint32_t st = acquire(); wg_fence(); \
      _Pragma("unroll") for (int ks = 0; ks < 4; ks++) { const uint4 f = a[4 * i + ks]; \
        wgmma_rs192(y, f.x, f.y, f.z, f.w, mkdesc(st, (ks >> 1) * 12288 + (ks & 1) * 2048, 4096, 1024, 1), i | ks); \
        wgmma_rs32(z, f.x, f.y, f.z, f.w, mkdesc(st, 24576 + ks * 1024, 512, 512, 2), i | ks); } \
      wg_commit(); if (i > 0) { wg_wait<1>(); release(); if (i < 4) ll_issue<(i < 4 ? 4 * i + 12 : 0), 4>(a, grp(i + 3), 32); } }
      F1STAGE(0)
      MARK(12 + L * 19);
      ll_issue<4, 4>(a, grp(1), 32); ll_issue<8, 4>(a, grp(2), 32); ll_issue<12, 4>(a, grp(3), 32);
      if (c < 7) {
        float s0 = 0.f, s1 = 0.f, v0 = 0.f, v1 = 0.f;
#pragma unroll
        for (int u = 0; u < 4; u++) { s0 += (blo(xr[u].x) + bhi(xr[u].x)) + (blo(xr[u].z) + bhi(xr[u].z)); s1 += (blo(xr[u].y) + bhi(xr[u].y)) + (blo(xr[u].w) + bhi(xr[u].w)); }
        s0 = qsum(s0) * (1.f / 64); s1 = qsum(s1) * (1.f / 64);
#pragma unroll
        for (int u = 0; u < 4; u++) {
          const float d0 = blo(xr[u].x) - s0, d1 = bhi(xr[u].x) - s0, d2 = blo(xr[u].z) - s0, d3 = bhi(xr[u].z) - s0;
          const float d4 = blo(xr[u].y) - s1, d5 = bhi(xr[u].y) - s1, d6 = blo(xr[u].w) - s1, d7 = bhi(xr[u].w) - s1;
          v0 += (d0 * d0 + d1 * d1) + (d2 * d2 + d3 * d3); v1 += (d4 * d4 + d5 * d5) + (d6 * d6 + d7 * d7);
        }
        v0 = qsum(v0); v1 = qsum(v1);
        if (q == 0) stll(g_ST + ((t * 8 + warp) * 8 + c) * 8 + (ln_ >> 2), tg(__float_as_uint(s0), tag), __float_as_uint(v0), __float_as_uint(s1), __float_as_uint(v1));
      }
      release(); release();
      F1STAGE(1) MARK(13 + L * 19); F1STAGE(2) F1STAGE(3)
      uint4 sv[2];
      const uint4* ps = g_ST + ((t * 8 + warp) * 8 + 2 * (laneid() & 3)) * 8 + (laneid() >> 2);
      ll_issue<0, 2>(sv, ps, q < 3 ? 8 : 0);
      F1STAGE(4)
      ll_check<0, 2, false>(sv, ps, q < 3 ? 8 : 0, tag);
      const float wb = q < 3 ? 1.f : 0.f;
      const float ma = __uint_as_float(sv[0].x), mb = __uint_as_float(sv[1].x), mc = __uint_as_float(sv[0].z), md = __uint_as_float(sv[1].z);
      const float m0 = qsum(ma + wb * mb) * (1.f / 7), m1 = qsum(mc + wb * md) * (1.f / 7);
      const float v0 = qsum(__uint_as_float(sv[0].y) + 64.f * (ma - m0) * (ma - m0) + wb * (__uint_as_float(sv[1].y) + 64.f * (mb - m0) * (mb - m0)));
      const float v1 = qsum(__uint_as_float(sv[0].w) + 64.f * (mc - m1) * (mc - m1) + wb * (__uint_as_float(sv[1].w) + 64.f * (md - m1) * (md - m1)));
      const float e0 = v0 * (1.f / 448) + 1e-5f, e1 = v1 * (1.f / 448) + 1e-5f;
      rr0 = 1.f / e0; rr1 = 1.f / e1;
      auto fold = [&](float m, float sd) -> uint32_t {
        const float mh = blo(pack(-m, 0.f)), sh_ = blo(pack(sd, 0.f));
        return q == 0 ? pack(mh, -m - mh) : q == 1 ? pack(mh, sh_) : q == 2 ? pack(sd - sh_, 0.f) : 0u;
      };
      const uint32_t fa = fold(m0, sqrtf(e0)), fb = fold(m1, sqrtf(e1));
      if (L == 0) asm volatile("bar.sync 4, 288;" ::: "memory");
      wg_fence();
      wgmma_rs192(y, fa, fb, 0u, 0u, mkdesc(d16, OFF_CB + 0, 512, 0, 2), 1);
      wgmma_rs32(z, fa, fb, 0u, 0u, mkdesc(d16, OFF_CB + 3072, 512, 0, 2), 1);
      F1STAGE(5) F1STAGE(6)
      wg_wait<0>(); release(); regfence(y); regfence(z);
      MARK(14 + L * 19);
#pragma unroll
      for (int j = 0; j < 56; j++) {
        uint32_t r; asm("cvt.rn.relu.bf16x2.f32 %0, %1, %2;" : "=r"(r) : "f"(j < 48 ? y[j < 48 ? 2 * j + 1 : 0] : z[j < 48 ? 0 : 2 * j - 95]), "f"(j < 48 ? y[j < 48 ? 2 * j : 0] : z[j < 48 ? 0 : 2 * j - 96]));
        asm("mul.bf16x2 %0, %1, %1;" : "=r"(hf[j]) : "r"(r));
      }
    }
    MARK(15 + L * 19);
    {
      PTRS
      float ya[32], yb[32];
      uint4* pp = g_P + ((t * 8 + warp) * 8 + c) * 28 * 32 + ln_;
#define F2STORE(j, Y) { regfence(Y); _Pragma("unroll") for (int u = 0; u < 4; u++) \
      stll(pp + (4 * (j) + u) * 32, tg(pack(Y[8 * u] * rr0, Y[8 * u + 1] * rr0), tag), pack(Y[8 * u + 2] * rr1, Y[8 * u + 3] * rr1), \
           pack(Y[8 * u + 4] * rr0, Y[8 * u + 5] * rr0), pack(Y[8 * u + 6] * rr1, Y[8 * u + 7] * rr1)); }
#define F2PASS(j, Y, Z) { const uint32_t st = acquire(); wg_fence(); \
      _Pragma("unroll") for (int ks = 0; ks < 14; ks++) wgmma_rs64(Y, hf[4 * ks], hf[4 * ks + 1], hf[4 * ks + 2], hf[4 * ks + 3], mkdesc(st, ks * 2048, 1024, 1024, 1), ks); \
      wg_commit(); if (j > 0) { wg_wait<1>(); release(); F2STORE(j - 1, Z) } }
      const uint4* pr = g_P + ((t * 8 + c) * 8 * 28 + warp) * 32 + ln_;
      uint4 p[8], p2[8]; uint2 xa, xb, xc, xd; uint32_t ba, bb, bc, bd;
#define RISSUE(m, P, XA, XB, BA, BB) { ll_issue<0, 8>(P, pr + (m) * 256, 896); \
      { const uint4 v_ = ldll(fr + X1 + (m) * 256); XA = make_uint2(v_.x, v_.y); XB = make_uint2(v_.z, v_.w); } \
      const uint32_t* bp = (const uint32_t*)(b2 + 128 * (m) + 16 * warp) + (ln_ & 3); BA = __ldg(bp); BB = __ldg(bp + 4); }
#define REDU(m, P, XA, XB, BA, BB) { ll_check<0, 8, false>(P, pr + (m) * 256, 896, tag); \
      float e[8] = {blo(XA.x) + blo(BA), bhi(XA.x) + bhi(BA), blo(XA.y) + blo(BA), bhi(XA.y) + bhi(BA), blo(XB.x) + blo(BB), bhi(XB.x) + bhi(BB), blo(XB.y) + blo(BB), bhi(XB.y) + bhi(BB)}; \
      _Pragma("unroll") for (int i = 0; i < 8; i++) { e[0] += blo(P[i].x); e[1] += bhi(P[i].x); e[2] += blo(P[i].y); e[3] += bhi(P[i].y); \
        e[4] += blo(P[i].z); e[5] += bhi(P[i].z); e[6] += blo(P[i].w); e[7] += bhi(P[i].w); } \
      xw[m][0] = pack(e[0], e[1]); xw[m][1] = pack(e[2], e[3]); xw[m][2] = pack(e[4], e[5]); xw[m][3] = pack(e[6], e[7]); }
      F2PASS(0, ya, yb) F2PASS(1, yb, ya) F2PASS(2, ya, yb) F2PASS(3, yb, ya) F2PASS(4, ya, yb)
      RISSUE(0, p, xa, xb, ba, bb)
      F2PASS(5, yb, ya)
      REDU(0, p, xa, xb, ba, bb)
      F2PASS(6, ya, yb)
      RISSUE(1, p, xa, xb, ba, bb)
      wg_wait<0>(); release(); F2STORE(6, ya)
      MARK(16 + L * 19);
      RISSUE(2, p2, xc, xd, bc, bd)
      REDU(1, p, xa, xb, ba, bb)
      REDU(2, p2, xc, xd, bc, bd)
      if (wg == 0) RISSUE(3, p, xa, xb, ba, bb)
      MARK(17 + L * 19);
      if (wg == 0) REDU(3, p, xa, xb, ba, bb) else { xw[3][0] = xw[3][1] = xw[3][2] = xw[3][3] = 0; }
    }
    MARK(18 + L * 19);
  }
  {
    uint32_t* op = (uint32_t*)(out + XOFF(laneid()));
#pragma unroll
    for (int u = 0; u < 4; u++) if (u < 3 || wg == 0) { op[u * 64] = xw[u][0]; op[u * 64 + 1792] = xw[u][1]; op[u * 64 + 4] = xw[u][2]; op[u * 64 + 1796] = xw[u][3]; }
    if (warp == 7 && blockIdx.x < 112 && lane < 4) stll(g_CS + blockIdx.x * 4 + lane, 0, 0, 0, 0);
  }
  MARK(38);
  }
}

typedef CUresult (*EncFn)(CUtensorMap*, CUtensorMapDataType, cuuint32_t, void*, const cuuint64_t*, const cuuint64_t*, const cuuint32_t*, const cuuint32_t*,
                          CUtensorMapInterleave, CUtensorMapSwizzle, CUtensorMapL2promotion, CUtensorMapFloatOOBfill);

extern "C" void kernel_launch(void* const* d_in, const int* in_sizes, int n_in, void* d_out, int out_size) {
  static EncFn enc = nullptr;
  if (!enc) {
    void* fn = nullptr; cudaDriverEntryPointQueryResult qr;
    cudaGetDriverEntryPoint("cuTensorMapEncodeTiled", &fn, cudaEnableDefault, &qr);
    enc = (EncFn)fn;
    cudaFuncSetAttribute(fused_kernel, cudaFuncAttributeMaxDynamicSharedMemorySize, SMEM_BYTES);
  }
  CUtensorMap mQKV, mWO, mW1, mW1b, mW2, mW2b;
  const cuuint32_t es[3] = {1, 1, 1};
  auto enc2 = [&](CUtensorMap* m, void* p, cuuint64_t cols, cuuint64_t rows, cuuint32_t bc, cuuint32_t br) {
    const cuuint64_t dims[2] = {cols, rows}, str[1] = {cols * 2}; const cuuint32_t box[2] = {bc, br};
    enc(m, CU_TENSOR_MAP_DATA_TYPE_BFLOAT16, 2, p, dims, str, box, es, CU_TENSOR_MAP_INTERLEAVE_NONE,
        bc == 64 ? CU_TENSOR_MAP_SWIZZLE_128B : CU_TENSOR_MAP_SWIZZLE_64B, CU_TENSOR_MAP_L2_PROMOTION_L2_128B, CU_TENSOR_MAP_FLOAT_OOB_FILL_NONE);
  };
  enc2(&mQKV, d_in[1], 1344, 448, 64, 112); enc2(&mWO, d_in[3], 448, 448, 64, 112); enc2(&mW1b, d_in[5], 1792, 448, 32, 32);
  enc2(&mW2, d_in[7], 448, 1792, 64, 96); enc2(&mW2b, d_in[7], 448, 1792, 64, 16);
  {
    const cuuint64_t dims[3] = {64, 448, 28}, str[2] = {3584, 128}; const cuuint32_t box[3] = {64, 32, 3};
    enc(&mW1, CU_TENSOR_MAP_DATA_TYPE_BFLOAT16, 3, d_in[5], dims, str, box, es, CU_TENSOR_MAP_INTERLEAVE_NONE, CU_TENSOR_MAP_SWIZZLE_128B,
        CU_TENSOR_MAP_L2_PROMOTION_L2_128B, CU_TENSOR_MAP_FLOAT_OOB_FILL_NONE);
  }
  typedef const __nv_bfloat16* BP;
  fused_kernel<<<128, 384, SMEM_BYTES>>>(mQKV, mWO, mW1, mW1b, mW2, mW2b, (BP)d_in[0], (BP)d_in[2], (BP)d_in[3], (BP)d_in[5], (BP)d_in[6], (BP)d_in[7], (BP)d_in[8],
                                         (__nv_bfloat16*)d_out);
}
```

```cpp
#include <cuda_runtime.h>
#include <cuda_bf16.h>
#include <cuda.h>
#include <stdint.h>

constexpr int NST = 6, STAGE = 28672;
constexpr int OFF_PHIK = NST * STAGE;
constexpr int OFF_V = OFF_PHIK + 32768;
constexpr int OFF_WPHI = OFF_V + 16384;
constexpr int OFF_CB = OFF_WPHI + 7168;
constexpr int OFF_BAR = OFF_CB + 3584;
constexpr int SMEM_BYTES = OFF_BAR + 16 * NST + 8;
constexpr int FR = 16 * 8 * 28 * 32;
constexpr int SPIN = 1 << 18;
#define MC 0
#define MAPPING MC
#define MCS
#define MCA(n)
#define CLUSTER
#define PACE 2

__device__ uint4 g_F[4 * FR];
constexpr int XN = 0, XR = FR, OO = 2 * FR, X1 = 3 * FR;
__device__ uint4 g_P[8 * FR];
__device__ uint4 g_ST[16 * 8 * 8 * 8];
__device__ uint4 g_KVP[8 * 16 * 1024];
__device__ uint2 g_KVR[8 * 1024];
__device__ uint4 g_CS[448];
__device__ uint32_t g_H[16 * 8 * 8];
#define MARK(i)

__device__ __forceinline__ uint32_t s2u(const void* p) { return (uint32_t)__cvta_generic_to_shared(p); }
__device__ __forceinline__ void mbar_init(uint32_t b, uint32_t c) { asm volatile("mbarrier.init.shared::cta.b64 [%0], %1;" ::"r"(b), "r"(c)); }
__device__ __forceinline__ void mbar_expect(uint32_t b, uint32_t tx) { asm volatile("mbarrier.arrive.expect_tx.shared::cta.b64 _, [%0], %1;" ::"r"(b), "r"(tx) : "memory"); }
__device__ __forceinline__ void mbar_arrive_cl(uint32_t b, uint32_t rank) {
  asm volatile("{.reg .b32 r; mapa.shared::cluster.u32 r, %0, %1; mbarrier.arrive.shared::cluster.b64 _, [r];}" ::"r"(b), "r"(rank) : "memory");
}
__device__ __forceinline__ void mbar_wait(uint32_t b, uint32_t ph) {
  uint32_t ok = 0;
#pragma unroll 1
  for (int it = 0; it < SPIN && !ok; it++)
    asm volatile("{.reg .pred p; mbarrier.try_wait.parity.shared::cta.b64 p,[%1],%2; selp.u32 %0,1,0,p;}" : "=r"(ok) : "r"(b), "r"(ph) : "memory");
}
__device__ __forceinline__ void tma2d(uint32_t dst, const CUtensorMap* m, int c0, int c1, uint32_t bar) {
  asm volatile("cp.async.bulk.tensor.2d.shared::cluster.global.mbarrier::complete_tx::bytes" MCS " [%0], [%1, {%3, %4}], [%2]" MCA(5) ";"
               ::"r"(dst), "l"(m), "r"(bar), "r"(c0), "r"(c1), "h"((uint16_t)3) : "memory");
}
__device__ __forceinline__ void tma3d(uint32_t dst, const CUtensorMap* m, int c0, int c1, int c2, uint32_t bar) {
  asm volatile("cp.async.bulk.tensor.3d.shared::cluster.global.mbarrier::complete_tx::bytes" MCS " [%0], [%1, {%3, %4, %5}], [%2]" MCA(6) ";"
               ::"r"(dst), "l"(m), "r"(bar), "r"(c0), "r"(c1), "r"(c2), "h"((uint16_t)3) : "memory");
}
__device__ __forceinline__ void l2pf(const void* p, uint32_t bytes) { asm volatile("cp.async.bulk.prefetch.L2.global [%0], %1;" ::"l"(p), "r"(bytes) : "memory"); }
__device__ __forceinline__ void wg_fence() { asm volatile("wgmma.fence.sync.aligned;" ::: "memory"); }
__device__ __forceinline__ void wg_commit() { asm volatile("wgmma.commit_group.sync.aligned;" ::: "memory"); }
template <int N> __device__ __forceinline__ void wg_wait() { asm volatile("wgmma.wait_group.sync.aligned %0;" ::"n"(N) : "memory"); }
template <int N> __device__ __forceinline__ void regfence(float (&d)[N]) {
#pragma unroll
  for (int i = 0; i < N; i++) asm volatile("" : "+f"(d[i])::"memory");
}
__device__ __forceinline__ void bar_cons() { asm volatile("bar.sync 1, 256;" ::: "memory"); }
__device__ __forceinline__ void fence_async() { asm volatile("fence.proxy.async.shared::cta;" ::: "memory"); }
struct Desc { uint32_t lo, hi; };
__device__ __forceinline__ Desc mkdesc(uint32_t base16, uint32_t off, uint32_t lbo, uint32_t sbo, uint32_t swz) {
  return Desc{base16 + ((off >> 4) | ((lbo >> 4) << 16)), (sbo >> 4) | (swz << 30)};
}
__device__ __forceinline__ uint4 ldll(const uint4* p) {
  uint4 v; asm volatile("ld.relaxed.gpu.global.v4.u32 {%0,%1,%2,%3}, [%4];" : "=r"(v.x), "=r"(v.y), "=r"(v.z), "=r"(v.w) : "l"(p) : "memory"); return v;
}
__device__ __forceinline__ uint2 ldll2(const uint2* p) {
  uint2 v; asm volatile("ld.relaxed.gpu.global.v2.u32 {%0,%1}, [%2];" : "=r"(v.x), "=r"(v.y) : "l"(p) : "memory"); return v;
}
__device__ __forceinline__ void stll(uint4* p, uint32_t x, uint32_t y, uint32_t z, uint32_t w) {
  asm volatile("st.relaxed.gpu.global.v4.u32 [%0], {%1,%2,%3,%4};" ::"l"(p), "r"(x), "r"(y), "r"(z), "r"(w) : "memory");
}
__device__ __forceinline__ void stll2(void* p, uint32_t x, uint32_t y) {
  asm volatile("st.relaxed.gpu.global.v2.u32 [%0], {%1,%2};" ::"l"(p), "r"(x), "r"(y) : "memory");
}
__device__ __forceinline__ int laneid() { int l; asm volatile("mov.u32 %0, %%laneid;" : "=r"(l)); return l; }
__device__ __forceinline__ uint32_t tg(uint32_t w, uint32_t tag) { return (w & ~1u) | tag; }
__device__ __forceinline__ uint32_t pack(float lo, float hi) {
  uint32_t r; asm("cvt.rn.bf16x2.f32 %0, %1, %2;" : "=r"(r) : "f"(hi), "f"(lo)); return r;
}
__device__ __forceinline__ float blo(uint32_t w) { return __uint_as_float(w << 16); }
__device__ __forceinline__ float bhi(uint32_t w) { return __uint_as_float(w & 0xffff0000u); }
__device__ __forceinline__ float ex2(float x) { float r; asm("ex2.approx.ftz.f32 %0, %1;" : "=f"(r) : "f"(x)); return r; }
__device__ __forceinline__ float rcp(float x) { float r; asm("rcp.approx.ftz.f32 %0, %1;" : "=f"(r) : "f"(x)); return r; }
__device__ __forceinline__ float qsum(float v) { v += __shfl_xor_sync(~0u, v, 1); v += __shfl_xor_sync(~0u, v, 2); return v; }
__device__ __forceinline__ void sts32(uint32_t a, uint32_t v) { asm volatile("st.shared.u32 [%0], %1;" ::"r"(a), "r"(v) : "memory"); }
__device__ __forceinline__ void sts16(uint32_t a, uint32_t v) { asm volatile("st.shared.u16 [%0], %1;" ::"r"(a), "h"((uint16_t)v) : "memory"); }
__device__ __forceinline__ void sts128(uint32_t a, uint32_t x, uint32_t y, uint32_t z, uint32_t w) {
  asm volatile("st.shared.v4.u32 [%0], {%1,%2,%3,%4};" ::"r"(a), "r"(x), "r"(y), "r"(z), "r"(w) : "memory");
}
__device__ __forceinline__ uint32_t sw128(int row, int col) { return row * 128 + ((((col >> 3) ^ row) & 7) << 4) + (col & 7) * 2; }

__device__ __forceinline__ void wgmma_rs56(float (&d)[28], const uint32_t a0, const uint32_t a1, const uint32_t a2, const uint32_t a3, Desc db, int sd) {
  asm volatile("{.reg .pred p; .reg .b64 da, db; setp.ne.b32 p, %33, 0; mov.b64 db, {%32, %34};\n wgmma.mma_async.sync.aligned.m64n56k16.f32.bf16.bf16 {%0,%1,%2,%3,%4,%5,%6,%7,%8,%9,%10,%11,%12,%13,%14,%15,%16,%17,%18,%19,%20,%21,%22,%23,%24,%25,%26,%27}, {%28,%29,%30,%31}, db, p, 1, 1, 1;}"
   : "+f"(d[0]),"+f"(d[1]),"+f"(d[2]),"+f"(d[3]),"+f"(d[4]),"+f"(d[5]),"+f"(d[6]),"+f"(d[7]),"+f"(d[8]),"+f"(d[9]),"+f"(d[10]),"+f"(d[11]),"+f"(d[12]),"+f"(d[13]),"+f"(d[14]),"+f"(d[15]),"+f"(d[16]),"+f"(d[17]),"+f"(d[18]),"+f"(d[19]),"+f"(d[20]),"+f"(d[21]),"+f"(d[22]),"+f"(d[23]),"+f"(d[24]),"+f"(d[25]),"+f"(d[26]),"+f"(d[27])
   : "r"(a0),"r"(a1),"r"(a2),"r"(a3),"r"(db.lo),"r"(sd),"r"(db.hi));
}
__device__ __forceinline__ void wgmma_rs64(float (&d)[32], const uint32_t a0, const uint32_t a1, const uint32_t a2, const uint32_t a3, Desc db, int sd) {
  asm volatile("{.reg .pred p; .reg .b64 da, db; setp.ne.b32 p, %37, 0; mov.b64 db, {%36, %38};\n wgmma.mma_async.sync.aligned.m64n64k16.f32.bf16.bf16 {%0,%1,%2,%3,%4,%5,%6,%7,%8,%9,%10,%11,%12,%13,%14,%15,%16,%17,%18,%19,%20,%21,%22,%23,%24,%25,%26,%27,%28,%29,%30,%31}, {%32,%33,%34,%35}, db, p, 1, 1, 1;}"
   : "+f"(d[0]),"+f"(d[1]),"+f"(d[2]),"+f"(d[3]),"+f"(d[4]),"+f"(d[5]),"+f"(d[6]),"+f"(d[7]),"+f"(d[8]),"+f"(d[9]),"+f"(d[10]),"+f"(d[11]),"+f"(d[12]),"+f"(d[13]),"+f"(d[14]),"+f"(d[15]),"+f"(d[16]),"+f"(d[17]),"+f"(d[18]),"+f"(d[19]),"+f"(d[20]),"+f"(d[21]),"+f"(d[22]),"+f"(d[23]),"+f"(d[24]),"+f"(d[25]),"+f"(d[26]),"+f"(d[27]),"+f"(d[28]),"+f"(d[29]),"+f"(d[30]),"+f"(d[31])
   : "r"(a0),"r"(a1),"r"(a2),"r"(a3),"r"(db.lo),"r"(sd),"r"(db.hi));
}
__device__ __forceinline__ void wgmma_rs192(float (&d)[96], const uint32_t a0, const uint32_t a1, const uint32_t a2, const uint32_t a3, Desc db, int sd) {
  asm volatile("{.reg .pred p; .reg .b64 db; setp.ne.b32 p, %101, 0; mov.b64 db, {%100, %102};\n wgmma.mma_async.sync.aligned.m64n192k16.f32.bf16.bf16 {%0,%1,%2,%3,%4,%5,%6,%7,%8,%9,%10,%11,%12,%13,%14,%15,%16,%17,%18,%19,%20,%21,%22,%23,%24,%25,%26,%27,%28,%29,%30,%31,%32,%33,%34,%35,%36,%37,%38,%39,%40,%41,%42,%43,%44,%45,%46,%47,%48,%49,%50,%51,%52,%53,%54,%55,%56,%57,%58,%59,%60,%61,%62,%63,%64,%65,%66,%67,%68,%69,%70,%71,%72,%73,%74,%75,%76,%77,%78,%79,%80,%81,%82,%83,%84,%85,%86,%87,%88,%89,%90,%91,%92,%93,%94,%95}, {%96,%97,%98,%99}, db, p, 1, 1, 1;}"
   : "+f"(d[0]),"+f"(d[1]),"+f"(d[2]),"+f"(d[3]),"+f"(d[4]),"+f"(d[5]),"+f"(d[6]),"+f"(d[7]),"+f"(d[8]),"+f"(d[9]),"+f"(d[10]),"+f"(d[11]),"+f"(d[12]),"+f"(d[13]),"+f"(d[14]),"+f"(d[15]),"+f"(d[16]),"+f"(d[17]),"+f"(d[18]),"+f"(d[19]),"+f"(d[20]),"+f"(d[21]),"+f"(d[22]),"+f"(d[23]),"+f"(d[24]),"+f"(d[25]),"+f"(d[26]),"+f"(d[27]),"+f"(d[28]),"+f"(d[29]),"+f"(d[30]),"+f"(d[31]),"+f"(d[32]),"+f"(d[33]),"+f"(d[34]),"+f"(d[35]),"+f"(d[36]),"+f"(d[37]),"+f"(d[38]),"+f"(d[39]),"+f"(d[40]),"+f"(d[41]),"+f"(d[42]),"+f"(d[43]),"+f"(d[44]),"+f"(d[45]),"+f"(d[46]),"+f"(d[47]),"+f"(d[48]),"+f"(d[49]),"+f"(d[50]),"+f"(d[51]),"+f"(d[52]),"+f"(d[53]),"+f"(d[54]),"+f"(d[55]),"+f"(d[56]),"+f"(d[57]),"+f"(d[58]),"+f"(d[59]),"+f"(d[60]),"+f"(d[61]),"+f"(d[62]),"+f"(d[63]),"+f"(d[64]),"+f"(d[65]),"+f"(d[66]),"+f"(d[67]),"+f"(d[68]),"+f"(d[69]),"+f"(d[70]),"+f"(d[71]),"+f"(d[72]),"+f"(d[73]),"+f"(d[74]),"+f"(d[75]),"+f"(d[76]),"+f"(d[77]),"+f"(d[78]),"+f"(d[79]),"+f"(d[80]),"+f"(d[81]),"+f"(d[82]),"+f"(d[83]),"+f"(d[84]),"+f"(d[85]),"+f"(d[86]),"+f"(d[87]),"+f"(d[88]),"+f"(d[89]),"+f"(d[90]),"+f"(d[91]),"+f"(d[92]),"+f"(d[93]),"+f"(d[94]),"+f"(d[95])
   : "r"(a0),"r"(a1),"r"(a2),"r"(a3),"r"(db.lo),"r"(sd),"r"(db.hi));
}
__device__ __forceinline__ void wgmma_rs32(float (&d)[16], const uint32_t a0, const uint32_t a1, const uint32_t a2, const uint32_t a3, Desc db, int sd) {
  asm volatile("{.reg .pred p; .reg .b64 db; setp.ne.b32 p, %21, 0; mov.b64 db, {%20, %22};\n wgmma.mma_async.sync.aligned.m64n32k16.f32.bf16.bf16 {%0,%1,%2,%3,%4,%5,%6,%7,%8,%9,%10,%11,%12,%13,%14,%15}, {%16,%17,%18,%19}, db, p, 1, 1, 1;}"
   : "+f"(d[0]),"+f"(d[1]),"+f"(d[2]),"+f"(d[3]),"+f"(d[4]),"+f"(d[5]),"+f"(d[6]),"+f"(d[7]),"+f"(d[8]),"+f"(d[9]),"+f"(d[10]),"+f"(d[11]),"+f"(d[12]),"+f"(d[13]),"+f"(d[14]),"+f"(d[15])
   : "r"(a0),"r"(a1),"r"(a2),"r"(a3),"r"(db.lo),"r"(sd),"r"(db.hi));
}
__device__ __forceinline__ void wgmma_ss32(float (&d)[16], Desc da, Desc db, int sd) {
  asm volatile("{.reg .pred p; .reg .b64 da, db; setp.ne.b32 p, %18, 0; mov.b64 da, {%16, %19}; mov.b64 db, {%17, %19};\n wgmma.mma_async.sync.aligned.m64n32k16.f32.bf16.bf16 {%0,%1,%2,%3,%4,%5,%6,%7,%8,%9,%10,%11,%12,%13,%14,%15}, da, db, p, 1, 1, 1, 1;}"
   : "+f"(d[0]),"+f"(d[1]),"+f"(d[2]),"+f"(d[3]),"+f"(d[4]),"+f"(d[5]),"+f"(d[6]),"+f"(d[7]),"+f"(d[8]),"+f"(d[9]),"+f"(d[10]),"+f"(d[11]),"+f"(d[12]),"+f"(d[13]),"+f"(d[14]),"+f"(d[15])
   : "r"(da.lo),"r"(db.lo),"r"(sd),"r"(db.hi));
}

__device__ __forceinline__ uint4 ldsm4(uint32_t a) {
  uint4 v; asm volatile("ldmatrix.sync.aligned.m8n8.x4.shared.b16 {%0,%1,%2,%3}, [%4];" : "=r"(v.x), "=r"(v.y), "=r"(v.z), "=r"(v.w) : "r"(a) : "memory"); return v;
}
__device__ __forceinline__ void mma16816(float (&d)[4], const uint4& a, uint32_t b0, uint32_t b1) {
  asm("mma.sync.aligned.m16n8k16.row.col.f32.bf16.bf16.f32 {%0,%1,%2,%3}, {%4,%5,%6,%7}, {%8,%9}, {%0,%1,%2,%3};"
      : "+f"(d[0]), "+f"(d[1]), "+f"(d[2]), "+f"(d[3]) : "r"(a.x), "r"(a.y), "r"(a.z), "r"(a.w), "r"(b0), "r"(b1));
}
__device__ __forceinline__ uint32_t bsub(uint32_t a, uint32_t b) { uint32_t r; asm("sub.bf16x2 %0, %1, %2;" : "=r"(r) : "r"(a), "r"(b)); return r; }
__device__ __forceinline__ uint32_t hint_ld(const uint32_t* p) { uint32_t v; asm volatile("ld.relaxed.gpu.global.u32 %0, [%1];" : "=r"(v) : "l"(p) : "memory"); return v; }
template <int S, int N, bool SPL = false, int T> __device__ __forceinline__ void ll_issue(uint4 (&v)[T], const uint4* p, int stride, const uint2* p2 = nullptr) {
#pragma unroll
  for (int i = S; i < S + N; i++) {
    if (SPL && i % 7 == 3) { const uint2 lo = ldll2(p2 + i * 64), hi = ldll2(p2 + i * 64 + 32); v[i] = make_uint4(lo.x, lo.y, hi.x, hi.y); }
    else v[i] = ldll(p + i * stride);
  }
}
template <int S, int N, bool SPL, int T> __device__ __forceinline__ void ll_check(uint4 (&v)[T], const uint4* p, int stride, uint32_t tag, const uint2* p2 = nullptr) {
#pragma unroll 1
  for (int it = 0; it < SPIN; it++) {
    uint32_t bad = 0;
#pragma unroll
    for (int i = S; i < S + N; i++) bad |= (v[i].x ^ tag) | ((SPL && i % 7 == 3) ? (v[i].z ^ tag) : 0u);
    if (!__any_sync(~0u, bad & 1)) break;
    ll_issue<S, N, SPL>(v, p, stride, p2);
  }
}
__device__ __forceinline__ void hint_post(uint32_t* p, uint32_t v, int lane) {
  if (lane == 0) asm volatile("st.relaxed.gpu.global.u32 [%0], %1;" ::"l"(p), "r"(v) : "memory");
}
__device__ __forceinline__ void hint_wait(const uint32_t* p, uint32_t s, uint32_t v = 0xffffu) {
#pragma unroll 1
  for (int it = 0; it < SPIN; it++) {
    if (__all_sync(~0u, v - s < 10u)) break;
    v = hint_ld(p);
  }
}
__device__ __forceinline__ void slice_store(uint4* pf, uint2* ph, const uint32_t (&w)[14], bool odd) {
#pragma unroll
  for (int u = 0; u < 3; u++)
    stll(pf + u * 32, odd ? w[4 * u + 2] : w[4 * u], odd ? w[4 * u + 3] : w[4 * u + 1], odd ? w[4 * u + 4] : w[4 * u + 2], odd ? w[4 * u + 5] : w[4 * u + 3]);
  stll2(ph, odd ? w[0] : w[12], odd ? w[1] : w[13]);
}
template <class F, class M> __device__ __forceinline__ void hedgehog(const float (&d)[28], F sink, M mid) {
  const float L2E = 1.4426950408889634f;
#define HX(G, p) ((p) < 6 ? d[((G) & 1) * 16 + ((p) >> 1) * 4 + ((p) & 1) + ((G) & 2)] : d[12 + (G)])
  float mx[4], mn[4], sp[4], sn[4], ep[4][7], en[4][7];
#pragma unroll
  for (int G = 0; G < 4; G++) {
    mx[G] = mn[G] = HX(G, 0);
#pragma unroll
    for (int p = 1; p < 7; p++) { mx[G] = fmaxf(mx[G], HX(G, p)); mn[G] = fminf(mn[G], HX(G, p)); }
  }
#pragma unroll
  for (int o = 1; o < 4; o <<= 1)
#pragma unroll
    for (int G = 0; G < 4; G++) { mx[G] = fmaxf(mx[G], __shfl_xor_sync(~0u, mx[G], o)); mn[G] = fminf(mn[G], __shfl_xor_sync(~0u, mn[G], o)); }
#pragma unroll
  for (int G = 0; G < 4; G++) {
    const float a = -mx[G] * L2E, b = mn[G] * L2E;
#pragma unroll
    for (int p = 0; p < 7; p++) { ep[G][p] = ex2(fmaf(HX(G, p), L2E, a)); en[G][p] = ex2(fmaf(HX(G, p), -L2E, b)); }
    sp[G] = ((ep[G][0] + ep[G][1]) + (ep[G][2] + ep[G][3])) + ((ep[G][4] + ep[G][5]) + ep[G][6]);
    sn[G] = ((en[G][0] + en[G][1]) + (en[G][2] + en[G][3])) + ((en[G][4] + en[G][5]) + en[G][6]);
    if (G == 1) mid();
  }
#pragma unroll
  for (int o = 1; o < 4; o <<= 1)
#pragma unroll
    for (int G = 0; G < 4; G++) { sp[G] += __shfl_xor_sync(~0u, sp[G], o); sn[G] += __shfl_xor_sync(~0u, sn[G], o); }
#pragma unroll
  for (int G = 0; G < 4; G++) {
    const float a = rcp(sp[G]), b = rcp(sn[G]);
#pragma unroll
    for (int p = 0; p < 7; p++) sink(G >> 1, G & 1, p, pack(ep[G][p] * a, en[G][p] * b));
  }
}
__device__ __forceinline__ void phi_gemm(const float (&x)[28], float (&y)[28], uint32_t wphi, float r0, float r1) {
  uint32_t f[14];
#pragma unroll
  for (int j = 0; j < 14; j++) f[j] = pack(x[2 * j] * (j & 1 ? r1 : r0), x[2 * j + 1] * (j & 1 ? r1 : r0));
  wg_fence();
#pragma unroll
  for (int ks = 0; ks < 3; ks++) wgmma_rs56(y, f[4 * ks], f[4 * ks + 1], f[4 * ks + 2], f[4 * ks + 3], mkdesc(wphi, ks * 2048, 1024, 1024, 1), ks);
  wgmma_rs56(y, f[12], f[13], 0u, 0u, mkdesc(wphi, 3 * 2048, 1024, 1024, 1), 1);
  wg_commit();
}
__device__ __forceinline__ void ln_publish(uint32_t (&xw)[4][4], float* sLN, int warp, int lane, uint4* fb, uint32_t tag) {
  const int g = lane >> 2; const bool full = warp < 4;
  float s0 = 0.f, s1 = 0.f;
#pragma unroll
  for (int u = 0; u < 4; u++) {
    s0 += (blo(xw[u][0]) + bhi(xw[u][0])) + (blo(xw[u][2]) + bhi(xw[u][2]));
    s1 += (blo(xw[u][1]) + bhi(xw[u][1])) + (blo(xw[u][3]) + bhi(xw[u][3]));
  }
  const float rc = full ? 1.f / 64 : 1.f / 48;
  s0 = qsum(s0); s1 = qsum(s1);
  const float a0 = s0 * rc, a1 = s1 * rc;
  float v0 = 0.f, v1 = 0.f;
#pragma unroll
  for (int u = 0; u < 4; u++)
    if (u < 3 || full) {
#pragma unroll
      for (int k = 0; k < 4; k += 2) {
        float a = blo(xw[u][k]) - a0, b = bhi(xw[u][k]) - a0, c2 = blo(xw[u][k + 1]) - a1, d2 = bhi(xw[u][k + 1]) - a1;
        v0 += a * a + b * b; v1 += c2 * c2 + d2 * d2;
      }
    }
  v0 = qsum(v0); v1 = qsum(v1);
  if ((lane & 3) == 0) *(float4*)(sLN + (g * 8 + warp) * 4) = make_float4(s0, v0, s1, v1);
  bar_cons();
  const float4 ea = *(const float4*)(sLN + (g * 8 + (lane & 3)) * 4), eb = *(const float4*)(sLN + (g * 8 + 4 + (lane & 3)) * 4);
  const float m0 = qsum(ea.x + eb.x) * (1.f / 448), m1 = qsum(ea.z + eb.z) * (1.f / 448);
  const float d0 = ea.x * (1.f / 64) - m0, d1 = eb.x * (1.f / 48) - m0, d2 = ea.z * (1.f / 64) - m1, d3 = eb.z * (1.f / 48) - m1;
  v0 = qsum(ea.y + eb.y + 64.f * d0 * d0 + 48.f * d1 * d1); v1 = qsum(ea.w + eb.w + 64.f * d2 * d2 + 48.f * d3 * d3);
  const float r0 = rsqrtf(v0 * (1.f / 448) + 1e-5f), r1 = rsqrtf(v1 * (1.f / 448) + 1e-5f), n0 = -m0 * r0, n1 = -m1 * r1;
#pragma unroll
  for (int u = 0; u < 4; u++)
    if (u < 3 || full)
      stll(fb + XN + u * 256, tg(pack(fmaf(blo(xw[u][0]), r0, n0), fmaf(bhi(xw[u][0]), r0, n0)), tag), pack(fmaf(blo(xw[u][1]), r1, n1), fmaf(bhi(xw[u][1]), r1, n1)),
           pack(fmaf(blo(xw[u][2]), r0, n0), fmaf(bhi(xw[u][2]), r0, n0)), pack(fmaf(blo(xw[u][3]), r1, n1), fmaf(bhi(xw[u][3]), r1, n1)));
}

__global__ void CLUSTER __launch_bounds__(384, 1)
fused_kernel(const __grid_constant__ CUtensorMap mQKV, const __grid_constant__ CUtensorMap mWO, const __grid_constant__ CUtensorMap mW1,
             const __grid_constant__ CUtensorMap mW1b, const __grid_constant__ CUtensorMap mW2, const __grid_constant__ CUtensorMap mW2b,
             const __grid_constant__ CUtensorMap mX, const __nv_bfloat16* __restrict__ wphi,
             const __nv_bfloat16* __restrict__ wo, const __nv_bfloat16* __restrict__ w1, const __nv_bfloat16* __restrict__ b1,
             const __nv_bfloat16* __restrict__ w2, const __nv_bfloat16* __restrict__ b2, __nv_bfloat16* __restrict__ out) {
  extern __shared__ __align__(1024) uint8_t sm[];
  const uint32_t sb = s2u(sm);
  const int tid = threadIdx.x, warp = __shfl_sync(~0u, tid >> 5, 0), lane = tid & 31,
            t = MAPPING ? (blockIdx.x >> 4) * 2 + (blockIdx.x & 1) : blockIdx.x >> 3, c = MAPPING ? (blockIdx.x >> 1) & 7 : blockIdx.x & 7;
  const uint32_t bfull = sb + OFF_BAR, bempty = bfull + 8 * NST;

#define XOFF(l) ((t * 128 + c * 16 + ((l) >> 2)) * 448 + warp * 16 + 2 * ((l) & 3))
  if (warp < 8) MARK(0);
  if (tid == 256) {
    for (int s = 0; s < NST; s++) { mbar_init(bfull + 8 * s, 1); mbar_init(bempty + 8 * s, MC ? 16 : 8); }
    mbar_init(bempty + 8 * NST, 1);
    asm volatile("fence.mbarrier_init.release.cluster;" ::: "memory");
    fence_async();
    mbar_expect(bempty + 8 * NST, 114688);
    for (int i = 0; i < 7; i++)
      asm volatile("cp.async.bulk.tensor.2d.shared::cluster.global.mbarrier::complete_tx::bytes [%0], [%1, {%3, %4}], [%2];"
                   ::"r"(sb + 2 * STAGE + i * 16384), "l"(&mX), "r"(bempty + 8 * NST), "r"(64 * i), "r"(128 * t) : "memory");
  }
  asm volatile("barrier.cluster.arrive.release.aligned; barrier.cluster.wait.acquire.aligned;" ::: "memory");
  if (warp >= 8) {
    asm volatile("setmaxnreg.dec.sync.aligned.u32 24;");
    auto issue = [&](int i, int s) {
      const uint32_t dst = sb + s * STAGE, bar = bfull + 8 * s;
      mbar_expect(bar, STAGE);
#pragma unroll 1
      for (int rk = MC ? (blockIdx.x & 1) : 0; rk < (MC ? (blockIdx.x & 1) + 1 : 2); rk++)
      if (i < 4) tma2d(dst + rk * 14336, &mQKV, 448 + 448 * rk + 56 * c, 112 * i, bar);
      else if (i < 8) tma2d(dst + rk * 14336, i < 6 ? &mQKV : &mWO, (i < 6 ? 56 : 64) * c, 224 * (i & 1) + 112 * rk, bar);
      else if (i < 15) { const int k0 = 64 * ((i - 8 + c) % 7) + 32 * rk;
        tma3d(dst + rk * 12288, &mW1, 0, k0, 3 * c, bar); tma2d(dst + 24576 + rk * 2048, &mW1b, 1536 + 32 * c, k0, bar); }
      else { tma2d(dst + rk * 12288, &mW2, 64 * (i - 15), 192 * c + 96 * rk, bar); tma2d(dst + 24576 + rk * 2048, &mW2b, 64 * (i - 15), 1536 + 32 * c + 16 * rk, bar); }
    };
    if (warp == 8) {
      int s = 0; uint32_t ph = 1;
      for (int n = 0; n < 44; n++) {
        if (n == PACE) asm volatile("bar.sync 2, 288;" ::: "memory");
        mbar_wait(bempty + 8 * s, ph);
        if (lane == 0) issue(n >= 22 ? n - 22 : n, s);
        __syncwarp();
        if (++s == NST) { s = 0; ph ^= 1; }
      }
    } else if (warp == 9) {
      mbar_wait(bfull + 8 * 3, 0);
      if (lane == 0) {
        l2pf((const uint8_t*)wo + blockIdx.x * 3136, 3136);
        l2pf((const uint8_t*)w1 + blockIdx.x * 12544, 12544);
        l2pf((const uint8_t*)w2 + blockIdx.x * 12544, 12544);
      }
      if (blockIdx.x < 112) {
        const uint2* wp = (const uint2*)(w1 + (size_t)(lane >> 2) * 1792 + blockIdx.x * 16 + (lane & 3) * 4);
        float s0 = 0.f, s1 = 0.f, s2 = 0.f, s3 = 0.f;
#pragma unroll 8
        for (int i = 0; i < 56; i++) { const uint2 v = __ldg(wp + i * 8 * 448); s0 += blo(v.x); s1 += bhi(v.x); s2 += blo(v.y); s3 += bhi(v.y); }
#pragma unroll 1
        for (int o = 4; o < 32; o <<= 1) { s0 += __shfl_xor_sync(~0u, s0, o); s1 += __shfl_xor_sync(~0u, s1, o); s2 += __shfl_xor_sync(~0u, s2, o); s3 += __shfl_xor_sync(~0u, s3, o); }
        if (lane < 4) stll(g_CS + blockIdx.x * 4 + lane, tg(__float_as_uint(s0), 1), __float_as_uint(s1), __float_as_uint(s2), __float_as_uint(s3));
      }
      asm volatile("bar.sync 6, 96;" ::: "memory");
#pragma unroll 1
      for (int i = 0; i < 2; i++) {
        const int e = lane < 28 ? lane + 28 * i : 0;
        uint4 cv[1];
        const int e4 = e < 48 ? 48 * c + e : 336 + 8 * c + e;
        ll_issue<0, 1>(cv, g_CS + e4, 0); ll_check<0, 1, false>(cv, g_CS + e4, 0, 1u);
        const uint2 bb = __ldg((const uint2*)b1 + e4);
        const uint32_t h0 = pack(__uint_as_float(cv[0].x), __uint_as_float(cv[0].y)), h1 = pack(__uint_as_float(cv[0].z), __uint_as_float(cv[0].w));
        const uint32_t l0 = pack(__uint_as_float(cv[0].x) - blo(h0), __uint_as_float(cv[0].y) - bhi(h0)), l1 = pack(__uint_as_float(cv[0].z) - blo(h1), __uint_as_float(cv[0].w) - bhi(h1));
#pragma unroll 1
        for (int r = 0; r < 8; r++) {
          const uint32_t ad = sb + OFF_CB + (e >> 3) * 512 + r * 64 + ((((e >> 1) ^ (r >> 1)) & 3) << 4) + (e & 1) * 8;
          sts32(ad, r < 2 ? h0 : r == 2 ? l0 : r < 5 ? bb.x : 0u); sts32(ad + 4, r < 2 ? h1 : r == 2 ? l1 : r < 5 ? bb.y : 0u);
        }
      }
      fence_async();
      asm volatile("bar.arrive 4, 288;" ::: "memory");
    } else if (warp >= 10) {
      const int h = warp - 10;
      uint32_t wv[13];
#pragma unroll
      for (int i = 0; i < 13; i++) { const int e = lane + 32 * i; wv[i] = e < 392 ? __ldg((const uint32_t*)wphi + (2 * c + h) * 392 + e) : 0u; }
#pragma unroll 1
      for (int i = 0; i < 8; i++) sts128(sb + OFF_WPHI + (h * 256 + i * 32 + lane) * 16, 0, 0, 0, 0);
      asm volatile("bar.arrive 6, 96;" ::: "memory");
#pragma unroll 1
      for (int i = 0; i < 4; i++) sts128(sb + OFF_PHIK + sw128(h * 128 + i * 32 + lane, 56), 0, 0, 0, 0);
      asm volatile("bar.sync 5, 64;" ::: "memory");
#pragma unroll
      for (int i = 0; i < 13; i++) {
        const int e = lane + 32 * i, d = e / 14, f2 = 2 * (e - 14 * d), k = 28 * h + d;
        if (e < 392) {
          if (f2 < 24) sts32(sb + OFF_WPHI + sw128(k, 32 * h + f2), wv[i]);
          else { sts16(sb + OFF_WPHI + sw128(k, 2 * f2 - 24 + h), wv[i]); sts16(sb + OFF_WPHI + sw128(k, 2 * f2 - 22 + h), wv[i] >> 16); }
        }
      }
      fence_async();
      asm volatile("bar.arrive 3, 320;" ::: "memory");
    }
  } else {
  asm volatile("setmaxnreg.inc.sync.aligned.u32 240;");

  const int wg = warp >> 2, g = lane >> 2, q = lane & 3;
  const int row0 = warp * 16 + g;
#define PTRS const int ln_ = laneid(); \
  uint4* const fm = g_F + ((t * 8 + warp) * 28) * 32 + ln_;            \
  uint4* const fr = g_F + ((t * 8 + c) * 28 + warp) * 32 + ln_;        \
  uint4* const sf = fm + (7 * (c >> 1) + 4 * (c & 1)) * 32;             \
  uint2* const f2 = (uint2*)(fm - ln_) + ln_;                           \
  uint2* const sh = f2 + (7 * (c >> 1) + 3) * 64 + 32 * (c & 1);        \
  uint32_t* const hme = g_H + (t * 8 + warp) * 8 + c; \
  const uint32_t* const hrow = g_H + (t * 8 + warp) * 8 + (ln_ & 7); \
  (void)fm; (void)fr; (void)sf; (void)f2; (void)sh; (void)hme; (void)hrow;
  float* sLN = (float*)(sm + OFF_V);
  const uint32_t sPK = sb + OFF_PHIK, sV = sb + OFF_V, d16 = (sb & 0x3FFFF) >> 4;
    uint32_t xw[4][4];
#pragma unroll
  for (int i = 0; i < 16; i++) xw[i >> 2][i & 3] = 0;
  int cs = 0, rs = 0; uint32_t cph = 0;
  auto acquire = [&]() -> uint32_t { mbar_wait(bfull + 8 * cs, cph); const uint32_t a = d16 + cs * (STAGE >> 4); if (++cs == NST) { cs = 0; cph ^= 1; } return a; };
  int nrel = 44 - NST;
  auto release = [&]() { if (lane < 1 + MC && nrel > 0) mbar_arrive_cl(bempty + 8 * rs, lane); nrel--; if (++rs == NST) rs = 0; };

#pragma unroll 1
  for (int L = 0; L < 2; L++) {
    const uint32_t tag = 1 - L;
    uint32_t phq[2][2][7];
    const uint32_t hs = 10 * L;
    {
      PTRS
      uint4 a[28];
      const uint4* pa = fm + XN;
      const uint32_t xtag = 1;
      float r0 = 1.f, r1 = 1.f;
      if (L == 0) {
        mbar_wait(bempty + 8 * NST, 0);
        MARK(1);
        const int row = warp * 16 + (ln_ & 15);
        const uint32_t xb = sb + 2 * STAGE + row * 128;
        float cs_[4] = {0.f, 0.f, 0.f, 0.f}, c0[4] = {0.f, 0.f, 0.f, 0.f}, c1[4] = {0.f, 0.f, 0.f, 0.f};
#pragma unroll
        for (int ks = 0; ks < 28; ks++) { a[ks] = ldsm4(xb + (ks >> 2) * 16384 + (((2 * (ks & 3) + (ln_ >> 4)) ^ (row & 7)) << 4)); mma16816(cs_, a[ks], 0x3F803F80u, 0x3F803F80u); }
        if (c < 7) {
#pragma unroll
          for (int u = 0; u < 4; u++) { const uint4 v = ldsm4(xb + c * 16384 + (((2 * u + (ln_ >> 4)) ^ (row & 7)) << 4)); stll(fm + XR + 128 * c + u * 32, tg(v.x, tag), v.y, v.z, v.w); }
        }
        const float m0 = cs_[0] * (1.f / 448), m1 = cs_[2] * (1.f / 448);
        const uint32_t mb0 = pack(m0, m0), mb1 = pack(m1, m1);
        asm volatile("bar.arrive 2, 288;" ::"r"(mb0) : "memory");
#pragma unroll
        for (int ks = 0; ks < 28; ks++) {
          a[ks].x = bsub(a[ks].x, mb0); a[ks].y = bsub(a[ks].y, mb1); a[ks].z = bsub(a[ks].z, mb0); a[ks].w = bsub(a[ks].w, mb1);
          mma16816(c0, a[ks], a[ks].x, a[ks].z); mma16816(c1, a[ks], a[ks].y, a[ks].w);
        }
        const int src = (ln_ & 28) | (g >> 1);
        const float q0 = __shfl_sync(~0u, (g & 1) ? c0[1] : c0[0], src), q1 = __shfl_sync(~0u, (g & 1) ? c1[3] : c1[2], src);
        const float e0 = m0 - blo(mb0), e1 = m1 - blo(mb1);
        r0 = rsqrtf(fmaxf(q0 * (1.f / 448) - e0 * e0, 0.f) + 1e-5f); r1 = rsqrtf(fmaxf(q1 * (1.f / 448) - e1 * e1, 0.f) + 1e-5f);
      } else {
        ln_publish(xw, sLN, warp, lane, fr, xtag);
        hint_post(hme, hs + 1, lane);
#pragma unroll
        for (int u = 0; u < 4; u++) if (u < 3 || wg == 0) stll(fr + XR + u * 256, tg(xw[u][0], tag), xw[u][1], xw[u][2], xw[u][3]);
        MARK(20);
        hint_wait(g_H + (t * 8 + (ln_ & 7)) * 8 + warp, hs + 1); ll_issue<0, 28>(a, pa, 32);
      }
      MARK(2 + L * 19);
      float ak[28], av[28], aq[28], pp[28];
#define KVSTAGE(i) { if (L) ll_check<7 * i, 7, false>(a, pa, 32, xtag); const uint32_t st = acquire(); wg_fence(); \
      _Pragma("unroll") for (int ks = 0; ks < 7; ks++) { const uint4 f = a[7 * i + ks]; \
        wgmma_rs56(ak, f.x, f.y, f.z, f.w, mkdesc(st, ks * 2048, 1024, 1024, 1), i | ks); \
        wgmma_rs56(av, f.x, f.y, f.z, f.w, mkdesc(st, 14336 + ks * 2048, 1024, 1024, 1), i | ks); } \
      wg_commit(); if (i > 0) { wg_wait<1>(); release(); } }
      KVSTAGE(0) KVSTAGE(1) KVSTAGE(2) KVSTAGE(3)
      wg_wait<0>(); release(); regfence(ak); regfence(av);
      MARK(3 + L * 19);
      if (L == 0) asm volatile("bar.sync 3, 320;" ::: "memory");
      phi_gemm(ak, pp, d16 + (OFF_WPHI >> 4), r0, r1);
#pragma unroll
      for (int j = 0; j < 7; j++) {
        const int n = 8 * j + 2 * q, n2 = n < 28 ? n : n + 4;
        sts32(sV + sw128(row0, n2), pack(av[4 * j] * r0, av[4 * j + 1] * r0)); sts32(sV + sw128(row0 + 8, n2), pack(av[4 * j + 2] * r1, av[4 * j + 3] * r1));
      }
      { const int n2 = 28 + 2 * (q & 1) + 32 * (q >> 1); const uint32_t v = (q & 1) ? 0u : 0x3F80u; sts32(sV + sw128(row0, n2), v); sts32(sV + sw128(row0 + 8, n2), v); }
      wg_wait<0>(); regfence(pp);
      hedgehog(pp, [&](int r, int h, int p, uint32_t v) { sts32(sPK + h * 16384 + sw128(row0 + 8 * r, 8 * p + 2 * q), v); }, [] {});
      fence_async();
      bar_cons();
      MARK(4 + L * 19);
      float kv[16];
      wg_fence();
#pragma unroll
      for (int ks = 0; ks < 8; ks++) wgmma_ss32(kv, mkdesc(d16 + wg * 1024, OFF_PHIK + ks * 2048, 1024, 1024, 1), mkdesc(d16 + wg * 4, OFF_V + ks * 2048, 1024, 1024, 1), ks);
      wg_commit(); wg_wait<0>(); regfence(kv);
      const int ln2 = laneid();
#pragma unroll
      for (int u = 0; u < 4; u++) {
        float e[4];
#pragma unroll
        for (int i = 0; i < 4; i++) e[i] = kv[4 * u + i];
        stll(g_KVP + (c * 16 + t) * 1024 + wg * 512 + u * 128 + (warp & 3) * 32 + ln2, tg(__float_as_uint(e[0]), tag), __float_as_uint(e[1]), __float_as_uint(e[2]), __float_as_uint(e[3]));
      }
      MARK(5 + L * 19);
      uint4 k4[4];
      const uint4* pk = g_KVP + (c * 16 + 4 * (ln2 & 3)) * 1024 + 64 * t + warp * 8 + (ln2 >> 2);
#pragma unroll
      for (int i = 0; i < 2; i++) {
        const uint32_t st = acquire(); wg_fence();
#pragma unroll
        for (int ks = 0; ks < 14; ks++) { const uint4 f = a[14 * i + ks]; wgmma_rs56(aq, f.x, f.y, f.z, f.w, mkdesc(st, ks * 2048, 1024, 1024, 1), i | ks); }
        wg_commit();
        if (i == 0) ll_issue<0, 4>(k4, pk, 1024);
      }
      ll_check<0, 4, false>(k4, pk, 1024, tag);
      float s0 = 0, s1 = 0, s2 = 0, s3 = 0;
#pragma unroll
      for (int i = 0; i < 4; i++) { s0 += __uint_as_float(k4[i].x); s1 += __uint_as_float(k4[i].y); s2 += __uint_as_float(k4[i].z); s3 += __uint_as_float(k4[i].w); }
      s0 = qsum(s0); s1 = qsum(s1); s2 = qsum(s2); s3 = qsum(s3);
      if (q == 0) stll2(g_KVR + c * 1024 + 64 * t + warp * 8 + (ln2 >> 2), tg(pack(s0, s1), tag), pack(s2, s3));
      MARK(6 + L * 19);
      wg_wait<0>(); release(); release(); regfence(aq);
      phi_gemm(aq, pp, d16 + (OFF_WPHI >> 4), r0, r1);
      bar_cons();
#pragma unroll
      for (int i = 0; i < 4; i++) sts128(sV + warp * 2048 + (lane + i * 32) * 16, 0, 0, 0, 0);
      wg_wait<0>(); regfence(pp);
      uint2 r[4];
      const uint2* pr = g_KVR + c * 1024 + wg * 512 + (warp & 3) * 32 + ln2;
      hedgehog(pp, [&](int r, int h, int p, uint32_t v) { phq[r][h][p] = v; }, [&] {
#pragma unroll
        for (int u = 0; u < 4; u++) r[u] = ldll2(pr + u * 128); });
      MARK(7 + L * 19);
#pragma unroll 1
      for (int it = 0; it < SPIN; it++) {
        if (!__any_sync(~0u, ((r[0].x ^ tag) | (r[1].x ^ tag) | (r[2].x ^ tag) | (r[3].x ^ tag)) & 1)) break;
#pragma unroll
        for (int u = 0; u < 4; u++) r[u] = ldll2(pr + u * 128);
      }
#pragma unroll
      for (int u = 0; u < 4; u++) {
        const int d = 8 * u + 2 * q;
        if (d < 28) { sts32(sV + sw128(row0, 28 * wg + d), r[u].x); sts32(sV + sw128(row0 + 8, 28 * wg + d), r[u].y); }
        else if (d == 28) {
#pragma unroll
          for (int j = 0; j < 4; j++) { sts16(sV + sw128(row0, 56 + 2 * j + wg), r[u].x); sts16(sV + sw128(row0 + 8, 56 + 2 * j + wg), r[u].y); }
        }
      }
      fence_async();
      bar_cons();
      MARK(8 + L * 19);
      float o[32];
      wg_fence();
#pragma unroll
      for (int ks = 0; ks < 8; ks++) {
        const int h = ks >> 2, p = 2 * (ks & 3);
        wgmma_rs64(o, phq[0][h][p], phq[1][h][p], p < 6 ? phq[0][h][p < 6 ? p + 1 : 0] : 0u, p < 6 ? phq[1][h][p < 6 ? p + 1 : 0] : 0u, mkdesc(d16, OFF_V + ks * 2048, 1024, 1024, 1), ks);
      }
      wg_commit(); wg_wait<0>(); regfence(o);
      const float iA0 = rcp(o[28] + 1e-6f), iB0 = rcp(o[29] + 1e-6f), iA1 = rcp(o[30] + 1e-6f), iB1 = rcp(o[31] + 1e-6f);
      uint32_t w[14];
      { PTRS
#pragma unroll
      for (int j = 0; j < 7; j++) {
        const bool hb = 8 * j + 2 * q >= 28; const float i0 = hb ? iB0 : iA0, i1 = hb ? iB1 : iA1;
        w[2 * j] = pack(o[4 * j] * i0, o[4 * j + 1] * i0); w[2 * j + 1] = pack(o[4 * j + 2] * i1, o[4 * j + 3] * i1);
        if (j == 0 || ((j ^ c) & 1) == 0) w[2 * j] = tg(w[2 * j], tag);
      }
      slice_store(sf + OO, sh + 2 * OO, w, c & 1);
      hint_post(hme, hs + 2, lane); }
    }
    MARK(9 + L * 19);
    uint4 xr[4];
    if (c < 7) {
      PTRS
      ll_issue<0, 4>(xr, fm + XR + 128 * c, 32);
      uint4 a[28];
      const uint4* pa = fm + OO;
      hint_wait(hrow, hs + 2);
      MARK(10 + L * 19);
      ll_issue<0, 28, true>(a, pa, 32, f2 + 2 * OO);
      float y[32];
      uint32_t st;
#define WOSTEP(i) { ll_check<7 * i, 7, true>(a, pa, 32, tag, f2 + 2 * OO); if (!(i & 1)) st = acquire(); wg_fence(); \
      _Pragma("unroll") for (int ks = 0; ks < 7; ks++) { const uint4 f = a[7 * i + ks]; \
        wgmma_rs64(y, f.x, f.y, f.z, f.w, mkdesc(st, ((i & 1) * 7 + ks) * 2048, 1024, 1024, 1), i | ks); } wg_commit(); }
      WOSTEP(0) WOSTEP(1) WOSTEP(2) WOSTEP(3)
      ll_check<0, 4, false>(xr, fm + XR + 128 * c, 32, tag);
      wg_wait<0>(); regfence(y);
      MARK(11 + L * 19);
#pragma unroll
      for (int u = 0; u < 4; u++) {
        xr[u].x = tg(pack(blo(xr[u].x) + y[8 * u], bhi(xr[u].x) + y[8 * u + 1]), tag); xr[u].y = pack(blo(xr[u].y) + y[8 * u + 2], bhi(xr[u].y) + y[8 * u + 3]);
        xr[u].z = pack(blo(xr[u].z) + y[8 * u + 4], bhi(xr[u].z) + y[8 * u + 5]); xr[u].w = pack(blo(xr[u].w) + y[8 * u + 6], bhi(xr[u].w) + y[8 * u + 7]);
        stll(fm + X1 + 128 * c + u * 32, xr[u].x, xr[u].y, xr[u].z, xr[u].w);
      }
      hint_post(hme, hs + 3, lane);
    } else {
      PTRS
      hint_post(hme, hs + 3, lane);
      acquire(); acquire();
      hint_wait(g_H + (t * 8 + warp) * 8, hs + 3);
      ll_issue<0, 4>(xr, fm + X1, 32); ll_check<0, 4, false>(xr, fm + X1, 32, tag);
      MARK(10 + L * 19); MARK(11 + L * 19);
    }
    uint32_t hf[56];
    float rr0, rr1;
    {
      PTRS
      uint4 a[28];
      const uint4* pa = fm + X1;
      auto grp = [&](int i) -> const uint4* { const int k = i + c; return pa + ((k >= 7 ? k - 7 : k) - i) * 128; };
#pragma unroll
      for (int u = 0; u < 4; u++) a[u] = xr[u];
      float y[96], z[16];
#define F1STAGE(i) { if (i > 0) ll_check<4 * i, 4, false>(a, grp(i), 32, tag); const uint32_t st = acquire(); wg_fence(); \
      _Pragma("unroll") for (int ks = 0; ks < 4; ks++) { const uint4 f = a[4 * i + ks]; \
        wgmma_rs192(y, f.x, f.y, f.z, f.w, mkdesc(st, (ks >> 1) * 12288 + (ks & 1) * 2048, 4096, 1024, 1), i | ks); \
        wgmma_rs32(z, f.x, f.y, f.z, f.w, mkdesc(st, 24576 + ks * 1024, 512, 512, 2), i | ks); } \
      wg_commit(); if (i > 0) { wg_wait<1>(); release(); if (i < 4) ll_issue<(i < 4 ? 4 * i + 12 : 0), 4>(a, grp(i + 3), 32); } }
      F1STAGE(0)
      hint_wait(hrow, hs + 3);
      MARK(12 + L * 19);
      ll_issue<4, 4>(a, grp(1), 32); ll_issue<8, 4>(a, grp(2), 32); ll_issue<12, 4>(a, grp(3), 32);
      if (c < 7) {
        float s0 = 0.f, s1 = 0.f, v0 = 0.f, v1 = 0.f;
#pragma unroll
        for (int u = 0; u < 4; u++) { s0 += (blo(xr[u].x) + bhi(xr[u].x)) + (blo(xr[u].z) + bhi(xr[u].z)); s1 += (blo(xr[u].y) + bhi(xr[u].y)) + (blo(xr[u].w) + bhi(xr[u].w)); }
        s0 = qsum(s0) * (1.f / 64); s1 = qsum(s1) * (1.f / 64);
#pragma unroll
        for (int u = 0; u < 4; u++) {
          const float d0 = blo(xr[u].x) - s0, d1 = bhi(xr[u].x) - s0, d2 = blo(xr[u].z) - s0, d3 = bhi(xr[u].z) - s0;
          const float d4 = blo(xr[u].y) - s1, d5 = bhi(xr[u].y) - s1, d6 = blo(xr[u].w) - s1, d7 = bhi(xr[u].w) - s1;
          v0 += (d0 * d0 + d1 * d1) + (d2 * d2 + d3 * d3); v1 += (d4 * d4 + d5 * d5) + (d6 * d6 + d7 * d7);
        }
        v0 = qsum(v0); v1 = qsum(v1);
        if (q == 0) stll(g_ST + ((t * 8 + warp) * 8 + c) * 8 + (ln_ >> 2), tg(__float_as_uint(s0), tag), __float_as_uint(v0), __float_as_uint(s1), __float_as_uint(v1));
      }
      release(); release();
      F1STAGE(1) MARK(13 + L * 19); F1STAGE(2) F1STAGE(3)
      uint4 sv[2];
      const uint4* ps = g_ST + ((t * 8 + warp) * 8 + 2 * (laneid() & 3)) * 8 + (laneid() >> 2);
      ll_issue<0, 2>(sv, ps, q < 3 ? 8 : 0);
      F1STAGE(4)
      ll_check<0, 2, false>(sv, ps, q < 3 ? 8 : 0, tag);
      const float wb = q < 3 ? 1.f : 0.f;
      const float ma = __uint_as_float(sv[0].x), mb = __uint_as_float(sv[1].x), mc = __uint_as_float(sv[0].z), md = __uint_as_float(sv[1].z);
      const float m0 = qsum(ma + wb * mb) * (1.f / 7), m1 = qsum(mc + wb * md) * (1.f / 7);
      const float v0 = qsum(__uint_as_float(sv[0].y) + 64.f * (ma - m0) * (ma - m0) + wb * (__uint_as_float(sv[1].y) + 64.f * (mb - m0) * (mb - m0)));
      const float v1 = qsum(__uint_as_float(sv[0].w) + 64.f * (mc - m1) * (mc - m1) + wb * (__uint_as_float(sv[1].w) + 64.f * (md - m1) * (md - m1)));
      const float e0 = v0 * (1.f / 448) + 1e-5f, e1 = v1 * (1.f / 448) + 1e-5f;
      rr0 = 1.f / e0; rr1 = 1.f / e1;
      auto fold = [&](float m, float sd) -> uint32_t {
        const float mh = blo(pack(-m, 0.f)), sh_ = blo(pack(sd, 0.f));
        return q == 0 ? pack(mh, -m - mh) : q == 1 ? pack(mh, sh_) : q == 2 ? pack(sd - sh_, 0.f) : 0u;
      };
      const uint32_t fa = fold(m0, sqrtf(e0)), fb = fold(m1, sqrtf(e1));
      if (L == 0) asm volatile("bar.sync 4, 288;" ::: "memory");
      wg_fence();
      wgmma_rs192(y, fa, fb, 0u, 0u, mkdesc(d16, OFF_CB + 0, 512, 0, 2), 1);
      wgmma_rs32(z, fa, fb, 0u, 0u, mkdesc(d16, OFF_CB + 3072, 512, 0, 2), 1);
      F1STAGE(5) F1STAGE(6)
      wg_wait<0>(); release(); regfence(y); regfence(z);
      MARK(14 + L * 19);
#pragma unroll
      for (int j = 0; j < 56; j++) {
        uint32_t r; asm("cvt.rn.relu.bf16x2.f32 %0, %1, %2;" : "=r"(r) : "f"(j < 48 ? y[j < 48 ? 2 * j + 1 : 0] : z[j < 48 ? 0 : 2 * j - 95]), "f"(j < 48 ? y[j < 48 ? 2 * j : 0] : z[j < 48 ? 0 : 2 * j - 96]));
        asm("mul.bf16x2 %0, %1, %1;" : "=r"(hf[j]) : "r"(r));
      }
    }
    MARK(15 + L * 19);
    {
      PTRS
      float ya[32], yb[32];
      uint4* pp = g_P + ((t * 8 + warp) * 8 + c) * 28 * 32 + ln_;
#define F2STORE(j, Y) { regfence(Y); _Pragma("unroll") for (int u = 0; u < 4; u++) \
      stll(pp + (4 * (j) + u) * 32, tg(pack(Y[8 * u] * rr0, Y[8 * u + 1] * rr0), tag), pack(Y[8 * u + 2] * rr1, Y[8 * u + 3] * rr1), \
           pack(Y[8 * u + 4] * rr0, Y[8 * u + 5] * rr0), pack(Y[8 * u + 6] * rr1, Y[8 * u + 7] * rr1)); hint_post(hme, hs + (4 + (j)), lane); }
#define F2PASS(j, Y, Z) { const uint32_t st = acquire(); wg_fence(); \
      _Pragma("unroll") for (int ks = 0; ks < 14; ks++) wgmma_rs64(Y, hf[4 * ks], hf[4 * ks + 1], hf[4 * ks + 2], hf[4 * ks + 3], mkdesc(st, ks * 2048, 1024, 1024, 1), ks); \
      wg_commit(); if (j > 0) { wg_wait<1>(); release(); F2STORE(j - 1, Z) } }
      const uint4* pr = g_P + ((t * 8 + c) * 8 * 28 + warp) * 32 + ln_;
      uint4 p[8], p2[8]; uint2 xa, xb, xc, xd; uint32_t ba, bb, bc, bd;
#define RISSUE(m, P, XA, XB, BA, BB) { ll_issue<0, 8>(P, pr + (m) * 256, 896); \
      { const uint4 v_ = ldll(fr + X1 + (m) * 256); XA = make_uint2(v_.x, v_.y); XB = make_uint2(v_.z, v_.w); } \
      const uint32_t* bp = (const uint32_t*)(b2 + 128 * (m) + 16 * warp) + (ln_ & 3); BA = __ldg(bp); BB = __ldg(bp + 4); }
#define REDU(m, P, XA, XB, BA, BB) { ll_check<0, 8, false>(P, pr + (m) * 256, 896, tag); \
      float e[8] = {blo(XA.x) + blo(BA), bhi(XA.x) + bhi(BA), blo(XA.y) + blo(BA), bhi(XA.y) + bhi(BA), blo(XB.x) + blo(BB), bhi(XB.x) + bhi(BB), blo(XB.y) + blo(BB), bhi(XB.y) + bhi(BB)}; \
      _Pragma("unroll") for (int i = 0; i < 8; i++) { e[0] += blo(P[i].x); e[1] += bhi(P[i].x); e[2] += blo(P[i].y); e[3] += bhi(P[i].y); \
        e[4] += blo(P[i].z); e[5] += bhi(P[i].z); e[6] += blo(P[i].w); e[7] += bhi(P[i].w); } \
      xw[m][0] = pack(e[0], e[1]); xw[m][1] = pack(e[2], e[3]); xw[m][2] = pack(e[4], e[5]); xw[m][3] = pack(e[6], e[7]); }
      const uint32_t* hred = g_H + (t * 8 + c) * 8 + (ln_ & 7);
      F2PASS(0, ya, yb) F2PASS(1, yb, ya) F2PASS(2, ya, yb) F2PASS(3, yb, ya)
      uint32_t hv = hint_ld(hred);
      F2PASS(4, ya, yb)
      hint_wait(hred, hs + 4 + wg, hv);
      RISSUE(0, p, xa, xb, ba, bb)
      F2PASS(5, yb, ya)
      hv = hint_ld(hred);
      REDU(0, p, xa, xb, ba, bb)
      F2PASS(6, ya, yb)
      hint_wait(hred, hs + 6 + wg, hv);
      RISSUE(1, p, xa, xb, ba, bb)
      hv = hint_ld(hred);
      wg_wait<0>(); release(); F2STORE(6, ya)
      MARK(16 + L * 19);
      hint_wait(hred, hs + 8 + wg, hv);
      RISSUE(2, p2, xc, xd, bc, bd)
      REDU(1, p, xa, xb, ba, bb)
      if (wg == 0) { hint_wait(hred, hs + 10); RISSUE(3, p, xa, xb, ba, bb) }
      MARK(17 + L * 19);
      REDU(2, p2, xc, xd, bc, bd)
      if (wg == 0) REDU(3, p, xa, xb, ba, bb) else { xw[3][0] = xw[3][1] = xw[3][2] = xw[3][3] = 0; }
    }
    MARK(18 + L * 19);
  }
  {
    uint32_t* op = (uint32_t*)(out + XOFF(laneid()));
#pragma unroll
    for (int u = 0; u < 4; u++) if (u < 3 || wg == 0) { op[u * 64] = xw[u][0]; op[u * 64 + 1792] = xw[u][1]; op[u * 64 + 4] = xw[u][2]; op[u * 64 + 1796] = xw[u][3]; }
    PTRS
#pragma unroll
    for (int u = 0; u < 4; u++) if (u < 3 || wg == 0) stll(fr + XN + u * 256, 0, 0, 0, 0);
    if (warp == 7 && blockIdx.x < 112 && lane < 4) stll(g_CS + blockIdx.x * 4 + lane, 0, 0, 0, 0);
  }
  MARK(38);
  }
}

typedef CUresult (*EncFn)(CUtensorMap*, CUtensorMapDataType, cuuint32_t, void*, const cuuint64_t*, const cuuint64_t*, const cuuint32_t*, const cuuint32_t*,
                          CUtensorMapInterleave, CUtensorMapSwizzle, CUtensorMapL2promotion, CUtensorMapFloatOOBfill);

extern "C" void kernel_launch(void* const* d_in, const int* in_sizes, int n_in, void* d_out, int out_size) {
  static EncFn enc = nullptr;
  if (!enc) {
    void* fn = nullptr; cudaDriverEntryPointQueryResult qr;
    cudaGetDriverEntryPoint("cuTensorMapEncodeTiled", &fn, cudaEnableDefault, &qr);
    enc = (EncFn)fn;
    cudaFuncSetAttribute(fused_kernel, cudaFuncAttributeMaxDynamicSharedMemorySize, SMEM_BYTES);
  }
  CUtensorMap mQKV, mWO, mW1, mW1b, mW2, mW2b, mX;
  const cuuint32_t es[3] = {1, 1, 1};
  auto enc2 = [&](CUtensorMap* m, void* p, cuuint64_t cols, cuuint64_t rows, cuuint32_t bc, cuuint32_t br) {
    const cuuint64_t dims[2] = {cols, rows}, str[1] = {cols * 2}; const cuuint32_t box[2] = {bc, br};
    enc(m, CU_TENSOR_MAP_DATA_TYPE_BFLOAT16, 2, p, dims, str, box, es, CU_TENSOR_MAP_INTERLEAVE_NONE,
        bc == 64 ? CU_TENSOR_MAP_SWIZZLE_128B : CU_TENSOR_MAP_SWIZZLE_64B, CU_TENSOR_MAP_L2_PROMOTION_L2_128B, CU_TENSOR_MAP_FLOAT_OOB_FILL_NONE);
  };
  enc2(&mQKV, d_in[1], 1344, 448, 64, 112); enc2(&mWO, d_in[3], 448, 448, 64, 112); enc2(&mW1b, d_in[5], 1792, 448, 32, 32);
  enc2(&mX, d_in[0], 448, 2048, 64, 128);
  enc2(&mW2, d_in[7], 448, 1792, 64, 96); enc2(&mW2b, d_in[7], 448, 1792, 64, 16);
  {
    const cuuint64_t dims[3] = {64, 448, 28}, str[2] = {3584, 128}; const cuuint32_t box[3] = {64, 32, 3};
    enc(&mW1, CU_TENSOR_MAP_DATA_TYPE_BFLOAT16, 3, d_in[5], dims, str, box, es, CU_TENSOR_MAP_INTERLEAVE_NONE, CU_TENSOR_MAP_SWIZZLE_128B,
        CU_TENSOR_MAP_L2_PROMOTION_L2_128B, CU_TENSOR_MAP_FLOAT_OOB_FILL_NONE);
  }
  typedef const __nv_bfloat16* BP;
  fused_kernel<<<128, 384, SMEM_BYTES>>>(mQKV, mWO, mW1, mW1b, mW2, mW2b, mX, (BP)d_in[2], (BP)d_in[3], (BP)d_in[5], (BP)d_in[6], (BP)d_in[7], (BP)d_in[8],
                                         (__nv_bfloat16*)d_out);
}
```

```cpp
#include <cuda_runtime.h>
#include <cuda_bf16.h>
#include <cuda.h>
#include <stdint.h>

constexpr int NST = 6, STAGE = 28672;
constexpr int OFF_PHIK = NST * STAGE;
constexpr int OFF_V = OFF_PHIK + 32768;
constexpr int OFF_WPHI = OFF_V + 16384;
constexpr int OFF_CB = OFF_WPHI + 7168;
constexpr int OFF_BAR = OFF_CB + 3584;
constexpr int SMEM_BYTES = OFF_BAR + 16 * NST + 8;
constexpr int FR = 16 * 8 * 28 * 32;
constexpr int SPIN = 1 << 18;
#define MC 0
#define MAPPING MC
#define MCS
#define MCA(n)
#define CLUSTER
#define PACE 2

__device__ uint4 g_F[4 * FR];
constexpr int XN = 0, XR = FR, OO = 2 * FR, X1 = 3 * FR;
__device__ uint4 g_P[8 * FR];
__device__ uint4 g_ST[16 * 8 * 8 * 8];
__device__ uint4 g_KVP[8 * 16 * 1024];
__device__ uint2 g_KVR[8 * 1024];
__device__ uint4 g_CS[448];
__device__ uint4 g_WQ[8 * 6 * (STAGE / 16)];
__device__ uint32_t g_WQF[8];
__device__ uint32_t g_H[16 * 8 * 8];
#define MARK(i)

__device__ __forceinline__ uint32_t s2u(const void* p) { return (uint32_t)__cvta_generic_to_shared(p); }
__device__ __forceinline__ void mbar_init(uint32_t b, uint32_t c) { asm volatile("mbarrier.init.shared::cta.b64 [%0], %1;" ::"r"(b), "r"(c)); }
__device__ __forceinline__ void mbar_expect(uint32_t b, uint32_t tx) { asm volatile("mbarrier.arrive.expect_tx.shared::cta.b64 _, [%0], %1;" ::"r"(b), "r"(tx) : "memory"); }
__device__ __forceinline__ void mbar_arrive_cl(uint32_t b, uint32_t rank) {
  asm volatile("{.reg .b32 r; mapa.shared::cluster.u32 r, %0, %1; mbarrier.arrive.shared::cluster.b64 _, [r];}" ::"r"(b), "r"(rank) : "memory");
}
__device__ __forceinline__ void mbar_wait(uint32_t b, uint32_t ph) {
  uint32_t ok = 0;
#pragma unroll 1
  for (int it = 0; it < SPIN && !ok; it++)
    asm volatile("{.reg .pred p; mbarrier.try_wait.parity.shared::cta.b64 p,[%1],%2; selp.u32 %0,1,0,p;}" : "=r"(ok) : "r"(b), "r"(ph) : "memory");
}
__device__ __forceinline__ void tma2d(uint32_t dst, const CUtensorMap* m, int c0, int c1, uint32_t bar) {
  asm volatile("cp.async.bulk.tensor.2d.shared::cluster.global.mbarrier::complete_tx::bytes" MCS " [%0], [%1, {%3, %4}], [%2]" MCA(5) ";"
               ::"r"(dst), "l"(m), "r"(bar), "r"(c0), "r"(c1), "h"((uint16_t)3) : "memory");
}
__device__ __forceinline__ void tma3d(uint32_t dst, const CUtensorMap* m, int c0, int c1, int c2, uint32_t bar) {
  asm volatile("cp.async.bulk.tensor.3d.shared::cluster.global.mbarrier::complete_tx::bytes" MCS " [%0], [%1, {%3, %4, %5}], [%2]" MCA(6) ";"
               ::"r"(dst), "l"(m), "r"(bar), "r"(c0), "r"(c1), "r"(c2), "h"((uint16_t)3) : "memory");
}
__device__ __forceinline__ void l2pf(const void* p, uint32_t bytes) { asm volatile("cp.async.bulk.prefetch.L2.global [%0], %1;" ::"l"(p), "r"(bytes) : "memory"); }
__device__ __forceinline__ void wg_fence() { asm volatile("wgmma.fence.sync.aligned;" ::: "memory"); }
__device__ __forceinline__ void wg_commit() { asm volatile("wgmma.commit_group.sync.aligned;" ::: "memory"); }
template <int N> __device__ __forceinline__ void wg_wait() { asm volatile("wgmma.wait_group.sync.aligned %0;" ::"n"(N) : "memory"); }
template <int N> __device__ __forceinline__ void regfence(float (&d)[N]) {
#pragma unroll
  for (int i = 0; i < N; i++) asm volatile("" : "+f"(d[i])::"memory");
}
__device__ __forceinline__ void bar_cons() { asm volatile("bar.sync 1, 256;" ::: "memory"); }
__device__ __forceinline__ void fence_async() { asm volatile("fence.proxy.async.shared::cta;" ::: "memory"); }
struct Desc { uint32_t lo, hi; };
__device__ __forceinline__ Desc mkdesc(uint32_t base16, uint32_t off, uint32_t lbo, uint32_t sbo, uint32_t swz) {
  return Desc{base16 + ((off >> 4) | ((lbo >> 4) << 16)), (sbo >> 4) | (swz << 30)};
}
__device__ __forceinline__ uint4 ldll(const uint4* p) {
  uint4 v; asm volatile("ld.relaxed.gpu.global.v4.u32 {%0,%1,%2,%3}, [%4];" : "=r"(v.x), "=r"(v.y), "=r"(v.z), "=r"(v.w) : "l"(p) : "memory"); return v;
}
__device__ __forceinline__ uint2 ldll2(const uint2* p) {
  uint2 v; asm volatile("ld.relaxed.gpu.global.v2.u32 {%0,%1}, [%2];" : "=r"(v.x), "=r"(v.y) : "l"(p) : "memory"); return v;
}
__device__ __forceinline__ void stll(uint4* p, uint32_t x, uint32_t y, uint32_t z, uint32_t w) {
  asm volatile("st.relaxed.gpu.global.v4.u32 [%0], {%1,%2,%3,%4};" ::"l"(p), "r"(x), "r"(y), "r"(z), "r"(w) : "memory");
}
__device__ __forceinline__ void stll2(void* p, uint32_t x, uint32_t y) {
  asm volatile("st.relaxed.gpu.global.v2.u32 [%0], {%1,%2};" ::"l"(p), "r"(x), "r"(y) : "memory");
}
__device__ __forceinline__ int laneid() { int l; asm volatile("mov.u32 %0, %%laneid;" : "=r"(l)); return l; }
__device__ __forceinline__ uint32_t tg(uint32_t w, uint32_t tag) { return (w & ~1u) | tag; }
__device__ __forceinline__ uint32_t pack(float lo, float hi) {
  uint32_t r; asm("cvt.rn.bf16x2.f32 %0, %1, %2;" : "=r"(r) : "f"(hi), "f"(lo)); return r;
}
__device__ __forceinline__ float blo(uint32_t w) { return __uint_as_float(w << 16); }
__device__ __forceinline__ float bhi(uint32_t w) { return __uint_as_float(w & 0xffff0000u); }
__device__ __forceinline__ float ex2(float x) { float r; asm("ex2.approx.ftz.f32 %0, %1;" : "=f"(r) : "f"(x)); return r; }
__device__ __forceinline__ float rcp(float x) { float r; asm("rcp.approx.ftz.f32 %0, %1;" : "=f"(r) : "f"(x)); return r; }
__device__ __forceinline__ float qsum(float v) { v += __shfl_xor_sync(~0u, v, 1); v += __shfl_xor_sync(~0u, v, 2); return v; }
__device__ __forceinline__ void sts32(uint32_t a, uint32_t v) { asm volatile("st.shared.u32 [%0], %1;" ::"r"(a), "r"(v) : "memory"); }
__device__ __forceinline__ void sts16(uint32_t a, uint32_t v) { asm volatile("st.shared.u16 [%0], %1;" ::"r"(a), "h"((uint16_t)v) : "memory"); }
__device__ __forceinline__ void sts128(uint32_t a, uint32_t x, uint32_t y, uint32_t z, uint32_t w) {
  asm volatile("st.shared.v4.u32 [%0], {%1,%2,%3,%4};" ::"r"(a), "r"(x), "r"(y), "r"(z), "r"(w) : "memory");
}
__device__ __forceinline__ uint32_t sw128(int row, int col) { return row * 128 + ((((col >> 3) ^ row) & 7) << 4) + (col & 7) * 2; }

__device__ __forceinline__ void wgmma_rs56(float (&d)[28], const uint32_t a0, const uint32_t a1, const uint32_t a2, const uint32_t a3, Desc db, int sd) {
  asm volatile("{.reg .pred p; .reg .b64 da, db; setp.ne.b32 p, %33, 0; mov.b64 db, {%32, %34};\n wgmma.mma_async.sync.aligned.m64n56k16.f32.bf16.bf16 {%0,%1,%2,%3,%4,%5,%6,%7,%8,%9,%10,%11,%12,%13,%14,%15,%16,%17,%18,%19,%20,%21,%22,%23,%24,%25,%26,%27}, {%28,%29,%30,%31}, db, p, 1, 1, 1;}"
   : "+f"(d[0]),"+f"(d[1]),"+f"(d[2]),"+f"(d[3]),"+f"(d[4]),"+f"(d[5]),"+f"(d[6]),"+f"(d[7]),"+f"(d[8]),"+f"(d[9]),"+f"(d[10]),"+f"(d[11]),"+f"(d[12]),"+f"(d[13]),"+f"(d[14]),"+f"(d[15]),"+f"(d[16]),"+f"(d[17]),"+f"(d[18]),"+f"(d[19]),"+f"(d[20]),"+f"(d[21]),"+f"(d[22]),"+f"(d[23]),"+f"(d[24]),"+f"(d[25]),"+f"(d[26]),"+f"(d[27])
   : "r"(a0),"r"(a1),"r"(a2),"r"(a3),"r"(db.lo),"r"(sd),"r"(db.hi));
}
__device__ __forceinline__ void wgmma_rs64(float (&d)[32], const uint32_t a0, const uint32_t a1, const uint32_t a2, const uint32_t a3, Desc db, int sd) {
  asm volatile("{.reg .pred p; .reg .b64 da, db; setp.ne.b32 p, %37, 0; mov.b64 db, {%36, %38};\n wgmma.mma_async.sync.aligned.m64n64k16.f32.bf16.bf16 {%0,%1,%2,%3,%4,%5,%6,%7,%8,%9,%10,%11,%12,%13,%14,%15,%16,%17,%18,%19,%20,%21,%22,%23,%24,%25,%26,%27,%28,%29,%30,%31}, {%32,%33,%34,%35}, db, p, 1, 1, 1;}"
   : "+f"(d[0]),"+f"(d[1]),"+f"(d[2]),"+f"(d[3]),"+f"(d[4]),"+f"(d[5]),"+f"(d[6]),"+f"(d[7]),"+f"(d[8]),"+f"(d[9]),"+f"(d[10]),"+f"(d[11]),"+f"(d[12]),"+f"(d[13]),"+f"(d[14]),"+f"(d[15]),"+f"(d[16]),"+f"(d[17]),"+f"(d[18]),"+f"(d[19]),"+f"(d[20]),"+f"(d[21]),"+f"(d[22]),"+f"(d[23]),"+f"(d[24]),"+f"(d[25]),"+f"(d[26]),"+f"(d[27]),"+f"(d[28]),"+f"(d[29]),"+f"(d[30]),"+f"(d[31])
   : "r"(a0),"r"(a1),"r"(a2),"r"(a3),"r"(db.lo),"r"(sd),"r"(db.hi));
}
__device__ __forceinline__ void wgmma_rs192(float (&d)[96], const uint32_t a0, const uint32_t a1, const uint32_t a2, const uint32_t a3, Desc db, int sd) {
  asm volatile("{.reg .pred p; .reg .b64 db; setp.ne.b32 p, %101, 0; mov.b64 db, {%100, %102};\n wgmma.mma_async.sync.aligned.m64n192k16.f32.bf16.bf16 {%0,%1,%2,%3,%4,%5,%6,%7,%8,%9,%10,%11,%12,%13,%14,%15,%16,%17,%18,%19,%20,%21,%22,%23,%24,%25,%26,%27,%28,%29,%30,%31,%32,%33,%34,%35,%36,%37,%38,%39,%40,%41,%42,%43,%44,%45,%46,%47,%48,%49,%50,%51,%52,%53,%54,%55,%56,%57,%58,%59,%60,%61,%62,%63,%64,%65,%66,%67,%68,%69,%70,%71,%72,%73,%74,%75,%76,%77,%78,%79,%80,%81,%82,%83,%84,%85,%86,%87,%88,%89,%90,%91,%92,%93,%94,%95}, {%96,%97,%98,%99}, db, p, 1, 1, 1;}"
   : "+f"(d[0]),"+f"(d[1]),"+f"(d[2]),"+f"(d[3]),"+f"(d[4]),"+f"(d[5]),"+f"(d[6]),"+f"(d[7]),"+f"(d[8]),"+f"(d[9]),"+f"(d[10]),"+f"(d[11]),"+f"(d[12]),"+f"(d[13]),"+f"(d[14]),"+f"(d[15]),"+f"(d[16]),"+f"(d[17]),"+f"(d[18]),"+f"(d[19]),"+f"(d[20]),"+f"(d[21]),"+f"(d[22]),"+f"(d[23]),"+f"(d[24]),"+f"(d[25]),"+f"(d[26]),"+f"(d[27]),"+f"(d[28]),"+f"(d[29]),"+f"(d[30]),"+f"(d[31]),"+f"(d[32]),"+f"(d[33]),"+f"(d[34]),"+f"(d[35]),"+f"(d[36]),"+f"(d[37]),"+f"(d[38]),"+f"(d[39]),"+f"(d[40]),"+f"(d[41]),"+f"(d[42]),"+f"(d[43]),"+f"(d[44]),"+f"(d[45]),"+f"(d[46]),"+f"(d[47]),"+f"(d[48]),"+f"(d[49]),"+f"(d[50]),"+f"(d[51]),"+f"(d[52]),"+f"(d[53]),"+f"(d[54]),"+f"(d[55]),"+f"(d[56]),"+f"(d[57]),"+f"(d[58]),"+f"(d[59]),"+f"(d[60]),"+f"(d[61]),"+f"(d[62]),"+f"(d[63]),"+f"(d[64]),"+f"(d[65]),"+f"(d[66]),"+f"(d[67]),"+f"(d[68]),"+f"(d[69]),"+f"(d[70]),"+f"(d[71]),"+f"(d[72]),"+f"(d[73]),"+f"(d[74]),"+f"(d[75]),"+f"(d[76]),"+f"(d[77]),"+f"(d[78]),"+f"(d[79]),"+f"(d[80]),"+f"(d[81]),"+f"(d[82]),"+f"(d[83]),"+f"(d[84]),"+f"(d[85]),"+f"(d[86]),"+f"(d[87]),"+f"(d[88]),"+f"(d[89]),"+f"(d[90]),"+f"(d[91]),"+f"(d[92]),"+f"(d[93]),"+f"(d[94]),"+f"(d[95])
   : "r"(a0),"r"(a1),"r"(a2),"r"(a3),"r"(db.lo),"r"(sd),"r"(db.hi));
}
__device__ __forceinline__ void wgmma_rs32(float (&d)[16], const uint32_t a0, const uint32_t a1, const uint32_t a2, const uint32_t a3, Desc db, int sd) {
  asm volatile("{.reg .pred p; .reg .b64 db; setp.ne.b32 p, %21, 0; mov.b64 db, {%20, %22};\n wgmma.mma_async.sync.aligned.m64n32k16.f32.bf16.bf16 {%0,%1,%2,%3,%4,%5,%6,%7,%8,%9,%10,%11,%12,%13,%14,%15}, {%16,%17,%18,%19}, db, p, 1, 1, 1;}"
   : "+f"(d[0]),"+f"(d[1]),"+f"(d[2]),"+f"(d[3]),"+f"(d[4]),"+f"(d[5]),"+f"(d[6]),"+f"(d[7]),"+f"(d[8]),"+f"(d[9]),"+f"(d[10]),"+f"(d[11]),"+f"(d[12]),"+f"(d[13]),"+f"(d[14]),"+f"(d[15])
   : "r"(a0),"r"(a1),"r"(a2),"r"(a3),"r"(db.lo),"r"(sd),"r"(db.hi));
}
__device__ __forceinline__ void wgmma_ss32(float (&d)[16], Desc da, Desc db, int sd) {
  asm volatile("{.reg .pred p; .reg .b64 da, db; setp.ne.b32 p, %18, 0; mov.b64 da, {%16, %19}; mov.b64 db, {%17, %19};\n wgmma.mma_async.sync.aligned.m64n32k16.f32.bf16.bf16 {%0,%1,%2,%3,%4,%5,%6,%7,%8,%9,%10,%11,%12,%13,%14,%15}, da, db, p, 1, 1, 1, 1;}"
   : "+f"(d[0]),"+f"(d[1]),"+f"(d[2]),"+f"(d[3]),"+f"(d[4]),"+f"(d[5]),"+f"(d[6]),"+f"(d[7]),"+f"(d[8]),"+f"(d[9]),"+f"(d[10]),"+f"(d[11]),"+f"(d[12]),"+f"(d[13]),"+f"(d[14]),"+f"(d[15])
   : "r"(da.lo),"r"(db.lo),"r"(sd),"r"(db.hi));
}

__device__ __forceinline__ uint4 ldsm4(uint32_t a) {
  uint4 v; asm volatile("ldmatrix.sync.aligned.m8n8.x4.shared.b16 {%0,%1,%2,%3}, [%4];" : "=r"(v.x), "=r"(v.y), "=r"(v.z), "=r"(v.w) : "r"(a) : "memory"); return v;
}
__device__ __forceinline__ void mma16816(float (&d)[4], const uint4& a, uint32_t b0, uint32_t b1) {
  asm("mma.sync.aligned.m16n8k16.row.col.f32.bf16.bf16.f32 {%0,%1,%2,%3}, {%4,%5,%6,%7}, {%8,%9}, {%0,%1,%2,%3};"
      : "+f"(d[0]), "+f"(d[1]), "+f"(d[2]), "+f"(d[3]) : "r"(a.x), "r"(a.y), "r"(a.z), "r"(a.w), "r"(b0), "r"(b1));
}
__device__ __forceinline__ uint32_t bsub(uint32_t a, uint32_t b) { uint32_t r; asm("sub.bf16x2 %0, %1, %2;" : "=r"(r) : "r"(a), "r"(b)); return r; }
__device__ __forceinline__ uint32_t hint_ld(const uint32_t* p) { uint32_t v; asm volatile("ld.relaxed.gpu.global.u32 %0, [%1];" : "=r"(v) : "l"(p) : "memory"); return v; }
template <int S, int N, bool SPL = false, int T> __device__ __forceinline__ void ll_issue(uint4 (&v)[T], const uint4* p, int stride, const uint2* p2 = nullptr) {
#pragma unroll
  for (int i = S; i < S + N; i++) {
    if (SPL && i % 7 == 3) { const uint2 lo = ldll2(p2 + i * 64), hi = ldll2(p2 + i * 64 + 32); v[i] = make_uint4(lo.x, lo.y, hi.x, hi.y); }
    else v[i] = ldll(p + i * stride);
  }
}
template <int S, int N, bool SPL, int T> __device__ __forceinline__ void ll_check(uint4 (&v)[T], const uint4* p, int stride, uint32_t tag, const uint2* p2 = nullptr) {
#pragma unroll 1
  for (int it = 0; it < SPIN; it++) {
    uint32_t bad = 0;
#pragma unroll
    for (int i = S; i < S + N; i++) bad |= (v[i].x ^ tag) | ((SPL && i % 7 == 3) ? (v[i].z ^ tag) : 0u);
    if (!__any_sync(~0u, bad & 1)) break;
    ll_issue<S, N, SPL>(v, p, stride, p2);
  }
}
__device__ __forceinline__ void hint_post(uint32_t* p, uint32_t v, int lane) {
  if (lane == 0) asm volatile("st.relaxed.gpu.global.u32 [%0], %1;" ::"l"(p), "r"(v) : "memory");
}
__device__ __forceinline__ void hint_wait(const uint32_t* p, uint32_t s, uint32_t v = 0xffffu) {
#pragma unroll 1
  for (int it = 0; it < SPIN; it++) {
    if (__all_sync(~0u, v - s < 10u)) break;
    v = hint_ld(p);
  }
}
__device__ __forceinline__ void slice_store(uint4* pf, uint2* ph, const uint32_t (&w)[14], bool odd) {
#pragma unroll
  for (int u = 0; u < 3; u++)
    stll(pf + u * 32, odd ? w[4 * u + 2] : w[4 * u], odd ? w[4 * u + 3] : w[4 * u + 1], odd ? w[4 * u + 4] : w[4 * u + 2], odd ? w[4 * u + 5] : w[4 * u + 3]);
  stll2(ph, odd ? w[0] : w[12], odd ? w[1] : w[13]);
}
template <class F, class M> __device__ __forceinline__ void hedgehog(const float (&d)[28], F sink, M mid) {
  const float L2E = 1.4426950408889634f;
#define HX(G, p) ((p) < 6 ? d[((G) & 1) * 16 + ((p) >> 1) * 4 + ((p) & 1) + ((G) & 2)] : d[12 + (G)])
  float mx[4], mn[4], sp[4], sn[4], ep[4][7], en[4][7];
#pragma unroll
  for (int G = 0; G < 4; G++) {
    mx[G] = mn[G] = HX(G, 0);
#pragma unroll
    for (int p = 1; p < 7; p++) { mx[G] = fmaxf(mx[G], HX(G, p)); mn[G] = fminf(mn[G], HX(G, p)); }
  }
#pragma unroll
  for (int o = 1; o < 4; o <<= 1)
#pragma unroll
    for (int G = 0; G < 4; G++) { mx[G] = fmaxf(mx[G], __shfl_xor_sync(~0u, mx[G], o)); mn[G] = fminf(mn[G], __shfl_xor_sync(~0u, mn[G], o)); }
#pragma unroll
  for (int G = 0; G < 4; G++) {
    const float a = -mx[G] * L2E, b = mn[G] * L2E;
#pragma unroll
    for (int p = 0; p < 7; p++) { ep[G][p] = ex2(fmaf(HX(G, p), L2E, a)); en[G][p] = ex2(fmaf(HX(G, p), -L2E, b)); }
    sp[G] = ((ep[G][0] + ep[G][1]) + (ep[G][2] + ep[G][3])) + ((ep[G][4] + ep[G][5]) + ep[G][6]);
    sn[G] = ((en[G][0] + en[G][1]) + (en[G][2] + en[G][3])) + ((en[G][4] + en[G][5]) + en[G][6]);
    if (G == 1) mid();
  }
#pragma unroll
  for (int o = 1; o < 4; o <<= 1)
#pragma unroll
    for (int G = 0; G < 4; G++) { sp[G] += __shfl_xor_sync(~0u, sp[G], o); sn[G] += __shfl_xor_sync(~0u, sn[G], o); }
#pragma unroll
  for (int G = 0; G < 4; G++) {
    const float a = rcp(sp[G]), b = rcp(sn[G]);
#pragma unroll
    for (int p = 0; p < 7; p++) sink(G >> 1, G & 1, p, pack(ep[G][p] * a, en[G][p] * b));
  }
}
__device__ __forceinline__ void phi_gemm(const float (&x)[28], float (&y)[28], uint32_t wphi, float r0, float r1) {
  uint32_t f[14];
#pragma unroll
  for (int j = 0; j < 14; j++) f[j] = pack(x[2 * j] * (j & 1 ? r1 : r0), x[2 * j + 1] * (j & 1 ? r1 : r0));
  wg_fence();
#pragma unroll
  for (int ks = 0; ks < 3; ks++) wgmma_rs56(y, f[4 * ks], f[4 * ks + 1], f[4 * ks + 2], f[4 * ks + 3], mkdesc(wphi, ks * 2048, 1024, 1024, 1), ks);
  wgmma_rs56(y, f[12], f[13], 0u, 0u, mkdesc(wphi, 3 * 2048, 1024, 1024, 1), 1);
  wg_commit();
}
__device__ __forceinline__ void ln_publish(uint32_t (&xw)[4][4], float* sLN, int warp, int lane, uint4* fb, uint32_t tag) {
  const int g = lane >> 2; const bool full = warp < 4;
  float s0 = 0.f, s1 = 0.f;
#pragma unroll
  for (int u = 0; u < 4; u++) {
    s0 += (blo(xw[u][0]) + bhi(xw[u][0])) + (blo(xw[u][2]) + bhi(xw[u][2]));
    s1 += (blo(xw[u][1]) + bhi(xw[u][1])) + (blo(xw[u][3]) + bhi(xw[u][3]));
  }
  const float rc = full ? 1.f / 64 : 1.f / 48;
  s0 = qsum(s0); s1 = qsum(s1);
  const float a0 = s0 * rc, a1 = s1 * rc;
  float v0 = 0.f, v1 = 0.f;
#pragma unroll
  for (int u = 0; u < 4; u++)
    if (u < 3 || full) {
#pragma unroll
      for (int k = 0; k < 4; k += 2) {
        float a = blo(xw[u][k]) - a0, b = bhi(xw[u][k]) - a0, c2 = blo(xw[u][k + 1]) - a1, d2 = bhi(xw[u][k + 1]) - a1;
        v0 += a * a + b * b; v1 += c2 * c2 + d2 * d2;
      }
    }
  v0 = qsum(v0); v1 = qsum(v1);
  if ((lane & 3) == 0) *(float4*)(sLN + (g * 8 + warp) * 4) = make_float4(s0, v0, s1, v1);
  bar_cons();
  const float4 ea = *(const float4*)(sLN + (g * 8 + (lane & 3)) * 4), eb = *(const float4*)(sLN + (g * 8 + 4 + (lane & 3)) * 4);
  const float m0 = qsum(ea.x + eb.x) * (1.f / 448), m1 = qsum(ea.z + eb.z) * (1.f / 448);
  const float d0 = ea.x * (1.f / 64) - m0, d1 = eb.x * (1.f / 48) - m0, d2 = ea.z * (1.f / 64) - m1, d3 = eb.z * (1.f / 48) - m1;
  v0 = qsum(ea.y + eb.y + 64.f * d0 * d0 + 48.f * d1 * d1); v1 = qsum(ea.w + eb.w + 64.f * d2 * d2 + 48.f * d3 * d3);
  const float r0 = rsqrtf(v0 * (1.f / 448) + 1e-5f), r1 = rsqrtf(v1 * (1.f / 448) + 1e-5f), n0 = -m0 * r0, n1 = -m1 * r1;
#pragma unroll
  for (int u = 0; u < 4; u++)
    if (u < 3 || full)
      stll(fb + XN + u * 256, tg(pack(fmaf(blo(xw[u][0]), r0, n0), fmaf(bhi(xw[u][0]), r0, n0)), tag), pack(fmaf(blo(xw[u][1]), r1, n1), fmaf(bhi(xw[u][1]), r1, n1)),
           pack(fmaf(blo(xw[u][2]), r0, n0), fmaf(bhi(xw[u][2]), r0, n0)), pack(fmaf(blo(xw[u][3]), r1, n1), fmaf(bhi(xw[u][3]), r1, n1)));
}

__global__ void CLUSTER __launch_bounds__(384, 1)
fused_kernel(const __grid_constant__ CUtensorMap mQKV, const __grid_constant__ CUtensorMap mWO, const __grid_constant__ CUtensorMap mW1,
             const __grid_constant__ CUtensorMap mW1b, const __grid_constant__ CUtensorMap mW2, const __grid_constant__ CUtensorMap mW2b,
             const __grid_constant__ CUtensorMap mX, const __nv_bfloat16* __restrict__ wqkv, const __nv_bfloat16* __restrict__ wphi,
             const __nv_bfloat16* __restrict__ wo, const __nv_bfloat16* __restrict__ w1, const __nv_bfloat16* __restrict__ b1,
             const __nv_bfloat16* __restrict__ w2, const __nv_bfloat16* __restrict__ b2, __nv_bfloat16* __restrict__ out) {
  extern __shared__ __align__(1024) uint8_t sm[];
  const uint32_t sb = s2u(sm);
  const int tid = threadIdx.x, warp = __shfl_sync(~0u, tid >> 5, 0), lane = tid & 31,
            t = MAPPING ? (blockIdx.x >> 4) * 2 + (blockIdx.x & 1) : blockIdx.x >> 3, c = MAPPING ? (blockIdx.x >> 1) & 7 : blockIdx.x & 7;
  const uint32_t bfull = sb + OFF_BAR, bempty = bfull + 8 * NST;

#define XOFF(l) ((t * 128 + c * 16 + ((l) >> 2)) * 448 + warp * 16 + 2 * ((l) & 3))
  if (warp < 8) MARK(0);
  if (tid == 256) {
    for (int s = 0; s < NST; s++) { mbar_init(bfull + 8 * s, 1); mbar_init(bempty + 8 * s, MC ? 16 : 8); }
    mbar_init(bempty + 8 * NST, 1);
    asm volatile("fence.mbarrier_init.release.cluster;" ::: "memory");
    fence_async();
    mbar_expect(bempty + 8 * NST, 114688);
    for (int i = 0; i < 7; i++)
      asm volatile("cp.async.bulk.tensor.2d.shared::cluster.global.mbarrier::complete_tx::bytes [%0], [%1, {%3, %4}], [%2];"
                   ::"r"(sb + 2 * STAGE + i * 16384), "l"(&mX), "r"(bempty + 8 * NST), "r"(64 * i), "r"(128 * t) : "memory");
  }
  asm volatile("barrier.cluster.arrive.release.aligned; barrier.cluster.wait.acquire.aligned;" ::: "memory");
  if (warp >= 8) {
    asm volatile("setmaxnreg.dec.sync.aligned.u32 24;");
    auto issue = [&](int i, int s) {
      const uint32_t dst = sb + s * STAGE, bar = bfull + 8 * s;
      mbar_expect(bar, STAGE);
#pragma unroll 1
      for (int rk = MC ? (blockIdx.x & 1) : 0; rk < (MC ? (blockIdx.x & 1) + 1 : 2); rk++)
      if (i < 4) tma2d(dst + rk * 14336, &mQKV, 448 + 448 * rk + 56 * c, 112 * i, bar);
      else if (i < 8) tma2d(dst + rk * 14336, i < 6 ? &mQKV : &mWO, (i < 6 ? 56 : 64) * c, 224 * (i & 1) + 112 * rk, bar);
      else if (i < 15) { const int k0 = 64 * ((i - 8 + c) % 7) + 32 * rk;
        tma3d(dst + rk * 12288, &mW1, 0, k0, 3 * c, bar); tma2d(dst + 24576 + rk * 2048, &mW1b, 1536 + 32 * c, k0, bar); }
      else { tma2d(dst + rk * 12288, &mW2, 64 * (i - 15), 192 * c + 96 * rk, bar); tma2d(dst + 24576 + rk * 2048, &mW2b, 64 * (i - 15), 1536 + 32 * c + 16 * rk, bar); }
    };
    if (warp == 8) {
      int s = 0; uint32_t ph = 1;
      for (int n = 0; n < 44; n++) {
        if (n == PACE) asm volatile("bar.sync 2, 288;" ::: "memory");
        mbar_wait(bempty + 8 * s, ph);
        if (n == 22) {
          uint32_t v = 0;
#pragma unroll 1
          for (int it = 0; it < SPIN && v < 32; it++) asm volatile("ld.acquire.gpu.global.u32 %0, [%1];" : "=r"(v) : "l"(g_WQF + c) : "memory");
          asm volatile("fence.proxy.async.global;" ::: "memory");
        }
        if (lane == 0) {
          if (n >= 22 && n < 28) {
            mbar_expect(bfull + 8 * s, STAGE);
            asm volatile("cp.async.bulk.shared::cluster.global.mbarrier::complete_tx::bytes [%0], [%1], %2, [%3];"
                         ::"r"(sb + s * STAGE), "l"(g_WQ + c * 10752 + (n - 22) * (STAGE / 16)), "r"(STAGE), "r"(bfull + 8 * s) : "memory");
          } else issue(n >= 22 ? n - 22 : n, s);
        }
        __syncwarp();
        if (++s == NST) { s = 0; ph ^= 1; }
      }
    } else if (warp == 9) {
      mbar_wait(bfull + 8 * 3, 0);
      if (lane == 0) {
        l2pf((const uint8_t*)wo + blockIdx.x * 3136, 3136);
        l2pf((const uint8_t*)w1 + blockIdx.x * 12544, 12544);
        l2pf((const uint8_t*)w2 + blockIdx.x * 12544, 12544);
      }
      if (blockIdx.x < 112) {
        const uint2* wp = (const uint2*)(w1 + (size_t)(lane >> 2) * 1792 + blockIdx.x * 16 + (lane & 3) * 4);
        float s0 = 0.f, s1 = 0.f, s2 = 0.f, s3 = 0.f;
#pragma unroll 8
        for (int i = 0; i < 56; i++) { const uint2 v = __ldg(wp + i * 8 * 448); s0 += blo(v.x); s1 += bhi(v.x); s2 += blo(v.y); s3 += bhi(v.y); }
#pragma unroll 1
        for (int o = 4; o < 32; o <<= 1) { s0 += __shfl_xor_sync(~0u, s0, o); s1 += __shfl_xor_sync(~0u, s1, o); s2 += __shfl_xor_sync(~0u, s2, o); s3 += __shfl_xor_sync(~0u, s3, o); }
        if (lane < 4) stll(g_CS + blockIdx.x * 4 + lane, tg(__float_as_uint(s0), 1), __float_as_uint(s1), __float_as_uint(s2), __float_as_uint(s3));
      }
      asm volatile("bar.sync 6, 96;" ::: "memory");
#pragma unroll 1
      for (int i = 0; i < 2; i++) {
        const int e = lane < 28 ? lane + 28 * i : 0;
        uint4 cv[1];
        const int e4 = e < 48 ? 48 * c + e : 336 + 8 * c + e;
        ll_issue<0, 1>(cv, g_CS + e4, 0); ll_check<0, 1, false>(cv, g_CS + e4, 0, 1u);
        const uint2 bb = __ldg((const uint2*)b1 + e4);
        const uint32_t h0 = pack(__uint_as_float(cv[0].x), __uint_as_float(cv[0].y)), h1 = pack(__uint_as_float(cv[0].z), __uint_as_float(cv[0].w));
        const uint32_t l0 = pack(__uint_as_float(cv[0].x) - blo(h0), __uint_as_float(cv[0].y) - bhi(h0)), l1 = pack(__uint_as_float(cv[0].z) - blo(h1), __uint_as_float(cv[0].w) - bhi(h1));
#pragma unroll 1
        for (int r = 0; r < 8; r++) {
          const uint32_t ad = sb + OFF_CB + (e >> 3) * 512 + r * 64 + ((((e >> 1) ^ (r >> 1)) & 3) << 4) + (e & 1) * 8;
          sts32(ad, r < 2 ? h0 : r == 2 ? l0 : r < 5 ? bb.x : 0u); sts32(ad + 4, r < 2 ? h1 : r == 2 ? l1 : r < 5 ? bb.y : 0u);
        }
      }
      fence_async();
      asm volatile("bar.arrive 4, 288;" ::: "memory");
    } else if (warp >= 10) {
      const int h = warp - 10;
      uint32_t wv[13];
#pragma unroll
      for (int i = 0; i < 13; i++) { const int e = lane + 32 * i; wv[i] = e < 392 ? __ldg((const uint32_t*)wphi + (2 * c + h) * 392 + e) : 0u; }
#pragma unroll 1
      for (int i = 0; i < 8; i++) sts128(sb + OFF_WPHI + (h * 256 + i * 32 + lane) * 16, 0, 0, 0, 0);
      asm volatile("bar.arrive 6, 96;" ::: "memory");
#pragma unroll 1
      for (int i = 0; i < 4; i++) sts128(sb + OFF_PHIK + sw128(h * 128 + i * 32 + lane, 56), 0, 0, 0, 0);
      asm volatile("bar.sync 5, 64;" ::: "memory");
#pragma unroll
      for (int i = 0; i < 13; i++) {
        const int e = lane + 32 * i, d = e / 14, f2 = 2 * (e - 14 * d), k = 28 * h + d;
        if (e < 392) {
          if (f2 < 24) sts32(sb + OFF_WPHI + sw128(k, 32 * h + f2), wv[i]);
          else { sts16(sb + OFF_WPHI + sw128(k, 2 * f2 - 24 + h), wv[i]); sts16(sb + OFF_WPHI + sw128(k, 2 * f2 - 22 + h), wv[i] >> 16); }
        }
      }
      fence_async();
      asm volatile("bar.arrive 3, 320;" ::: "memory");
      mbar_wait(bfull + 8 * 5, 0);
#pragma unroll 2
      for (int e = t * 672 + h * 32 + lane; e < t * 672 + 672; e += 64) {
        const int r = e >> 3, st = r / 224, rr = r - st * 224, ch = (e & 7) ^ (rr & 7);
        const int k = st < 4 ? 112 * st + (rr >= 112 ? rr - 112 : rr) : 224 * (st - 4) + rr, col = (st < 4 ? (rr >= 112 ? 896 : 448) : 0) + 56 * c + 8 * ch;
        g_WQ[c * 10752 + e] = ch < 7 ? __ldg((const uint4*)(wqkv + k * 1344 + col)) : make_uint4(0, 0, 0, 0);
      }
      __syncwarp();
      if (lane == 0) asm volatile("red.release.gpu.global.add.u32 [%0], 1;" ::"l"(g_WQF + c) : "memory");
    }
  } else {
  asm volatile("setmaxnreg.inc.sync.aligned.u32 240;");

  const int wg = warp >> 2, g = lane >> 2, q = lane & 3;
  const int row0 = warp * 16 + g;
#define PTRS const int ln_ = laneid(); \
  uint4* const fm = g_F + ((t * 8 + warp) * 28) * 32 + ln_;            \
  uint4* const fr = g_F + ((t * 8 + c) * 28 + warp) * 32 + ln_;        \
  uint4* const sf = fm + (7 * (c >> 1) + 4 * (c & 1)) * 32;             \
  uint2* const f2 = (uint2*)(fm - ln_) + ln_;                           \
  uint2* const sh = f2 + (7 * (c >> 1) + 3) * 64 + 32 * (c & 1);        \
  uint32_t* const hme = g_H + (t * 8 + warp) * 8 + c; \
  const uint32_t* const hrow = g_H + (t * 8 + warp) * 8 + (ln_ & 7); \
  (void)fm; (void)fr; (void)sf; (void)f2; (void)sh; (void)hme; (void)hrow;
  float* sLN = (float*)(sm + OFF_V);
  const uint32_t sPK = sb + OFF_PHIK, sV = sb + OFF_V, d16 = (sb & 0x3FFFF) >> 4;
    uint32_t xw[4][4];
#pragma unroll
  for (int i = 0; i < 16; i++) xw[i >> 2][i & 3] = 0;
  int cs = 0, rs = 0; uint32_t cph = 0;
  auto acquire = [&]() -> uint32_t { mbar_wait(bfull + 8 * cs, cph); const uint32_t a = d16 + cs * (STAGE >> 4); if (++cs == NST) { cs = 0; cph ^= 1; } return a; };
  int nrel = 44 - NST;
  auto release = [&]() { if (lane < 1 + MC && nrel > 0) mbar_arrive_cl(bempty + 8 * rs, lane); nrel--; if (++rs == NST) rs = 0; };

#pragma unroll 1
  for (int L = 0; L < 2; L++) {
    const uint32_t tag = 1 - L;
    uint32_t phq[2][2][7];
    const uint32_t hs = 10 * L;
    {
      PTRS
      uint4 a[28];
      const uint4* pa = fm + XN;
      const uint32_t xtag = 1;
      float r0 = 1.f, r1 = 1.f;
      if (L == 0) {
        mbar_wait(bempty + 8 * NST, 0);
        MARK(1);
        const int row = warp * 16 + (ln_ & 15);
        const uint32_t xb = sb + 2 * STAGE + row * 128;
        float cs_[4][4] = {}, c0[2][4] = {}, c1[2][4] = {};
#pragma unroll
        for (int ks = 0; ks < 28; ks++) { a[ks] = ldsm4(xb + (ks >> 2) * 16384 + (((2 * (ks & 3) + (ln_ >> 4)) ^ (row & 7)) << 4)); mma16816(cs_[ks & 3], a[ks], 0x3F803F80u, 0x3F803F80u); }
        if (c < 7) {
#pragma unroll
          for (int u = 0; u < 4; u++) { const uint4 v = ldsm4(xb + c * 16384 + (((2 * u + (ln_ >> 4)) ^ (row & 7)) << 4)); stll(fm + XR + 128 * c + u * 32, tg(v.x, tag), v.y, v.z, v.w); }
        }
        const float m0 = ((cs_[0][0] + cs_[1][0]) + (cs_[2][0] + cs_[3][0])) * (1.f / 448), m1 = ((cs_[0][2] + cs_[1][2]) + (cs_[2][2] + cs_[3][2])) * (1.f / 448);
        const uint32_t mb0 = pack(m0, m0), mb1 = pack(m1, m1);
        asm volatile("bar.arrive 2, 288;" ::"r"(mb0) : "memory");
#pragma unroll
        for (int ks = 0; ks < 28; ks++) {
          a[ks].x = bsub(a[ks].x, mb0); a[ks].y = bsub(a[ks].y, mb1); a[ks].z = bsub(a[ks].z, mb0); a[ks].w = bsub(a[ks].w, mb1);
          mma16816(c0[ks & 1], a[ks], a[ks].x, a[ks].z); mma16816(c1[ks & 1], a[ks], a[ks].y, a[ks].w);
        }
        const int src = (ln_ & 28) | (g >> 1);
        const float q0 = __shfl_sync(~0u, (g & 1) ? c0[0][1] + c0[1][1] : c0[0][0] + c0[1][0], src), q1 = __shfl_sync(~0u, (g & 1) ? c1[0][3] + c1[1][3] : c1[0][2] + c1[1][2], src);
        const float e0 = m0 - blo(mb0), e1 = m1 - blo(mb1);
        r0 = rsqrtf(fmaxf(q0 * (1.f / 448) - e0 * e0, 0.f) + 1e-5f); r1 = rsqrtf(fmaxf(q1 * (1.f / 448) - e1 * e1, 0.f) + 1e-5f);
      } else {
        ln_publish(xw, sLN, warp, lane, fr, xtag);
        hint_post(hme, hs + 1, lane);
#pragma unroll
        for (int u = 0; u < 4; u++) if (u < 3 || wg == 0) stll(fr + XR + u * 256, tg(xw[u][0], tag), xw[u][1], xw[u][2], xw[u][3]);
        MARK(20);
        hint_wait(g_H + (t * 8 + (ln_ & 7)) * 8 + warp, hs + 1); ll_issue<0, 28>(a, pa, 32);
      }
      MARK(2 + L * 19);
      float ak[28], av[28], aq[28], pp[28];
#define KVSTAGE(i) { if (L) ll_check<7 * i, 7, false>(a, pa, 32, xtag); const uint32_t st = acquire(); wg_fence(); \
      _Pragma("unroll") for (int ks = 0; ks < 7; ks++) { const uint4 f = a[7 * i + ks]; \
        wgmma_rs56(ak, f.x, f.y, f.z, f.w, mkdesc(st, ks * 2048, 1024, 1024, 1), i | ks); \
        wgmma_rs56(av, f.x, f.y, f.z, f.w, mkdesc(st, 14336 + ks * 2048, 1024, 1024, 1), i | ks); } \
      wg_commit(); if (i > 0) { wg_wait<1>(); release(); } }
      KVSTAGE(0) KVSTAGE(1) KVSTAGE(2) KVSTAGE(3)
      wg_wait<0>(); release(); regfence(ak); regfence(av);
      MARK(3 + L * 19);
      if (L == 0) asm volatile("bar.sync 3, 320;" ::: "memory");
      phi_gemm(ak, pp, d16 + (OFF_WPHI >> 4), r0, r1);
#pragma unroll
      for (int j = 0; j < 7; j++) {
        const int n = 8 * j + 2 * q, n2 = n < 28 ? n : n + 4;
        sts32(sV + sw128(row0, n2), pack(av[4 * j] * r0, av[4 * j + 1] * r0)); sts32(sV + sw128(row0 + 8, n2), pack(av[4 * j + 2] * r1, av[4 * j + 3] * r1));
      }
      { const int n2 = 28 + 2 * (q & 1) + 32 * (q >> 1); const uint32_t v = (q & 1) ? 0u : 0x3F80u; sts32(sV + sw128(row0, n2), v); sts32(sV + sw128(row0 + 8, n2), v); }
      wg_wait<0>(); regfence(pp);
      hedgehog(pp, [&](int r, int h, int p, uint32_t v) { sts32(sPK + h * 16384 + sw128(row0 + 8 * r, 8 * p + 2 * q), v); }, [] {});
      fence_async();
      bar_cons();
      MARK(4 + L * 19);
      float kv[16];
      wg_fence();
#pragma unroll
      for (int ks = 0; ks < 8; ks++) wgmma_ss32(kv, mkdesc(d16 + wg * 1024, OFF_PHIK + ks * 2048, 1024, 1024, 1), mkdesc(d16 + wg * 4, OFF_V + ks * 2048, 1024, 1024, 1), ks);
      wg_commit(); wg_wait<0>(); regfence(kv);
      const int ln2 = laneid();
#pragma unroll
      for (int u = 0; u < 4; u++) {
        float e[4];
#pragma unroll
        for (int i = 0; i < 4; i++) e[i] = kv[4 * u + i];
        stll(g_KVP + (c * 16 + t) * 1024 + wg * 512 + u * 128 + (warp & 3) * 32 + ln2, tg(__float_as_uint(e[0]), tag), __float_as_uint(e[1]), __float_as_uint(e[2]), __float_as_uint(e[3]));
      }
      MARK(5 + L * 19);
      uint4 k4[4];
      const uint4* pk = g_KVP + (c * 16 + 4 * (ln2 & 3)) * 1024 + 64 * t + warp * 8 + (ln2 >> 2);
#pragma unroll
      for (int i = 0; i < 2; i++) {
        const uint32_t st = acquire(); wg_fence();
#pragma unroll
        for (int ks = 0; ks < 14; ks++) { const uint4 f = a[14 * i + ks]; wgmma_rs56(aq, f.x, f.y, f.z, f.w, mkdesc(st, ks * 2048, 1024, 1024, 1), i | ks); }
        wg_commit();
        if (i == 0) ll_issue<0, 4>(k4, pk, 1024);
      }
      ll_check<0, 4, false>(k4, pk, 1024, tag);
      float s0 = 0, s1 = 0, s2 = 0, s3 = 0;
#pragma unroll
      for (int i = 0; i < 4; i++) { s0 += __uint_as_float(k4[i].x); s1 += __uint_as_float(k4[i].y); s2 += __uint_as_float(k4[i].z); s3 += __uint_as_float(k4[i].w); }
      s0 = qsum(s0); s1 = qsum(s1); s2 = qsum(s2); s3 = qsum(s3);
      if (q == 0) stll2(g_KVR + c * 1024 + 64 * t + warp * 8 + (ln2 >> 2), tg(pack(s0, s1), tag), pack(s2, s3));
      MARK(6 + L * 19);
      wg_wait<0>(); release(); release(); regfence(aq);
      phi_gemm(aq, pp, d16 + (OFF_WPHI >> 4), r0, r1);
      bar_cons();
#pragma unroll
      for (int i = 0; i < 4; i++) sts128(sV + warp * 2048 + (lane + i * 32) * 16, 0, 0, 0, 0);
      wg_wait<0>(); regfence(pp);
      uint2 r[4];
      const uint2* pr = g_KVR + c * 1024 + wg * 512 + (warp & 3) * 32 + ln2;
      hedgehog(pp, [&](int r, int h, int p, uint32_t v) { phq[r][h][p] = v; }, [&] {
#pragma unroll
        for (int u = 0; u < 4; u++) r[u] = ldll2(pr + u * 128); });
      MARK(7 + L * 19);
#pragma unroll 1
      for (int it = 0; it < SPIN; it++) {
        if (!__any_sync(~0u, ((r[0].x ^ tag) | (r[1].x ^ tag) | (r[2].x ^ tag) | (r[3].x ^ tag)) & 1)) break;
#pragma unroll
        for (int u = 0; u < 4; u++) r[u] = ldll2(pr + u * 128);
      }
#pragma unroll
      for (int u = 0; u < 4; u++) {
        const int d = 8 * u + 2 * q;
        if (d < 28) { sts32(sV + sw128(row0, 28 * wg + d), r[u].x); sts32(sV + sw128(row0 + 8, 28 * wg + d), r[u].y); }
        else if (d == 28) {
#pragma unroll
          for (int j = 0; j < 4; j++) { sts16(sV + sw128(row0, 56 + 2 * j + wg), r[u].x); sts16(sV + sw128(row0 + 8, 56 + 2 * j + wg), r[u].y); }
        }
      }
      fence_async();
      bar_cons();
      MARK(8 + L * 19);
      float o[32];
      wg_fence();
#pragma unroll
      for (int ks = 0; ks < 8; ks++) {
        const int h = ks >> 2, p = 2 * (ks & 3);
        wgmma_rs64(o, phq[0][h][p], phq[1][h][p], p < 6 ? phq[0][h][p < 6 ? p + 1 : 0] : 0u, p < 6 ? phq[1][h][p < 6 ? p + 1 : 0] : 0u, mkdesc(d16, OFF_V + ks * 2048, 1024, 1024, 1), ks);
      }
      wg_commit(); wg_wait<0>(); regfence(o);
      const float iA0 = rcp(o[28] + 1e-6f), iB0 = rcp(o[29] + 1e-6f), iA1 = rcp(o[30] + 1e-6f), iB1 = rcp(o[31] + 1e-6f);
      uint32_t w[14];
      { PTRS
#pragma unroll
      for (int j = 0; j < 7; j++) {
        const bool hb = 8 * j + 2 * q >= 28; const float i0 = hb ? iB0 : iA0, i1 = hb ? iB1 : iA1;
        w[2 * j] = pack(o[4 * j] * i0, o[4 * j + 1] * i0); w[2 * j + 1] = pack(o[4 * j + 2] * i1, o[4 * j + 3] * i1);
        if (j == 0 || ((j ^ c) & 1) == 0) w[2 * j] = tg(w[2 * j], tag);
      }
      slice_store(sf + OO, sh + 2 * OO, w, c & 1);
      hint_post(hme, hs + 2, lane); }
    }
    MARK(9 + L * 19);
    uint4 xr[4];
    if (c < 7) {
      PTRS
      ll_issue<0, 4>(xr, fm + XR + 128 * c, 32);
      uint4 a[28];
      const uint4* pa = fm + OO;
      hint_wait(hrow, hs + 2);
      MARK(10 + L * 19);
      ll_issue<0, 28, true>(a, pa, 32, f2 + 2 * OO);
      float y[32];
      uint32_t st;
#define WOSTEP(i) { ll_check<7 * i, 7, true>(a, pa, 32, tag, f2 + 2 * OO); if (!(i & 1)) st = acquire(); wg_fence(); \
      _Pragma("unroll") for (int ks = 0; ks < 7; ks++) { const uint4 f = a[7 * i + ks]; \
        wgmma_rs64(y, f.x, f.y, f.z, f.w, mkdesc(st, ((i & 1) * 7 + ks) * 2048, 1024, 1024, 1), i | ks); } wg_commit(); }
      WOSTEP(0) WOSTEP(1) WOSTEP(2) WOSTEP(3)
      ll_check<0, 4, false>(xr, fm + XR + 128 * c, 32, tag);
      wg_wait<0>(); regfence(y);
      MARK(11 + L * 19);
#pragma unroll
      for (int u = 0; u < 4; u++) {
        xr[u].x = tg(pack(blo(xr[u].x) + y[8 * u], bhi(xr[u].x) + y[8 * u + 1]), tag); xr[u].y = pack(blo(xr[u].y) + y[8 * u + 2], bhi(xr[u].y) + y[8 * u + 3]);
        xr[u].z = pack(blo(xr[u].z) + y[8 * u + 4], bhi(xr[u].z) + y[8 * u + 5]); xr[u].w = pack(blo(xr[u].w) + y[8 * u + 6], bhi(xr[u].w) + y[8 * u + 7]);
        stll(fm + X1 + 128 * c + u * 32, xr[u].x, xr[u].y, xr[u].z, xr[u].w);
      }
      hint_post(hme, hs + 3, lane);
    } else {
      PTRS
      hint_post(hme, hs + 3, lane);
      acquire(); acquire();
      hint_wait(g_H + (t * 8 + warp) * 8, hs + 3);
      ll_issue<0, 4>(xr, fm + X1, 32); ll_check<0, 4, false>(xr, fm + X1, 32, tag);
      MARK(10 + L * 19); MARK(11 + L * 19);
    }
    uint32_t hf[56];
    float rr0, rr1;
    {
      PTRS
      uint4 a[28];
      const uint4* pa = fm + X1;
      auto grp = [&](int i) -> const uint4* { const int k = i + c; return pa + ((k >= 7 ? k - 7 : k) - i) * 128; };
#pragma unroll
      for (int u = 0; u < 4; u++) a[u] = xr[u];
      float y[96], z[16];
#define F1STAGE(i) { if (i > 0) ll_check<4 * i, 4, false>(a, grp(i), 32, tag); const uint32_t st = acquire(); wg_fence(); \
      _Pragma("unroll") for (int ks = 0; ks < 4; ks++) { const uint4 f = a[4 * i + ks]; \
        wgmma_rs192(y, f.x, f.y, f.z, f.w, mkdesc(st, (ks >> 1) * 12288 + (ks & 1) * 2048, 4096, 1024, 1), i | ks); \
        wgmma_rs32(z, f.x, f.y, f.z, f.w, mkdesc(st, 24576 + ks * 1024, 512, 512, 2), i | ks); } \
      wg_commit(); if (i > 0) { wg_wait<1>(); release(); if (i < 4) ll_issue<(i < 4 ? 4 * i + 12 : 0), 4>(a, grp(i + 3), 32); } }
      F1STAGE(0)
      hint_wait(hrow, hs + 3);
      MARK(12 + L * 19);
      ll_issue<4, 4>(a, grp(1), 32); ll_issue<8, 4>(a, grp(2), 32); ll_issue<12, 4>(a, grp(3), 32);
      if (c < 7) {
        float s0 = 0.f, s1 = 0.f, v0 = 0.f, v1 = 0.f;
#pragma unroll
        for (int u = 0; u < 4; u++) { s0 += (blo(xr[u].x) + bhi(xr[u].x)) + (blo(xr[u].z) + bhi(xr[u].z)); s1 += (blo(xr[u].y) + bhi(xr[u].y)) + (blo(xr[u].w) + bhi(xr[u].w)); }
        s0 = qsum(s0) * (1.f / 64); s1 = qsum(s1) * (1.f / 64);
#pragma unroll
        for (int u = 0; u < 4; u++) {
          const float d0 = blo(xr[u].x) - s0, d1 = bhi(xr[u].x) - s0, d2 = blo(xr[u].z) - s0, d3 = bhi(xr[u].z) - s0;
          const float d4 = blo(xr[u].y) - s1, d5 = bhi(xr[u].y) - s1, d6 = blo(xr[u].w) - s1, d7 = bhi(xr[u].w) - s1;
          v0 += (d0 * d0 + d1 * d1) + (d2 * d2 + d3 * d3); v1 += (d4 * d4 + d5 * d5) + (d6 * d6 + d7 * d7);
        }
        v0 = qsum(v0); v1 = qsum(v1);
        if (q == 0) stll(g_ST + ((t * 8 + warp) * 8 + c) * 8 + (ln_ >> 2), tg(__float_as_uint(s0), tag), __float_as_uint(v0), __float_as_uint(s1), __float_as_uint(v1));
      }
      release(); release();
      F1STAGE(1) MARK(13 + L * 19); F1STAGE(2) F1STAGE(3)
      uint4 sv[2];
      const uint4* ps = g_ST + ((t * 8 + warp) * 8 + 2 * (laneid() & 3)) * 8 + (laneid() >> 2);
      ll_issue<0, 2>(sv, ps, q < 3 ? 8 : 0);
      F1STAGE(4)
      ll_check<0, 2, false>(sv, ps, q < 3 ? 8 : 0, tag);
      const float wb = q < 3 ? 1.f : 0.f;
      const float ma = __uint_as_float(sv[0].x), mb = __uint_as_float(sv[1].x), mc = __uint_as_float(sv[0].z), md = __uint_as_float(sv[1].z);
      const float m0 = qsum(ma + wb * mb) * (1.f / 7), m1 = qsum(mc + wb * md) * (1.f / 7);
      const float v0 = qsum(__uint_as_float(sv[0].y) + 64.f * (ma - m0) * (ma - m0) + wb * (__uint_as_float(sv[1].y) + 64.f * (mb - m0) * (mb - m0)));
      const float v1 = qsum(__uint_as_float(sv[0].w) + 64.f * (mc - m1) * (mc - m1) + wb * (__uint_as_float(sv[1].w) + 64.f * (md - m1) * (md - m1)));
      const float e0 = v0 * (1.f / 448) + 1e-5f, e1 = v1 * (1.f / 448) + 1e-5f;
      rr0 = 1.f / e0; rr1 = 1.f / e1;
      auto fold = [&](float m, float sd) -> uint32_t {
        const float mh = blo(pack(-m, 0.f)), sh_ = blo(pack(sd, 0.f));
        return q == 0 ? pack(mh, -m - mh) : q == 1 ? pack(mh, sh_) : q == 2 ? pack(sd - sh_, 0.f) : 0u;
      };
      const uint32_t fa = fold(m0, sqrtf(e0)), fb = fold(m1, sqrtf(e1));
      if (L == 0) asm volatile("bar.sync 4, 288;" ::: "memory");
      wg_fence();
      wgmma_rs192(y, fa, fb, 0u, 0u, mkdesc(d16, OFF_CB + 0, 512, 0, 2), 1);
      wgmma_rs32(z, fa, fb, 0u, 0u, mkdesc(d16, OFF_CB + 3072, 512, 0, 2), 1);
      F1STAGE(5) F1STAGE(6)
      wg_wait<0>(); release(); regfence(y); regfence(z);
      MARK(14 + L * 19);
#pragma unroll
      for (int j = 0; j < 56; j++) {
        uint32_t r; asm("cvt.rn.relu.bf16x2.f32 %0, %1, %2;" : "=r"(r) : "f"(j < 48 ? y[j < 48 ? 2 * j + 1 : 0] : z[j < 48 ? 0 : 2 * j - 95]), "f"(j < 48 ? y[j < 48 ? 2 * j : 0] : z[j < 48 ? 0 : 2 * j - 96]));
        asm("mul.bf16x2 %0, %1, %1;" : "=r"(hf[j]) : "r"(r));
      }
    }
    MARK(15 + L * 19);
    {
      PTRS
      float ya[32], yb[32];
      uint4* pp = g_P + ((t * 8 + warp) * 8 + c) * 28 * 32 + ln_;
#define F2STORE(j, Y) { regfence(Y); _Pragma("unroll") for (int u = 0; u < 4; u++) \
      stll(pp + (4 * (j) + u) * 32, tg(pack(Y[8 * u] * rr0, Y[8 * u + 1] * rr0), tag), pack(Y[8 * u + 2] * rr1, Y[8 * u + 3] * rr1), \
           pack(Y[8 * u + 4] * rr0, Y[8 * u + 5] * rr0), pack(Y[8 * u + 6] * rr1, Y[8 * u + 7] * rr1)); if ((j) >= 5) hint_post(hme, hs + (4 + (j)), lane); }
#define F2PASS(j, Y, Z) { const uint32_t st = acquire(); wg_fence(); \
      _Pragma("unroll") for (int ks = 0; ks < 14; ks++) wgmma_rs64(Y, hf[4 * ks], hf[4 * ks + 1], hf[4 * ks + 2], hf[4 * ks + 3], mkdesc(st, ks * 2048, 1024, 1024, 1), ks); \
      wg_commit(); if (j > 0) { wg_wait<1>(); release(); F2STORE(j - 1, Z) } }
      const uint4* pr = g_P + ((t * 8 + c) * 8 * 28 + warp) * 32 + ln_;
      uint4 p[8], p2[8]; uint2 xa, xb, xc, xd; uint32_t ba, bb, bc, bd;
#define RISSUE(m, P, XA, XB, BA, BB) { ll_issue<0, 8>(P, pr + (m) * 256, 896); \
      { const uint4 v_ = ldll(fr + X1 + (m) * 256); XA = make_uint2(v_.x, v_.y); XB = make_uint2(v_.z, v_.w); } \
      const uint32_t* bp = (const uint32_t*)(b2 + 128 * (m) + 16 * warp) + (ln_ & 3); BA = __ldg(bp); BB = __ldg(bp + 4); }
#define REDU(m, P, XA, XB, BA, BB) { ll_check<0, 8, false>(P, pr + (m) * 256, 896, tag); \
      float e[8] = {blo(XA.x) + blo(BA), bhi(XA.x) + bhi(BA), blo(XA.y) + blo(BA), bhi(XA.y) + bhi(BA), blo(XB.x) + blo(BB), bhi(XB.x) + bhi(BB), blo(XB.y) + blo(BB), bhi(XB.y) + bhi(BB)}; \
      _Pragma("unroll") for (int i = 0; i < 8; i++) { e[0] += blo(P[i].x); e[1] += bhi(P[i].x); e[2] += blo(P[i].y); e[3] += bhi(P[i].y); \
        e[4] += blo(P[i].z); e[5] += bhi(P[i].z); e[6] += blo(P[i].w); e[7] += bhi(P[i].w); } \
      xw[m][0] = pack(e[0], e[1]); xw[m][1] = pack(e[2], e[3]); xw[m][2] = pack(e[4], e[5]); xw[m][3] = pack(e[6], e[7]); }
      const uint32_t* hred = g_H + (t * 8 + c) * 8 + (ln_ & 7);
      F2PASS(0, ya, yb) F2PASS(1, yb, ya) F2PASS(2, ya, yb) F2PASS(3, yb, ya)
      F2PASS(4, ya, yb)
      RISSUE(0, p, xa, xb, ba, bb)
      F2PASS(5, yb, ya)
      REDU(0, p, xa, xb, ba, bb)
      F2PASS(6, ya, yb)
      RISSUE(1, p, xa, xb, ba, bb)
      wg_wait<0>(); release(); F2STORE(6, ya)
      MARK(16 + L * 19);
      if (wg) hint_wait(hred, hs + 9);
      RISSUE(2, p2, xc, xd, bc, bd)
      REDU(1, p, xa, xb, ba, bb)
      if (wg == 0) { hint_wait(hred, hs + 10); RISSUE(3, p, xa, xb, ba, bb) }
      MARK(17 + L * 19);
      REDU(2, p2, xc, xd, bc, bd)
      if (wg == 0) REDU(3, p, xa, xb, ba, bb) else { xw[3][0] = xw[3][1] = xw[3][2] = xw[3][3] = 0; }
    }
    MARK(18 + L * 19);
  }
  {
    uint32_t* op = (uint32_t*)(out + XOFF(laneid()));
#pragma unroll
    for (int u = 0; u < 4; u++) if (u < 3 || wg == 0) { op[u * 64] = xw[u][0]; op[u * 64 + 1792] = xw[u][1]; op[u * 64 + 4] = xw[u][2]; op[u * 64 + 1796] = xw[u][3]; }
    PTRS
#pragma unroll
    for (int u = 0; u < 4; u++) if (u < 3 || wg == 0) stll(fr + XN + u * 256, 0, 0, 0, 0);
    if (t == 0 && tid == 0) g_WQF[c] = 0;
    if (warp == 7 && blockIdx.x < 112 && lane < 4) stll(g_CS + blockIdx.x * 4 + lane, 0, 0, 0, 0);
  }
  MARK(38);
  }
}

typedef CUresult (*EncFn)(CUtensorMap*, CUtensorMapDataType, cuuint32_t, void*, const cuuint64_t*, const cuuint64_t*, const cuuint32_t*, const cuuint32_t*,
                          CUtensorMapInterleave, CUtensorMapSwizzle, CUtensorMapL2promotion, CUtensorMapFloatOOBfill);

extern "C" void kernel_launch(void* const* d_in, const int* in_sizes, int n_in, void* d_out, int out_size) {
  static EncFn enc = nullptr;
  if (!enc) {
    void* fn = nullptr; cudaDriverEntryPointQueryResult qr;
    cudaGetDriverEntryPoint("cuTensorMapEncodeTiled", &fn, cudaEnableDefault, &qr);
    enc = (EncFn)fn;
    cudaFuncSetAttribute(fused_kernel, cudaFuncAttributeMaxDynamicSharedMemorySize, SMEM_BYTES);
  }
  CUtensorMap mQKV, mWO, mW1, mW1b, mW2, mW2b, mX;
  const cuuint32_t es[3] = {1, 1, 1};
  auto enc2 = [&](CUtensorMap* m, void* p, cuuint64_t cols, cuuint64_t rows, cuuint32_t bc, cuuint32_t br) {
    const cuuint64_t dims[2] = {cols, rows}, str[1] = {cols * 2}; const cuuint32_t box[2] = {bc, br};
    enc(m, CU_TENSOR_MAP_DATA_TYPE_BFLOAT16, 2, p, dims, str, box, es, CU_TENSOR_MAP_INTERLEAVE_NONE,
        bc == 64 ? CU_TENSOR_MAP_SWIZZLE_128B : CU_TENSOR_MAP_SWIZZLE_64B, CU_TENSOR_MAP_L2_PROMOTION_L2_128B, CU_TENSOR_MAP_FLOAT_OOB_FILL_NONE);
  };
  enc2(&mQKV, d_in[1], 1344, 448, 64, 112); enc2(&mWO, d_in[3], 448, 448, 64, 112); enc2(&mW1b, d_in[5], 1792, 448, 32, 32);
  enc2(&mX, d_in[0], 448, 2048, 64, 128);
  enc2(&mW2, d_in[7], 448, 1792, 64, 96); enc2(&mW2b, d_in[7], 448, 1792, 64, 16);
  {
    const cuuint64_t dims[3] = {64, 448, 28}, str[2] = {3584, 128}; const cuuint32_t box[3] = {64, 32, 3};
    enc(&mW1, CU_TENSOR_MAP_DATA_TYPE_BFLOAT16, 3, d_in[5], dims, str, box, es, CU_TENSOR_MAP_INTERLEAVE_NONE, CU_TENSOR_MAP_SWIZZLE_128B,
        CU_TENSOR_MAP_L2_PROMOTION_L2_128B, CU_TENSOR_MAP_FLOAT_OOB_FILL_NONE);
  }
  typedef const __nv_bfloat16* BP;
  fused_kernel<<<128, 384, SMEM_BYTES>>>(mQKV, mWO, mW1, mW1b, mW2, mW2b, mX, (BP)d_in[1], (BP)d_in[2], (BP)d_in[3], (BP)d_in[5], (BP)d_in[6], (BP)d_in[7], (BP)d_in[8],
                                         (__nv_bfloat16*)d_out);
}
```

```cpp
#include <cuda_runtime.h>
#include <cuda_bf16.h>
#include <cuda.h>
#include <stdint.h>

constexpr int NST = 6, STAGE = 28672;
constexpr int OFF_PHIK = NST * STAGE;
constexpr int OFF_V = OFF_PHIK + 32768;
constexpr int OFF_WPHI = OFF_V + 16384;
constexpr int OFF_CB = OFF_WPHI + 7168;
constexpr int OFF_BAR = OFF_CB + 3584;
constexpr int SMEM_BYTES = OFF_BAR + 16 * NST + 8;
constexpr int FR = 16 * 8 * 28 * 32;
constexpr int SPIN = 1 << 18;
#define MC 0
#define MAPPING MC
#define MCS
#define MCA(n)
#define CLUSTER
#define PACE 2

__device__ uint4 g_F[3 * FR];
constexpr int XR = 0, OO = FR, X1 = 2 * FR;
__device__ uint4 g_P[8 * FR];
__device__ uint4 g_ST[16 * 8 * 8 * 8];
__device__ uint4 g_KVP[8 * 16 * 1024];
__device__ uint2 g_KVR[8 * 1024];
__device__ uint4 g_CS[784];
__device__ uint4 g_S2[16 * 8 * 8];
__device__ uint4 g_WQ[8 * 6 * (STAGE / 16)];
__device__ uint32_t g_WQF[8];
__device__ uint32_t g_H[16 * 8 * 8];
#define MARK(i)
#define GT(i)

__device__ __forceinline__ uint32_t s2u(const void* p) { return (uint32_t)__cvta_generic_to_shared(p); }
__device__ __forceinline__ void mbar_init(uint32_t b, uint32_t c) { asm volatile("mbarrier.init.shared::cta.b64 [%0], %1;" ::"r"(b), "r"(c)); }
__device__ __forceinline__ void mbar_expect(uint32_t b, uint32_t tx) { asm volatile("mbarrier.arrive.expect_tx.shared::cta.b64 _, [%0], %1;" ::"r"(b), "r"(tx) : "memory"); }
__device__ __forceinline__ void mbar_arrive_cl(uint32_t b, uint32_t rank) {
  asm volatile("{.reg .b32 r; mapa.shared::cluster.u32 r, %0, %1; mbarrier.arrive.shared::cluster.b64 _, [r];}" ::"r"(b), "r"(rank) : "memory");
}
__device__ __forceinline__ void mbar_wait(uint32_t b, uint32_t ph) {
  uint32_t ok = 0;
#pragma unroll 1
  for (int it = 0; it < SPIN && !ok; it++)
    asm volatile("{.reg .pred p; mbarrier.try_wait.parity.shared::cta.b64 p,[%1],%2; selp.u32 %0,1,0,p;}" : "=r"(ok) : "r"(b), "r"(ph) : "memory");
}
__device__ __forceinline__ void tma2d(uint32_t dst, const CUtensorMap* m, int c0, int c1, uint32_t bar) {
  asm volatile("cp.async.bulk.tensor.2d.shared::cluster.global.mbarrier::complete_tx::bytes" MCS " [%0], [%1, {%3, %4}], [%2]" MCA(5) ";"
               ::"r"(dst), "l"(m), "r"(bar), "r"(c0), "r"(c1), "h"((uint16_t)3) : "memory");
}
__device__ __forceinline__ void tma3d(uint32_t dst, const CUtensorMap* m, int c0, int c1, int c2, uint32_t bar) {
  asm volatile("cp.async.bulk.tensor.3d.shared::cluster.global.mbarrier::complete_tx::bytes" MCS " [%0], [%1, {%3, %4, %5}], [%2]" MCA(6) ";"
               ::"r"(dst), "l"(m), "r"(bar), "r"(c0), "r"(c1), "r"(c2), "h"((uint16_t)3) : "memory");
}
__device__ __forceinline__ void l2pf(const void* p, uint32_t bytes) { asm volatile("cp.async.bulk.prefetch.L2.global [%0], %1;" ::"l"(p), "r"(bytes) : "memory"); }
__device__ __forceinline__ void wg_fence() { asm volatile("wgmma.fence.sync.aligned;" ::: "memory"); }
__device__ __forceinline__ void wg_commit() { asm volatile("wgmma.commit_group.sync.aligned;" ::: "memory"); }
template <int N> __device__ __forceinline__ void wg_wait() { asm volatile("wgmma.wait_group.sync.aligned %0;" ::"n"(N) : "memory"); }
template <int N> __device__ __forceinline__ void regfence(float (&d)[N]) {
#pragma unroll
  for (int i = 0; i < N; i++) asm volatile("" : "+f"(d[i])::"memory");
}
__device__ __forceinline__ void bar_cons() { asm volatile("bar.sync 1, 256;" ::: "memory"); }
__device__ __forceinline__ void fence_async() { asm volatile("fence.proxy.async.shared::cta;" ::: "memory"); }
struct Desc { uint32_t lo, hi; };
__device__ __forceinline__ Desc mkdesc(uint32_t base16, uint32_t off, uint32_t lbo, uint32_t sbo, uint32_t swz) {
  return Desc{base16 + ((off >> 4) | ((lbo >> 4) << 16)), (sbo >> 4) | (swz << 30)};
}
__device__ __forceinline__ uint4 ldll(const uint4* p) {
  uint4 v; asm volatile("ld.relaxed.gpu.global.v4.u32 {%0,%1,%2,%3}, [%4];" : "=r"(v.x), "=r"(v.y), "=r"(v.z), "=r"(v.w) : "l"(p) : "memory"); return v;
}
__device__ __forceinline__ uint2 ldll2(const uint2* p) {
  uint2 v; asm volatile("ld.relaxed.gpu.global.v2.u32 {%0,%1}, [%2];" : "=r"(v.x), "=r"(v.y) : "l"(p) : "memory"); return v;
}
__device__ __forceinline__ void stll(uint4* p, uint32_t x, uint32_t y, uint32_t z, uint32_t w) {
  asm volatile("st.relaxed.gpu.global.v4.u32 [%0], {%1,%2,%3,%4};" ::"l"(p), "r"(x), "r"(y), "r"(z), "r"(w) : "memory");
}
__device__ __forceinline__ void stll2(void* p, uint32_t x, uint32_t y) {
  asm volatile("st.relaxed.gpu.global.v2.u32 [%0], {%1,%2};" ::"l"(p), "r"(x), "r"(y) : "memory");
}
__device__ __forceinline__ int laneid() { int l; asm volatile("mov.u32 %0, %%laneid;" : "=r"(l)); return l; }
__device__ __forceinline__ uint32_t tg(uint32_t w, uint32_t tag) { return (w & ~1u) | tag; }
__device__ __forceinline__ uint32_t pack(float lo, float hi) {
  uint32_t r; asm("cvt.rn.bf16x2.f32 %0, %1, %2;" : "=r"(r) : "f"(hi), "f"(lo)); return r;
}
__device__ __forceinline__ float blo(uint32_t w) { return __uint_as_float(w << 16); }
__device__ __forceinline__ float bhi(uint32_t w) { return __uint_as_float(w & 0xffff0000u); }
__device__ __forceinline__ float ex2(float x) { float r; asm("ex2.approx.ftz.f32 %0, %1;" : "=f"(r) : "f"(x)); return r; }
__device__ __forceinline__ float rcp(float x) { float r; asm("rcp.approx.ftz.f32 %0, %1;" : "=f"(r) : "f"(x)); return r; }
__device__ __forceinline__ float qsum(float v) { v += __shfl_xor_sync(~0u, v, 1); v += __shfl_xor_sync(~0u, v, 2); return v; }
__device__ __forceinline__ void sts32(uint32_t a, uint32_t v) { asm volatile("st.shared.u32 [%0], %1;" ::"r"(a), "r"(v) : "memory"); }
__device__ __forceinline__ void sts16(uint32_t a, uint32_t v) { asm volatile("st.shared.u16 [%0], %1;" ::"r"(a), "h"((uint16_t)v) : "memory"); }
__device__ __forceinline__ void sts128(uint32_t a, uint32_t x, uint32_t y, uint32_t z, uint32_t w) {
  asm volatile("st.shared.v4.u32 [%0], {%1,%2,%3,%4};" ::"r"(a), "r"(x), "r"(y), "r"(z), "r"(w) : "memory");
}
__device__ __forceinline__ uint32_t sw128(int row, int col) { return row * 128 + ((((col >> 3) ^ row) & 7) << 4) + (col & 7) * 2; }

__device__ __forceinline__ void wgmma_rs56(float (&d)[28], const uint32_t a0, const uint32_t a1, const uint32_t a2, const uint32_t a3, Desc db, int sd) {
  asm volatile("{.reg .pred p; .reg .b64 da, db; setp.ne.b32 p, %33, 0; mov.b64 db, {%32, %34};\n wgmma.mma_async.sync.aligned.m64n56k16.f32.bf16.bf16 {%0,%1,%2,%3,%4,%5,%6,%7,%8,%9,%10,%11,%12,%13,%14,%15,%16,%17,%18,%19,%20,%21,%22,%23,%24,%25,%26,%27}, {%28,%29,%30,%31}, db, p, 1, 1, 1;}"
   : "+f"(d[0]),"+f"(d[1]),"+f"(d[2]),"+f"(d[3]),"+f"(d[4]),"+f"(d[5]),"+f"(d[6]),"+f"(d[7]),"+f"(d[8]),"+f"(d[9]),"+f"(d[10]),"+f"(d[11]),"+f"(d[12]),"+f"(d[13]),"+f"(d[14]),"+f"(d[15]),"+f"(d[16]),"+f"(d[17]),"+f"(d[18]),"+f"(d[19]),"+f"(d[20]),"+f"(d[21]),"+f"(d[22]),"+f"(d[23]),"+f"(d[24]),"+f"(d[25]),"+f"(d[26]),"+f"(d[27])
   : "r"(a0),"r"(a1),"r"(a2),"r"(a3),"r"(db.lo),"r"(sd),"r"(db.hi));
}
__device__ __forceinline__ void wgmma_rs64(float (&d)[32], const uint32_t a0, const uint32_t a1, const uint32_t a2, const uint32_t a3, Desc db, int sd) {
  asm volatile("{.reg .pred p; .reg .b64 da, db; setp.ne.b32 p, %37, 0; mov.b64 db, {%36, %38};\n wgmma.mma_async.sync.aligned.m64n64k16.f32.bf16.bf16 {%0,%1,%2,%3,%4,%5,%6,%7,%8,%9,%10,%11,%12,%13,%14,%15,%16,%17,%18,%19,%20,%21,%22,%23,%24,%25,%26,%27,%28,%29,%30,%31}, {%32,%33,%34,%35}, db, p, 1, 1, 1;}"
   : "+f"(d[0]),"+f"(d[1]),"+f"(d[2]),"+f"(d[3]),"+f"(d[4]),"+f"(d[5]),"+f"(d[6]),"+f"(d[7]),"+f"(d[8]),"+f"(d[9]),"+f"(d[10]),"+f"(d[11]),"+f"(d[12]),"+f"(d[13]),"+f"(d[14]),"+f"(d[15]),"+f"(d[16]),"+f"(d[17]),"+f"(d[18]),"+f"(d[19]),"+f"(d[20]),"+f"(d[21]),"+f"(d[22]),"+f"(d[23]),"+f"(d[24]),"+f"(d[25]),"+f"(d[26]),"+f"(d[27]),"+f"(d[28]),"+f"(d[29]),"+f"(d[30]),"+f"(d[31])
   : "r"(a0),"r"(a1),"r"(a2),"r"(a3),"r"(db.lo),"r"(sd),"r"(db.hi));
}
__device__ __forceinline__ void wgmma_rs192(float (&d)[96], const uint32_t a0, const uint32_t a1, const uint32_t a2, const uint32_t a3, Desc db, int sd) {
  asm volatile("{.reg .pred p; .reg .b64 db; setp.ne.b32 p, %101, 0; mov.b64 db, {%100, %102};\n wgmma.mma_async.sync.aligned.m64n192k16.f32.bf16.bf16 {%0,%1,%2,%3,%4,%5,%6,%7,%8,%9,%10,%11,%12,%13,%14,%15,%16,%17,%18,%19,%20,%21,%22,%23,%24,%25,%26,%27,%28,%29,%30,%31,%32,%33,%34,%35,%36,%37,%38,%39,%40,%41,%42,%43,%44,%45,%46,%47,%48,%49,%50,%51,%52,%53,%54,%55,%56,%57,%58,%59,%60,%61,%62,%63,%64,%65,%66,%67,%68,%69,%70,%71,%72,%73,%74,%75,%76,%77,%78,%79,%80,%81,%82,%83,%84,%85,%86,%87,%88,%89,%90,%91,%92,%93,%94,%95}, {%96,%97,%98,%99}, db, p, 1, 1, 1;}"
   : "+f"(d[0]),"+f"(d[1]),"+f"(d[2]),"+f"(d[3]),"+f"(d[4]),"+f"(d[5]),"+f"(d[6]),"+f"(d[7]),"+f"(d[8]),"+f"(d[9]),"+f"(d[10]),"+f"(d[11]),"+f"(d[12]),"+f"(d[13]),"+f"(d[14]),"+f"(d[15]),"+f"(d[16]),"+f"(d[17]),"+f"(d[18]),"+f"(d[19]),"+f"(d[20]),"+f"(d[21]),"+f"(d[22]),"+f"(d[23]),"+f"(d[24]),"+f"(d[25]),"+f"(d[26]),"+f"(d[27]),"+f"(d[28]),"+f"(d[29]),"+f"(d[30]),"+f"(d[31]),"+f"(d[32]),"+f"(d[33]),"+f"(d[34]),"+f"(d[35]),"+f"(d[36]),"+f"(d[37]),"+f"(d[38]),"+f"(d[39]),"+f"(d[40]),"+f"(d[41]),"+f"(d[42]),"+f"(d[43]),"+f"(d[44]),"+f"(d[45]),"+f"(d[46]),"+f"(d[47]),"+f"(d[48]),"+f"(d[49]),"+f"(d[50]),"+f"(d[51]),"+f"(d[52]),"+f"(d[53]),"+f"(d[54]),"+f"(d[55]),"+f"(d[56]),"+f"(d[57]),"+f"(d[58]),"+f"(d[59]),"+f"(d[60]),"+f"(d[61]),"+f"(d[62]),"+f"(d[63]),"+f"(d[64]),"+f"(d[65]),"+f"(d[66]),"+f"(d[67]),"+f"(d[68]),"+f"(d[69]),"+f"(d[70]),"+f"(d[71]),"+f"(d[72]),"+f"(d[73]),"+f"(d[74]),"+f"(d[75]),"+f"(d[76]),"+f"(d[77]),"+f"(d[78]),"+f"(d[79]),"+f"(d[80]),"+f"(d[81]),"+f"(d[82]),"+f"(d[83]),"+f"(d[84]),"+f"(d[85]),"+f"(d[86]),"+f"(d[87]),"+f"(d[88]),"+f"(d[89]),"+f"(d[90]),"+f"(d[91]),"+f"(d[92]),"+f"(d[93]),"+f"(d[94]),"+f"(d[95])
   : "r"(a0),"r"(a1),"r"(a2),"r"(a3),"r"(db.lo),"r"(sd),"r"(db.hi));
}
__device__ __forceinline__ void wgmma_rs32(float (&d)[16], const uint32_t a0, const uint32_t a1, const uint32_t a2, const uint32_t a3, Desc db, int sd) {
  asm volatile("{.reg .pred p; .reg .b64 db; setp.ne.b32 p, %21, 0; mov.b64 db, {%20, %22};\n wgmma.mma_async.sync.aligned.m64n32k16.f32.bf16.bf16 {%0,%1,%2,%3,%4,%5,%6,%7,%8,%9,%10,%11,%12,%13,%14,%15}, {%16,%17,%18,%19}, db, p, 1, 1, 1;}"
   : "+f"(d[0]),"+f"(d[1]),"+f"(d[2]),"+f"(d[3]),"+f"(d[4]),"+f"(d[5]),"+f"(d[6]),"+f"(d[7]),"+f"(d[8]),"+f"(d[9]),"+f"(d[10]),"+f"(d[11]),"+f"(d[12]),"+f"(d[13]),"+f"(d[14]),"+f"(d[15])
   : "r"(a0),"r"(a1),"r"(a2),"r"(a3),"r"(db.lo),"r"(sd),"r"(db.hi));
}
__device__ __forceinline__ void wgmma_ss32(float (&d)[16], Desc da, Desc db, int sd) {
  asm volatile("{.reg .pred p; .reg .b64 da, db; setp.ne.b32 p, %18, 0; mov.b64 da, {%16, %19}; mov.b64 db, {%17, %19};\n wgmma.mma_async.sync.aligned.m64n32k16.f32.bf16.bf16 {%0,%1,%2,%3,%4,%5,%6,%7,%8,%9,%10,%11,%12,%13,%14,%15}, da, db, p, 1, 1, 1, 1;}"
   : "+f"(d[0]),"+f"(d[1]),"+f"(d[2]),"+f"(d[3]),"+f"(d[4]),"+f"(d[5]),"+f"(d[6]),"+f"(d[7]),"+f"(d[8]),"+f"(d[9]),"+f"(d[10]),"+f"(d[11]),"+f"(d[12]),"+f"(d[13]),"+f"(d[14]),"+f"(d[15])
   : "r"(da.lo),"r"(db.lo),"r"(sd),"r"(db.hi));
}

__device__ __forceinline__ uint4 ldsm4(uint32_t a) {
  uint4 v; asm volatile("ldmatrix.sync.aligned.m8n8.x4.shared.b16 {%0,%1,%2,%3}, [%4];" : "=r"(v.x), "=r"(v.y), "=r"(v.z), "=r"(v.w) : "r"(a) : "memory"); return v;
}
__device__ __forceinline__ void mma16816(float (&d)[4], const uint4& a, uint32_t b0, uint32_t b1) {
  asm("mma.sync.aligned.m16n8k16.row.col.f32.bf16.bf16.f32 {%0,%1,%2,%3}, {%4,%5,%6,%7}, {%8,%9}, {%0,%1,%2,%3};"
      : "+f"(d[0]), "+f"(d[1]), "+f"(d[2]), "+f"(d[3]) : "r"(a.x), "r"(a.y), "r"(a.z), "r"(a.w), "r"(b0), "r"(b1));
}
__device__ __forceinline__ uint32_t bsub(uint32_t a, uint32_t b) { uint32_t r; asm("sub.bf16x2 %0, %1, %2;" : "=r"(r) : "r"(a), "r"(b)); return r; }
__device__ __forceinline__ uint32_t hint_ld(const uint32_t* p) { uint32_t v; asm volatile("ld.relaxed.gpu.global.u32 %0, [%1];" : "=r"(v) : "l"(p) : "memory"); return v; }
template <int S, int N, bool SPL = false, int T> __device__ __forceinline__ void ll_issue(uint4 (&v)[T], const uint4* p, int stride, const uint2* p2 = nullptr) {
#pragma unroll
  for (int i = S; i < S + N; i++) {
    if (SPL && i % 7 == 3) { const uint2 lo = ldll2(p2 + i * 64), hi = ldll2(p2 + i * 64 + 32); v[i] = make_uint4(lo.x, lo.y, hi.x, hi.y); }
    else v[i] = ldll(p + i * stride);
  }
}
template <int S, int N, bool SPL, int T> __device__ __forceinline__ void ll_check(uint4 (&v)[T], const uint4* p, int stride, uint32_t tag, const uint2* p2 = nullptr) {
#pragma unroll 1
  for (int it = 0; it < SPIN; it++) {
    uint32_t bad = 0;
#pragma unroll
    for (int i = S; i < S + N; i++) bad |= (v[i].x ^ tag) | ((SPL && i % 7 == 3) ? (v[i].z ^ tag) : 0u);
    if (!__any_sync(~0u, bad & 1)) break;
    ll_issue<S, N, SPL>(v, p, stride, p2);
  }
}
__device__ __forceinline__ void hint_post(uint32_t* p, uint32_t v, int lane) {
  if (lane == 0) asm volatile("st.relaxed.gpu.global.u32 [%0], %1;" ::"l"(p), "r"(v) : "memory");
}
__device__ __forceinline__ void hint_wait(const uint32_t* p, uint32_t s, uint32_t v = 0xffffu) {
#pragma unroll 1
  for (int it = 0; it < SPIN; it++) {
    if (__all_sync(~0u, v - s < 10u)) break;
    v = hint_ld(p);
  }
}
__device__ __forceinline__ void slice_store(uint4* pf, uint2* ph, const uint32_t (&w)[14], bool odd) {
#pragma unroll
  for (int u = 0; u < 3; u++)
    stll(pf + u * 32, odd ? w[4 * u + 2] : w[4 * u], odd ? w[4 * u + 3] : w[4 * u + 1], odd ? w[4 * u + 4] : w[4 * u + 2], odd ? w[4 * u + 5] : w[4 * u + 3]);
  stll2(ph, odd ? w[0] : w[12], odd ? w[1] : w[13]);
}
template <class F, class M> __device__ __forceinline__ void hedgehog(const float (&d)[28], F sink, M mid) {
  const float L2E = 1.4426950408889634f;
#define HX(G, p) ((p) < 6 ? d[((G) & 1) * 16 + ((p) >> 1) * 4 + ((p) & 1) + ((G) & 2)] : d[12 + (G)])
  float mx[4], mn[4], sp[4], sn[4], ep[4][7], en[4][7];
#pragma unroll
  for (int G = 0; G < 4; G++) {
    mx[G] = mn[G] = HX(G, 0);
#pragma unroll
    for (int p = 1; p < 7; p++) { mx[G] = fmaxf(mx[G], HX(G, p)); mn[G] = fminf(mn[G], HX(G, p)); }
  }
#pragma unroll
  for (int o = 1; o < 4; o <<= 1)
#pragma unroll
    for (int G = 0; G < 4; G++) { mx[G] = fmaxf(mx[G], __shfl_xor_sync(~0u, mx[G], o)); mn[G] = fminf(mn[G], __shfl_xor_sync(~0u, mn[G], o)); }
#pragma unroll
  for (int G = 0; G < 4; G++) {
    const float a = -mx[G] * L2E, b = mn[G] * L2E;
#pragma unroll
    for (int p = 0; p < 7; p++) { ep[G][p] = ex2(fmaf(HX(G, p), L2E, a)); en[G][p] = ex2(fmaf(HX(G, p), -L2E, b)); }
    sp[G] = ((ep[G][0] + ep[G][1]) + (ep[G][2] + ep[G][3])) + ((ep[G][4] + ep[G][5]) + ep[G][6]);
    sn[G] = ((en[G][0] + en[G][1]) + (en[G][2] + en[G][3])) + ((en[G][4] + en[G][5]) + en[G][6]);
    if (G == 1) mid();
  }
#pragma unroll
  for (int o = 1; o < 4; o <<= 1)
#pragma unroll
    for (int G = 0; G < 4; G++) { sp[G] += __shfl_xor_sync(~0u, sp[G], o); sn[G] += __shfl_xor_sync(~0u, sn[G], o); }
#pragma unroll
  for (int G = 0; G < 4; G++) {
    const float a = rcp(sp[G]), b = rcp(sn[G]);
#pragma unroll
    for (int p = 0; p < 7; p++) sink(G >> 1, G & 1, p, pack(ep[G][p] * a, en[G][p] * b));
  }
}
__device__ __forceinline__ void phi_gemm(const float (&x)[28], float (&y)[28], uint32_t wphi, float r0, float r1) {
  uint32_t f[14];
#pragma unroll
  for (int j = 0; j < 14; j++) f[j] = pack(x[2 * j] * (j & 1 ? r1 : r0), x[2 * j + 1] * (j & 1 ? r1 : r0));
  wg_fence();
#pragma unroll
  for (int ks = 0; ks < 3; ks++) wgmma_rs56(y, f[4 * ks], f[4 * ks + 1], f[4 * ks + 2], f[4 * ks + 3], mkdesc(wphi, ks * 2048, 1024, 1024, 1), ks);
  wgmma_rs56(y, f[12], f[13], 0u, 0u, mkdesc(wphi, 3 * 2048, 1024, 1024, 1), 1);
  wg_commit();
}
__device__ __forceinline__ void ln_stats(uint32_t (&xw)[4][4], float* sLN, int warp, int lane, uint4* dst) {
  const int g = lane >> 2; const bool full = warp < 4;
  float s0 = 0.f, s1 = 0.f;
#pragma unroll
  for (int u = 0; u < 4; u++) {
    s0 += (blo(xw[u][0]) + bhi(xw[u][0])) + (blo(xw[u][2]) + bhi(xw[u][2]));
    s1 += (blo(xw[u][1]) + bhi(xw[u][1])) + (blo(xw[u][3]) + bhi(xw[u][3]));
  }
  const float rc = full ? 1.f / 64 : 1.f / 48;
  s0 = qsum(s0); s1 = qsum(s1);
  const float a0 = s0 * rc, a1 = s1 * rc;
  float v0 = 0.f, v1 = 0.f;
#pragma unroll
  for (int u = 0; u < 4; u++)
    if (u < 3 || full) {
#pragma unroll
      for (int k = 0; k < 4; k += 2) {
        float a = blo(xw[u][k]) - a0, b = bhi(xw[u][k]) - a0, c2 = blo(xw[u][k + 1]) - a1, d2 = bhi(xw[u][k + 1]) - a1;
        v0 += a * a + b * b; v1 += c2 * c2 + d2 * d2;
      }
    }
  v0 = qsum(v0); v1 = qsum(v1);
  if ((lane & 3) == 0) *(float4*)(sLN + (g * 8 + warp) * 4) = make_float4(s0, v0, s1, v1);
  if (warp) { asm volatile("bar.arrive 7, 256;" ::: "memory"); return; }
  asm volatile("bar.sync 7, 256;" ::: "memory");
  const float4 ea = *(const float4*)(sLN + (g * 8 + (lane & 3)) * 4), eb = *(const float4*)(sLN + (g * 8 + 4 + (lane & 3)) * 4);
  const float m0 = qsum(ea.x + eb.x) * (1.f / 448), m1 = qsum(ea.z + eb.z) * (1.f / 448);
  const float d0 = ea.x * (1.f / 64) - m0, d1 = eb.x * (1.f / 48) - m0, d2 = ea.z * (1.f / 64) - m1, d3 = eb.z * (1.f / 48) - m1;
  v0 = qsum(ea.y + eb.y + 64.f * d0 * d0 + 48.f * d1 * d1); v1 = qsum(ea.w + eb.w + 64.f * d2 * d2 + 48.f * d3 * d3);
  if ((lane & 3) == 0) stll(dst + g, tg(__float_as_uint(m0), 1), __float_as_uint(rsqrtf(v0 * (1.f / 448) + 1e-5f)), __float_as_uint(m1), __float_as_uint(rsqrtf(v1 * (1.f / 448) + 1e-5f)));
}

__global__ void CLUSTER __launch_bounds__(384, 1)
fused_kernel(const __grid_constant__ CUtensorMap mQKV, const __grid_constant__ CUtensorMap mWO, const __grid_constant__ CUtensorMap mW1,
             const __grid_constant__ CUtensorMap mW1b, const __grid_constant__ CUtensorMap mW2, const __grid_constant__ CUtensorMap mW2b,
             const __grid_constant__ CUtensorMap mX, const __nv_bfloat16* __restrict__ wqkv, const __nv_bfloat16* __restrict__ wphi,
             const __nv_bfloat16* __restrict__ wo, const __nv_bfloat16* __restrict__ w1, const __nv_bfloat16* __restrict__ b1,
             const __nv_bfloat16* __restrict__ w2, const __nv_bfloat16* __restrict__ b2, __nv_bfloat16* __restrict__ out) {
  extern __shared__ __align__(1024) uint8_t sm[];
  const uint32_t sb = s2u(sm);
  const int tid = threadIdx.x, warp = __shfl_sync(~0u, tid >> 5, 0), lane = tid & 31,
            t = MAPPING ? (blockIdx.x >> 4) * 2 + (blockIdx.x & 1) : blockIdx.x >> 3, c = MAPPING ? (blockIdx.x >> 1) & 7 : blockIdx.x & 7;
  const uint32_t bfull = sb + OFF_BAR, bempty = bfull + 8 * NST;

#define XOFF(l) ((t * 128 + c * 16 + ((l) >> 2)) * 448 + warp * 16 + 2 * ((l) & 3))
  if (warp < 8) { MARK(0); GT(19); }
  if (tid == 256) {
    for (int s = 0; s < NST; s++) { mbar_init(bfull + 8 * s, 1); mbar_init(bempty + 8 * s, MC ? 16 : 8); }
    mbar_init(bempty + 8 * NST, 1);
    asm volatile("fence.mbarrier_init.release.cluster;" ::: "memory");
    fence_async();
    mbar_expect(bempty + 8 * NST, 114688);
    for (int i = 0; i < 7; i++)
      asm volatile("cp.async.bulk.tensor.2d.shared::cluster.global.mbarrier::complete_tx::bytes [%0], [%1, {%3, %4}], [%2];"
                   ::"r"(sb + 2 * STAGE + i * 16384), "l"(&mX), "r"(bempty + 8 * NST), "r"(64 * i), "r"(128 * t) : "memory");
  }
  asm volatile("barrier.cluster.arrive.release.aligned; barrier.cluster.wait.acquire.aligned;" ::: "memory");
  if (warp >= 8) {
    asm volatile("setmaxnreg.dec.sync.aligned.u32 24;");
    auto issue = [&](int i, int s) {
      const uint32_t dst = sb + s * STAGE, bar = bfull + 8 * s;
      mbar_expect(bar, STAGE);
#pragma unroll 1
      for (int rk = MC ? (blockIdx.x & 1) : 0; rk < (MC ? (blockIdx.x & 1) + 1 : 2); rk++)
      if (i < 4) tma2d(dst + rk * 14336, &mQKV, 448 + 448 * rk + 56 * c, 112 * i, bar);
      else if (i < 8) tma2d(dst + rk * 14336, i < 6 ? &mQKV : &mWO, (i < 6 ? 56 : 64) * c, 224 * (i & 1) + 112 * rk, bar);
      else if (i < 15) { const int k0 = 64 * ((i - 8 + c) % 7) + 32 * rk;
        tma3d(dst + rk * 12288, &mW1, 0, k0, 3 * c, bar); tma2d(dst + 24576 + rk * 2048, &mW1b, 1536 + 32 * c, k0, bar); }
      else { tma2d(dst + rk * 12288, &mW2, 64 * (i - 15), 192 * c + 96 * rk, bar); tma2d(dst + 24576 + rk * 2048, &mW2b, 64 * (i - 15), 1536 + 32 * c + 16 * rk, bar); }
    };
    if (warp == 8) {
      int s = 0; uint32_t ph = 1;
      for (int n = 0; n < 44; n++) {
        if (n == PACE) asm volatile("bar.sync 2, 288;" ::: "memory");
        mbar_wait(bempty + 8 * s, ph);
        if (n == 22) {
          uint32_t v = 0;
#pragma unroll 1
          for (int it = 0; it < SPIN && v < 32; it++) asm volatile("ld.acquire.gpu.global.u32 %0, [%1];" : "=r"(v) : "l"(g_WQF + c) : "memory");
          asm volatile("fence.proxy.async.global;" ::: "memory");
        }
        if (lane == 0) {
          if (n >= 22 && n < 28) {
            mbar_expect(bfull + 8 * s, STAGE);
            asm volatile("cp.async.bulk.shared::cluster.global.mbarrier::complete_tx::bytes [%0], [%1], %2, [%3];"
                         ::"r"(sb + s * STAGE), "l"(g_WQ + c * 10752 + (n - 22) * (STAGE / 16)), "r"(STAGE), "r"(bfull + 8 * s) : "memory");
          } else issue(n >= 22 ? n - 22 : n, s);
        }
        __syncwarp();
        if (++s == NST) { s = 0; ph ^= 1; }
      }
    } else if (warp == 9) {
      mbar_wait(bfull + 8 * 3, 0);
      if (lane == 0) {
        l2pf((const uint8_t*)wo + blockIdx.x * 3136, 3136);
        l2pf((const uint8_t*)w1 + blockIdx.x * 12544, 12544);
        l2pf((const uint8_t*)w2 + blockIdx.x * 12544, 12544);
      }
#pragma unroll 1
      for (int job = blockIdx.x; job < 196; job += 128) {
        const int ld4 = job < 112 ? 448 : 336;
        const uint2* wp = (job < 112 ? (const uint2*)w1 + job * 4 : (const uint2*)wqkv + (job - 112) * 4) + (lane >> 2) * ld4 + (lane & 3);
        float s0 = 0.f, s1 = 0.f, s2 = 0.f, s3 = 0.f;
#pragma unroll 8
        for (int i = 0; i < 56; i++) { const uint2 v = __ldg(wp + i * 8 * ld4); s0 += blo(v.x); s1 += bhi(v.x); s2 += blo(v.y); s3 += bhi(v.y); }
#pragma unroll 1
        for (int o = 4; o < 32; o <<= 1) { s0 += __shfl_xor_sync(~0u, s0, o); s1 += __shfl_xor_sync(~0u, s1, o); s2 += __shfl_xor_sync(~0u, s2, o); s3 += __shfl_xor_sync(~0u, s3, o); }
        if (lane < 4) stll(g_CS + job * 4 + lane, tg(__float_as_uint(s0), 1), __float_as_uint(s1), __float_as_uint(s2), __float_as_uint(s3));
      }
      asm volatile("bar.sync 6, 96;" ::: "memory");
#pragma unroll 1
      for (int i = 0; i < 4; i++) {
        const int e = lane < 28 ? lane + 28 * (i & 1) : 0;
        const bool ok = i < 2 || (e < 48 && (e & 15) < 14);
        const int e4 = i < 2 ? (e < 48 ? 48 * c + e : 336 + 8 * c + e) : ok ? 448 + 112 * (e >> 4) + 14 * c + (e & 15) : 448;
        uint4 cv[1];
        ll_issue<0, 1>(cv, g_CS + e4, 0); ll_check<0, 1, false>(cv, g_CS + e4, 0, 1u);
        const uint2 bb = __ldg((const uint2*)b1 + (i < 2 ? e4 : 0));
        const uint32_t h0 = pack(__uint_as_float(cv[0].x), __uint_as_float(cv[0].y)), h1 = pack(__uint_as_float(cv[0].z), __uint_as_float(cv[0].w));
        const uint32_t l0 = pack(__uint_as_float(cv[0].x) - blo(h0), __uint_as_float(cv[0].y) - bhi(h0)), l1 = pack(__uint_as_float(cv[0].z) - blo(h1), __uint_as_float(cv[0].w) - bhi(h1));
#pragma unroll 1
        for (int j = 0; j < (i < 2 ? 5 : 3); j++) {
          const int r = i < 2 ? j : j + 5;
          const uint32_t ad = sb + OFF_CB + (e >> 3) * 512 + r * 64 + ((((e >> 1) ^ (r >> 1)) & 3) << 4) + (e & 1) * 8;
          sts32(ad, j < 2 ? h0 : j == 2 ? l0 : bb.x); sts32(ad + 4, j < 2 ? h1 : j == 2 ? l1 : bb.y);
        }
      }
      fence_async();
      asm volatile("bar.arrive 4, 288;" ::: "memory");
    } else if (warp >= 10) {
      const int h = warp - 10;
      uint32_t wv[13];
#pragma unroll
      for (int i = 0; i < 13; i++) { const int e = lane + 32 * i; wv[i] = e < 392 ? __ldg((const uint32_t*)wphi + (2 * c + h) * 392 + e) : 0u; }
#pragma unroll 1
      for (int e = h * 32 + lane; e < 672; e += 64) sts128(sb + OFF_WPHI + e * 16, 0, 0, 0, 0);
      asm volatile("bar.arrive 6, 96;" ::: "memory");
#pragma unroll 1
      for (int i = 0; i < 4; i++) sts128(sb + OFF_PHIK + sw128(h * 128 + i * 32 + lane, 56), 0, 0, 0, 0);
      asm volatile("bar.sync 5, 64;" ::: "memory");
#pragma unroll
      for (int i = 0; i < 13; i++) {
        const int e = lane + 32 * i, d = e / 14, f2 = 2 * (e - 14 * d), k = 28 * h + d;
        if (e < 392) {
          if (f2 < 24) sts32(sb + OFF_WPHI + sw128(k, 32 * h + f2), wv[i]);
          else { sts16(sb + OFF_WPHI + sw128(k, 2 * f2 - 24 + h), wv[i]); sts16(sb + OFF_WPHI + sw128(k, 2 * f2 - 22 + h), wv[i] >> 16); }
        }
      }
      fence_async();
      asm volatile("bar.arrive 3, 320;" ::: "memory");
      mbar_wait(bfull + 8 * 5, 0);
#pragma unroll 2
      for (int e = t * 672 + h * 32 + lane; e < t * 672 + 672; e += 64) {
        const int r = e >> 3, st = r / 224, rr = r - st * 224, ch = (e & 7) ^ (rr & 7);
        const int k = st < 4 ? 112 * st + (rr >= 112 ? rr - 112 : rr) : 224 * (st - 4) + rr, col = (st < 4 ? (rr >= 112 ? 896 : 448) : 0) + 56 * c + 8 * ch;
        g_WQ[c * 10752 + e] = ch < 7 ? __ldg((const uint4*)(wqkv + k * 1344 + col)) : make_uint4(0, 0, 0, 0);
      }
      __syncwarp();
      if (lane == 0) asm volatile("red.release.gpu.global.add.u32 [%0], 1;" ::"l"(g_WQF + c) : "memory");
    }
  } else {
  asm volatile("setmaxnreg.inc.sync.aligned.u32 240;");

  const int wg = warp >> 2, g = lane >> 2, q = lane & 3;
  const int row0 = warp * 16 + g;
#define PTRS const int ln_ = laneid(); \
  uint4* const fm = g_F + ((t * 8 + warp) * 28) * 32 + ln_;            \
  uint4* const fr = g_F + ((t * 8 + c) * 28 + warp) * 32 + ln_;        \
  uint4* const sf = fm + (7 * (c >> 1) + 4 * (c & 1)) * 32;             \
  uint2* const f2 = (uint2*)(fm - ln_) + ln_;                           \
  uint2* const sh = f2 + (7 * (c >> 1) + 3) * 64 + 32 * (c & 1);        \
  uint32_t* const hme = g_H + (t * 8 + warp) * 8 + c; \
  const uint32_t* const hrow = g_H + (t * 8 + warp) * 8 + (ln_ & 7); \
  (void)fm; (void)fr; (void)sf; (void)f2; (void)sh; (void)hme; (void)hrow;
  float* sLN = (float*)(sm + OFF_V);
  const uint32_t sPK = sb + OFF_PHIK, sV = sb + OFF_V, d16 = (sb & 0x3FFFF) >> 4;
    uint32_t xw[4][4];
#pragma unroll
  for (int i = 0; i < 16; i++) xw[i >> 2][i & 3] = 0;
  int cs = 0, rs = 0; uint32_t cph = 0;
  auto acquire = [&]() -> uint32_t { mbar_wait(bfull + 8 * cs, cph); const uint32_t a = d16 + cs * (STAGE >> 4); if (++cs == NST) { cs = 0; cph ^= 1; } return a; };
  int nrel = 44 - NST;
  auto release = [&]() { if (lane < 1 + MC && nrel > 0) mbar_arrive_cl(bempty + 8 * rs, lane); nrel--; if (++rs == NST) rs = 0; };

#define RISSUE(m, P, XA, XB, BA, BB) { ll_issue<0, 8>(P, pr + (m) * 256, 896); \
      { const uint4 v_ = ldll(fr + X1 + (m) * 256); XA = make_uint2(v_.x, v_.y); XB = make_uint2(v_.z, v_.w); } \
      const uint32_t* bp = (const uint32_t*)(b2 + 128 * (m) + 16 * warp) + (ln_ & 3); BA = __ldg(bp); BB = __ldg(bp + 4); }
#define REDU(m, P, XA, XB, BA, BB) { ll_check<0, 8, false>(P, pr + (m) * 256, 896, ptag); \
      float e[8] = {blo(XA.x) + blo(BA), bhi(XA.x) + bhi(BA), blo(XA.y) + blo(BA), bhi(XA.y) + bhi(BA), blo(XB.x) + blo(BB), bhi(XB.x) + bhi(BB), blo(XB.y) + blo(BB), bhi(XB.y) + bhi(BB)}; \
      _Pragma("unroll") for (int i = 0; i < 8; i++) { e[0] += blo(P[i].x); e[1] += bhi(P[i].x); e[2] += blo(P[i].y); e[3] += bhi(P[i].y); \
        e[4] += blo(P[i].z); e[5] += bhi(P[i].z); e[6] += blo(P[i].w); e[7] += bhi(P[i].w); } \
      xw[m][0] = pack(e[0], e[1]); xw[m][1] = pack(e[2], e[3]); xw[m][2] = pack(e[4], e[5]); xw[m][3] = pack(e[6], e[7]); }
#define RPUB(m) stll(fr + XR + (m) * 256, tg(xw[m][0], 0), xw[m][1], xw[m][2], xw[m][3]);
#define RLAST(ptag_, hv) { const uint32_t ptag = ptag_; const uint4* pr = g_P + ((t * 8 + c) * 8 * 28 + warp) * 32 + ln_; uint4 p[8]; uint2 xa, xb; uint32_t ba, bb; \
      hint_wait(g_H + (t * 8 + c) * 8 + (ln_ & 7), hv); RISSUE(3, p, xa, xb, ba, bb) REDU(3, p, xa, xb, ba, bb) }
#pragma unroll 1
  for (int L = 0; L < 2; L++) {
    const uint32_t tag = 1 - L;
    uint32_t phq[2][2][7];
    const uint32_t hs = 10 * L;
    {
      PTRS
      uint4 a[28];
      const uint4* pa = fm + XR;
      uint32_t fa = 0, fb = 0;
      float r0 = 1.f, r1 = 1.f;
      if (L == 0) {
        mbar_wait(bempty + 8 * NST, 0);
        MARK(1);
        const int row = warp * 16 + (ln_ & 15);
        const uint32_t xb = sb + 2 * STAGE + row * 128;
        float cs_[4][4] = {}, c0[2][4] = {}, c1[2][4] = {};
#pragma unroll
        for (int ks = 0; ks < 28; ks++) { a[ks] = ldsm4(xb + (ks >> 2) * 16384 + (((2 * (ks & 3) + (ln_ >> 4)) ^ (row & 7)) << 4)); mma16816(cs_[ks & 3], a[ks], 0x3F803F80u, 0x3F803F80u); }
        if (c < 7) {
#pragma unroll
          for (int u = 0; u < 4; u++) { const uint4 v = ldsm4(xb + c * 16384 + (((2 * u + (ln_ >> 4)) ^ (row & 7)) << 4)); stll(fm + XR + 128 * c + u * 32, tg(v.x, tag), v.y, v.z, v.w); }
        }
        const float m0 = ((cs_[0][0] + cs_[1][0]) + (cs_[2][0] + cs_[3][0])) * (1.f / 448), m1 = ((cs_[0][2] + cs_[1][2]) + (cs_[2][2] + cs_[3][2])) * (1.f / 448);
        const uint32_t mb0 = pack(m0, m0), mb1 = pack(m1, m1);
        asm volatile("bar.arrive 2, 288;" ::"r"(mb0) : "memory");
#pragma unroll
        for (int ks = 0; ks < 28; ks++) {
          a[ks].x = bsub(a[ks].x, mb0); a[ks].y = bsub(a[ks].y, mb1); a[ks].z = bsub(a[ks].z, mb0); a[ks].w = bsub(a[ks].w, mb1);
          mma16816(c0[ks & 1], a[ks], a[ks].x, a[ks].z); mma16816(c1[ks & 1], a[ks], a[ks].y, a[ks].w);
        }
        const int src = (ln_ & 28) | (g >> 1);
        const float q0 = __shfl_sync(~0u, (g & 1) ? c0[0][1] + c0[1][1] : c0[0][0] + c0[1][0], src), q1 = __shfl_sync(~0u, (g & 1) ? c1[0][3] + c1[1][3] : c1[0][2] + c1[1][2], src);
        const float e0 = m0 - blo(mb0), e1 = m1 - blo(mb1);
        r0 = rsqrtf(fmaxf(q0 * (1.f / 448) - e0 * e0, 0.f) + 1e-5f); r1 = rsqrtf(fmaxf(q1 * (1.f / 448) - e1 * e1, 0.f) + 1e-5f);
      } else {
        ll_issue<0, 14>(a, pa, 32);
        if (wg == 0) { RLAST(1u, 10u) xw[3][0] = tg(xw[3][0], 0); RPUB(3) } else { xw[3][0] = xw[3][1] = xw[3][2] = xw[3][3] = 0; }
        MARK(20);
        ll_issue<14, 7>(a, pa, 32);
        ln_stats(xw, sLN, warp, lane, g_S2 + (t * 8 + c) * 8);
      }
      MARK(2 + L * 19);
      float ak[28], av[28], aq[28], pp[28];
#define KVSTAGE(i) { if (L) ll_check<7 * i, 7, false>(a, pa, 32, tag); const uint32_t st = acquire(); wg_fence(); \
      _Pragma("unroll") for (int ks = 0; ks < 7; ks++) { const uint4 f = a[7 * i + ks]; \
        wgmma_rs56(ak, f.x, f.y, f.z, f.w, mkdesc(st, ks * 2048, 1024, 1024, 1), i | ks); \
        wgmma_rs56(av, f.x, f.y, f.z, f.w, mkdesc(st, 14336 + ks * 2048, 1024, 1024, 1), i | ks); } \
      wg_commit(); if (i > 0) { wg_wait<1>(); release(); } }
      KVSTAGE(0) KVSTAGE(1)
      uint4 sv[1];
      const uint4* ps = g_S2 + (t * 8 + warp) * 8 + (ln_ >> 2);
      if (L) { ll_issue<21, 7>(a, pa, 32); ll_issue<0, 1>(sv, ps, 0); }
      KVSTAGE(2) KVSTAGE(3)
      if (L) {
        ll_check<0, 1, false>(sv, ps, 0, 1u);
        const float m0 = -__uint_as_float(sv[0].x), m1 = -__uint_as_float(sv[0].z), h0 = blo(pack(m0, 0.f)), h1 = blo(pack(m1, 0.f));
        r0 = __uint_as_float(sv[0].y); r1 = __uint_as_float(sv[0].w);
        fa = q == 2 ? pack(0.f, h0) : q == 3 ? pack(m0 - h0, h0) : 0u; fb = q == 2 ? pack(0.f, h1) : q == 3 ? pack(m1 - h1, h1) : 0u;
      } else asm volatile("bar.sync 3, 320;" ::: "memory");
      wg_fence();
      wgmma_rs56(ak, fa, fb, 0u, 0u, mkdesc(d16, OFF_CB + 1024, 512, 0, 2), 1);
      wgmma_rs56(av, fa, fb, 0u, 0u, mkdesc(d16, OFF_CB + 2048, 512, 0, 2), 1);
      wg_commit();
      wg_wait<0>(); release(); regfence(ak); regfence(av);
      MARK(3 + L * 19);
      phi_gemm(ak, pp, d16 + (OFF_WPHI >> 4), r0, r1);
#pragma unroll
      for (int j = 0; j < 7; j++) {
        const int n = 8 * j + 2 * q, n2 = n < 28 ? n : n + 4;
        sts32(sV + sw128(row0, n2), pack(av[4 * j] * r0, av[4 * j + 1] * r0)); sts32(sV + sw128(row0 + 8, n2), pack(av[4 * j + 2] * r1, av[4 * j + 3] * r1));
      }
      { const int n2 = 28 + 2 * (q & 1) + 32 * (q >> 1); const uint32_t v = (q & 1) ? 0u : 0x3F80u; sts32(sV + sw128(row0, n2), v); sts32(sV + sw128(row0 + 8, n2), v); }
      wg_wait<0>(); regfence(pp);
      hedgehog(pp, [&](int r, int h, int p, uint32_t v) { sts32(sPK + h * 16384 + sw128(row0 + 8 * r, 8 * p + 2 * q), v); }, [] {});
      fence_async();
      bar_cons();
      MARK(4 + L * 19);
      float kv[16];
      wg_fence();
#pragma unroll
      for (int ks = 0; ks < 8; ks++) wgmma_ss32(kv, mkdesc(d16 + wg * 1024, OFF_PHIK + ks * 2048, 1024, 1024, 1), mkdesc(d16 + wg * 4, OFF_V + ks * 2048, 1024, 1024, 1), ks);
      wg_commit(); wg_wait<0>(); regfence(kv);
      const int ln2 = laneid();
#pragma unroll
      for (int u = 0; u < 4; u++) {
        float e[4];
#pragma unroll
        for (int i = 0; i < 4; i++) e[i] = kv[4 * u + i];
        stll(g_KVP + (c * 16 + t) * 1024 + wg * 512 + u * 128 + (warp & 3) * 32 + ln2, tg(__float_as_uint(e[0]), tag), __float_as_uint(e[1]), __float_as_uint(e[2]), __float_as_uint(e[3]));
      }
      MARK(5 + L * 19);
      uint4 k4[4];
      const uint4* pk = g_KVP + (c * 16 + 4 * (ln2 & 3)) * 1024 + 64 * t + warp * 8 + (ln2 >> 2);
#pragma unroll
      for (int i = 0; i < 2; i++) {
        const uint32_t st = acquire(); wg_fence();
#pragma unroll
        for (int ks = 0; ks < 14; ks++) { const uint4 f = a[14 * i + ks]; wgmma_rs56(aq, f.x, f.y, f.z, f.w, mkdesc(st, ks * 2048, 1024, 1024, 1), i | ks); }
        if (i == 1) wgmma_rs56(aq, fa, fb, 0u, 0u, mkdesc(d16, OFF_CB, 512, 0, 2), 1);
        wg_commit();
        if (i == 0) ll_issue<0, 4>(k4, pk, 1024);
      }
      ll_check<0, 4, false>(k4, pk, 1024, tag);
      float s0 = 0, s1 = 0, s2 = 0, s3 = 0;
#pragma unroll
      for (int i = 0; i < 4; i++) { s0 += __uint_as_float(k4[i].x); s1 += __uint_as_float(k4[i].y); s2 += __uint_as_float(k4[i].z); s3 += __uint_as_float(k4[i].w); }
      s0 = qsum(s0); s1 = qsum(s1); s2 = qsum(s2); s3 = qsum(s3);
      if (q == 0) stll2(g_KVR + c * 1024 + 64 * t + warp * 8 + (ln2 >> 2), tg(pack(s0, s1), tag), pack(s2, s3));
      MARK(6 + L * 19);
      wg_wait<0>(); release(); release(); regfence(aq);
      phi_gemm(aq, pp, d16 + (OFF_WPHI >> 4), r0, r1);
      bar_cons();
#pragma unroll
      for (int i = 0; i < 4; i++) sts128(sV + warp * 2048 + (lane + i * 32) * 16, 0, 0, 0, 0);
      wg_wait<0>(); regfence(pp);
      uint2 r[4];
      const uint2* pr = g_KVR + c * 1024 + wg * 512 + (warp & 3) * 32 + ln2;
      hedgehog(pp, [&](int r, int h, int p, uint32_t v) { phq[r][h][p] = v; }, [&] {
#pragma unroll
        for (int u = 0; u < 4; u++) r[u] = ldll2(pr + u * 128); });
      MARK(7 + L * 19);
#pragma unroll 1
      for (int it = 0; it < SPIN; it++) {
        if (!__any_sync(~0u, ((r[0].x ^ tag) | (r[1].x ^ tag) | (r[2].x ^ tag) | (r[3].x ^ tag)) & 1)) break;
#pragma unroll
        for (int u = 0; u < 4; u++) r[u] = ldll2(pr + u * 128);
      }
#pragma unroll
      for (int u = 0; u < 4; u++) {
        const int d = 8 * u + 2 * q;
        if (d < 28) { sts32(sV + sw128(row0, 28 * wg + d), r[u].x); sts32(sV + sw128(row0 + 8, 28 * wg + d), r[u].y); }
        else if (d == 28) {
#pragma unroll
          for (int j = 0; j < 4; j++) { sts16(sV + sw128(row0, 56 + 2 * j + wg), r[u].x); sts16(sV + sw128(row0 + 8, 56 + 2 * j + wg), r[u].y); }
        }
      }
      fence_async();
      bar_cons();
      MARK(8 + L * 19);
      float o[32];
      wg_fence();
#pragma unroll
      for (int ks = 0; ks < 8; ks++) {
        const int h = ks >> 2, p = 2 * (ks & 3);
        wgmma_rs64(o, phq[0][h][p], phq[1][h][p], p < 6 ? phq[0][h][p < 6 ? p + 1 : 0] : 0u, p < 6 ? phq[1][h][p < 6 ? p + 1 : 0] : 0u, mkdesc(d16, OFF_V + ks * 2048, 1024, 1024, 1), ks);
      }
      wg_commit(); wg_wait<0>(); regfence(o);
      const float iA0 = rcp(o[28] + 1e-6f), iB0 = rcp(o[29] + 1e-6f), iA1 = rcp(o[30] + 1e-6f), iB1 = rcp(o[31] + 1e-6f);
      uint32_t w[14];
      { PTRS
#pragma unroll
      for (int j = 0; j < 7; j++) {
        const bool hb = 8 * j + 2 * q >= 28; const float i0 = hb ? iB0 : iA0, i1 = hb ? iB1 : iA1;
        w[2 * j] = pack(o[4 * j] * i0, o[4 * j + 1] * i0); w[2 * j + 1] = pack(o[4 * j + 2] * i1, o[4 * j + 3] * i1);
        if (j == 0 || ((j ^ c) & 1) == 0) w[2 * j] = tg(w[2 * j], tag);
      }
      slice_store(sf + OO, sh + 2 * OO, w, c & 1);
      hint_post(hme, hs + 2, lane); }
    }
    MARK(9 + L * 19);
    uint4 xr[4];
    if (c < 7) {
      PTRS
      ll_issue<0, 4>(xr, fm + XR + 128 * c, 32);
      uint4 a[28];
      const uint4* pa = fm + OO;
      hint_wait(hrow, hs + 2);
      MARK(10 + L * 19);
      ll_issue<0, 28, true>(a, pa, 32, f2 + 2 * OO);
      float y[32];
      uint32_t st;
#define WOSTEP(i) { ll_check<7 * i, 7, true>(a, pa, 32, tag, f2 + 2 * OO); if (!(i & 1)) st = acquire(); wg_fence(); \
      _Pragma("unroll") for (int ks = 0; ks < 7; ks++) { const uint4 f = a[7 * i + ks]; \
        wgmma_rs64(y, f.x, f.y, f.z, f.w, mkdesc(st, ((i & 1) * 7 + ks) * 2048, 1024, 1024, 1), i | ks); } wg_commit(); }
      WOSTEP(0) WOSTEP(1) WOSTEP(2) WOSTEP(3)
      ll_check<0, 4, false>(xr, fm + XR + 128 * c, 32, tag);
      wg_wait<0>(); regfence(y);
      MARK(11 + L * 19);
#pragma unroll
      for (int u = 0; u < 4; u++) {
        xr[u].x = tg(pack(blo(xr[u].x) + y[8 * u], bhi(xr[u].x) + y[8 * u + 1]), tag); xr[u].y = pack(blo(xr[u].y) + y[8 * u + 2], bhi(xr[u].y) + y[8 * u + 3]);
        xr[u].z = pack(blo(xr[u].z) + y[8 * u + 4], bhi(xr[u].z) + y[8 * u + 5]); xr[u].w = pack(blo(xr[u].w) + y[8 * u + 6], bhi(xr[u].w) + y[8 * u + 7]);
        stll(fm + X1 + 128 * c + u * 32, xr[u].x, xr[u].y, xr[u].z, xr[u].w);
      }
      hint_post(hme, hs + 3, lane);
    } else {
      PTRS
      hint_post(hme, hs + 3, lane);
      acquire(); acquire();
      hint_wait(g_H + (t * 8 + warp) * 8, hs + 3);
      ll_issue<0, 4>(xr, fm + X1, 32); ll_check<0, 4, false>(xr, fm + X1, 32, tag);
      MARK(10 + L * 19); MARK(11 + L * 19);
    }
    uint32_t hf[56];
    float rr0, rr1;
    {
      PTRS
      uint4 a[28];
      const uint4* pa = fm + X1;
      auto grp = [&](int i) -> const uint4* { const int k = i + c; return pa + ((k >= 7 ? k - 7 : k) - i) * 128; };
#pragma unroll
      for (int u = 0; u < 4; u++) a[u] = xr[u];
      float y[96], z[16];
#define F1STAGE(i) { if (i > 0) ll_check<4 * i, 4, false>(a, grp(i), 32, tag); const uint32_t st = acquire(); wg_fence(); \
      _Pragma("unroll") for (int ks = 0; ks < 4; ks++) { const uint4 f = a[4 * i + ks]; \
        wgmma_rs192(y, f.x, f.y, f.z, f.w, mkdesc(st, (ks >> 1) * 12288 + (ks & 1) * 2048, 4096, 1024, 1), i | ks); \
        wgmma_rs32(z, f.x, f.y, f.z, f.w, mkdesc(st, 24576 + ks * 1024, 512, 512, 2), i | ks); } \
      wg_commit(); if (i > 0) { wg_wait<1>(); release(); if (i < 4) ll_issue<(i < 4 ? 4 * i + 12 : 0), 4>(a, grp(i + 3), 32); } }
      F1STAGE(0)
      hint_wait(hrow, hs + 3);
      MARK(12 + L * 19);
      ll_issue<4, 4>(a, grp(1), 32); ll_issue<8, 4>(a, grp(2), 32); ll_issue<12, 4>(a, grp(3), 32);
      if (c < 7) {
        float s0 = 0.f, s1 = 0.f, v0 = 0.f, v1 = 0.f;
#pragma unroll
        for (int u = 0; u < 4; u++) { s0 += (blo(xr[u].x) + bhi(xr[u].x)) + (blo(xr[u].z) + bhi(xr[u].z)); s1 += (blo(xr[u].y) + bhi(xr[u].y)) + (blo(xr[u].w) + bhi(xr[u].w)); }
        s0 = qsum(s0) * (1.f / 64); s1 = qsum(s1) * (1.f / 64);
#pragma unroll
        for (int u = 0; u < 4; u++) {
          const float d0 = blo(xr[u].x) - s0, d1 = bhi(xr[u].x) - s0, d2 = blo(xr[u].z) - s0, d3 = bhi(xr[u].z) - s0;
          const float d4 = blo(xr[u].y) - s1, d5 = bhi(xr[u].y) - s1, d6 = blo(xr[u].w) - s1, d7 = bhi(xr[u].w) - s1;
          v0 += (d0 * d0 + d1 * d1) + (d2 * d2 + d3 * d3); v1 += (d4 * d4 + d5 * d5) + (d6 * d6 + d7 * d7);
        }
        v0 = qsum(v0); v1 = qsum(v1);
        if (q == 0) stll(g_ST + ((t * 8 + warp) * 8 + c) * 8 + (ln_ >> 2), tg(__float_as_uint(s0), tag), __float_as_uint(v0), __float_as_uint(s1), __float_as_uint(v1));
      }
      release(); release();
      F1STAGE(1) MARK(13 + L * 19); F1STAGE(2) F1STAGE(3)
      uint4 sv[2];
      const uint4* ps = g_ST + ((t * 8 + warp) * 8 + 2 * (laneid() & 3)) * 8 + (laneid() >> 2);
      ll_issue<0, 2>(sv, ps, q < 3 ? 8 : 0);
      F1STAGE(4)
      ll_check<0, 2, false>(sv, ps, q < 3 ? 8 : 0, tag);
      const float wb = q < 3 ? 1.f : 0.f;
      const float ma = __uint_as_float(sv[0].x), mb = __uint_as_float(sv[1].x), mc = __uint_as_float(sv[0].z), md = __uint_as_float(sv[1].z);
      const float m0 = qsum(ma + wb * mb) * (1.f / 7), m1 = qsum(mc + wb * md) * (1.f / 7);
      const float v0 = qsum(__uint_as_float(sv[0].y) + 64.f * (ma - m0) * (ma - m0) + wb * (__uint_as_float(sv[1].y) + 64.f * (mb - m0) * (mb - m0)));
      const float v1 = qsum(__uint_as_float(sv[0].w) + 64.f * (mc - m1) * (mc - m1) + wb * (__uint_as_float(sv[1].w) + 64.f * (md - m1) * (md - m1)));
      const float e0 = v0 * (1.f / 448) + 1e-5f, e1 = v1 * (1.f / 448) + 1e-5f;
      rr0 = 1.f / e0; rr1 = 1.f / e1;
      auto fold = [&](float m, float sd) -> uint32_t {
        const float mh = blo(pack(-m, 0.f)), sh_ = blo(pack(sd, 0.f));
        return q == 0 ? pack(mh, -m - mh) : q == 1 ? pack(mh, sh_) : q == 2 ? pack(sd - sh_, 0.f) : 0u;
      };
      const uint32_t fa = fold(m0, sqrtf(e0)), fb = fold(m1, sqrtf(e1));
      if (L == 0) asm volatile("bar.sync 4, 288;" ::: "memory");
      wg_fence();
      wgmma_rs192(y, fa, fb, 0u, 0u, mkdesc(d16, OFF_CB + 0, 512, 0, 2), 1);
      wgmma_rs32(z, fa, fb, 0u, 0u, mkdesc(d16, OFF_CB + 3072, 512, 0, 2), 1);
      F1STAGE(5) F1STAGE(6)
      wg_wait<0>(); release(); regfence(y); regfence(z);
      MARK(14 + L * 19);
#pragma unroll
      for (int j = 0; j < 56; j++) {
        uint32_t r; asm("cvt.rn.relu.bf16x2.f32 %0, %1, %2;" : "=r"(r) : "f"(j < 48 ? y[j < 48 ? 2 * j + 1 : 0] : z[j < 48 ? 0 : 2 * j - 95]), "f"(j < 48 ? y[j < 48 ? 2 * j : 0] : z[j < 48 ? 0 : 2 * j - 96]));
        asm("mul.bf16x2 %0, %1, %1;" : "=r"(hf[j]) : "r"(r));
      }
    }
    MARK(15 + L * 19);
    {
      PTRS
      float ya[32], yb[32];
      uint4* pp = g_P + ((t * 8 + warp) * 8 + c) * 28 * 32 + ln_;
#define F2STORE(j, Y) { regfence(Y); _Pragma("unroll") for (int u = 0; u < 4; u++) \
      stll(pp + (4 * (j) + u) * 32, tg(pack(Y[8 * u] * rr0, Y[8 * u + 1] * rr0), tag), pack(Y[8 * u + 2] * rr1, Y[8 * u + 3] * rr1), \
           pack(Y[8 * u + 4] * rr0, Y[8 * u + 5] * rr0), pack(Y[8 * u + 6] * rr1, Y[8 * u + 7] * rr1)); if ((j) >= 5) hint_post(hme, hs + (4 + (j)), lane); }
#define F2PASS(j, Y, Z) { const uint32_t st = acquire(); wg_fence(); \
      _Pragma("unroll") for (int ks = 0; ks < 14; ks++) wgmma_rs64(Y, hf[4 * ks], hf[4 * ks + 1], hf[4 * ks + 2], hf[4 * ks + 3], mkdesc(st, ks * 2048, 1024, 1024, 1), ks); \
      wg_commit(); if (j > 0) { wg_wait<1>(); release(); F2STORE(j - 1, Z) } }
      const uint4* pr = g_P + ((t * 8 + c) * 8 * 28 + warp) * 32 + ln_;
      uint4 p[8], p2[8]; uint2 xa, xb, xc, xd; uint32_t ba, bb, bc, bd;
      const uint32_t ptag = tag;
      const uint32_t* hred = g_H + (t * 8 + c) * 8 + (ln_ & 7);
      F2PASS(0, ya, yb) F2PASS(1, yb, ya) F2PASS(2, ya, yb) F2PASS(3, yb, ya)
      F2PASS(4, ya, yb)
      RISSUE(0, p, xa, xb, ba, bb)
      F2PASS(5, yb, ya)
      REDU(0, p, xa, xb, ba, bb)
      if (L == 0) { xw[0][0] = tg(xw[0][0], 0); RPUB(0) }
      F2PASS(6, ya, yb)
      RISSUE(1, p, xa, xb, ba, bb)
      wg_wait<0>(); release(); F2STORE(6, ya)
      MARK(16 + L * 19);
      if (wg) hint_wait(hred, hs + 9);
      RISSUE(2, p2, xc, xd, bc, bd)
      REDU(1, p, xa, xb, ba, bb)
      if (L == 0) { xw[1][0] = tg(xw[1][0], 0); RPUB(1) }
      MARK(17 + L * 19);
      REDU(2, p2, xc, xd, bc, bd)
      if (L == 0) { xw[2][0] = tg(xw[2][0], 0); RPUB(2) }
    }
    MARK(18 + L * 19);
  }
  {
    PTRS
    uint32_t* op = (uint32_t*)(out + XOFF(ln_));
#define OUT(u) { op[u * 64] = xw[u][0]; op[u * 64 + 1792] = xw[u][1]; op[u * 64 + 4] = xw[u][2]; op[u * 64 + 1796] = xw[u][3]; }
    OUT(0) OUT(1) OUT(2)
    if (wg == 0) { RLAST(0u, 20u) OUT(3) }
    else if (warp == 7) {
      if (t == 0 && lane == 0) g_WQF[c] = 0;
      if (lane < 8) stll(g_S2 + (t * 8 + c) * 8 + lane, 0, 0, 0, 0);
      if (lane < 4) { stll(g_CS + blockIdx.x * 4 + lane, 0, 0, 0, 0); if (blockIdx.x < 68) stll(g_CS + 512 + blockIdx.x * 4 + lane, 0, 0, 0, 0); }
    }
  }
  MARK(38); GT(39);
  }
}

typedef CUresult (*EncFn)(CUtensorMap*, CUtensorMapDataType, cuuint32_t, void*, const cuuint64_t*, const cuuint64_t*, const cuuint32_t*, const cuuint32_t*,
                          CUtensorMapInterleave, CUtensorMapSwizzle, CUtensorMapL2promotion, CUtensorMapFloatOOBfill);

extern "C" void kernel_launch(void* const* d_in, const int* in_sizes, int n_in, void* d_out, int out_size) {
  static EncFn enc = nullptr;
  if (!enc) {
    void* fn = nullptr; cudaDriverEntryPointQueryResult qr;
    cudaGetDriverEntryPoint("cuTensorMapEncodeTiled", &fn, cudaEnableDefault, &qr);
    enc = (EncFn)fn;
    cudaFuncSetAttribute(fused_kernel, cudaFuncAttributeMaxDynamicSharedMemorySize, SMEM_BYTES);
  }
  CUtensorMap mQKV, mWO, mW1, mW1b, mW2, mW2b, mX;
  const cuuint32_t es[3] = {1, 1, 1};
  auto enc2 = [&](CUtensorMap* m, void* p, cuuint64_t cols, cuuint64_t rows, cuuint32_t bc, cuuint32_t br) {
    const cuuint64_t dims[2] = {cols, rows}, str[1] = {cols * 2}; const cuuint32_t box[2] = {bc, br};
    enc(m, CU_TENSOR_MAP_DATA_TYPE_BFLOAT16, 2, p, dims, str, box, es, CU_TENSOR_MAP_INTERLEAVE_NONE,
        bc == 64 ? CU_TENSOR_MAP_SWIZZLE_128B : CU_TENSOR_MAP_SWIZZLE_64B, CU_TENSOR_MAP_L2_PROMOTION_L2_128B, CU_TENSOR_MAP_FLOAT_OOB_FILL_NONE);
  };
  enc2(&mQKV, d_in[1], 1344, 448, 64, 112); enc2(&mWO, d_in[3], 448, 448, 64, 112); enc2(&mW1b, d_in[5], 1792, 448, 32, 32);
  enc2(&mX, d_in[0], 448, 2048, 64, 128);
  enc2(&mW2, d_in[7], 448, 1792, 64, 96); enc2(&mW2b, d_in[7], 448, 1792, 64, 16);
  {
    const cuuint64_t dims[3] = {64, 448, 28}, str[2] = {3584, 128}; const cuuint32_t box[3] = {64, 32, 3};
    enc(&mW1, CU_TENSOR_MAP_DATA_TYPE_BFLOAT16, 3, d_in[5], dims, str, box, es, CU_TENSOR_MAP_INTERLEAVE_NONE, CU_TENSOR_MAP_SWIZZLE_128B,
        CU_TENSOR_MAP_L2_PROMOTION_L2_128B, CU_TENSOR_MAP_FLOAT_OOB_FILL_NONE);
  }
  typedef const __nv_bfloat16* BP;
  fused_kernel<<<128, 384, SMEM_BYTES>>>(mQKV, mWO, mW1, mW1b, mW2, mW2b, mX, (BP)d_in[1], (BP)d_in[2], (BP)d_in[3], (BP)d_in[5], (BP)d_in[6], (BP)d_in[7], (BP)d_in[8],
                                         (__nv_bfloat16*)d_out);
}
```

```cpp
#include <cuda_runtime.h>
#include <cuda_bf16.h>
#include <cuda.h>
#include <stdint.h>

constexpr int NST = 6, STAGE = 28672;
constexpr int OFF_PHIK = NST * STAGE;
constexpr int OFF_V = OFF_PHIK + 32768;
constexpr int OFF_WPHI = OFF_V + 16384;
constexpr int OFF_CB = OFF_WPHI + 7168;
constexpr int OFF_BAR = OFF_CB + 3584;
constexpr int SMEM_BYTES = OFF_BAR + 16 * NST + 8;
constexpr int FR = 16 * 8 * 28 * 32;
constexpr int SPIN = 1 << 18;
#define MC 0
#define MAPPING MC
#define MCS
#define MCA(n)
#define CLUSTER
#define PACE 2

__device__ uint4 g_F[3 * FR];
constexpr int XR = 0, OO = FR, X1 = 2 * FR;
__device__ uint4 g_P[8 * FR];
__device__ uint4 g_ST[16 * 8 * 8 * 8];
__device__ uint4 g_KVP[8 * 16 * 1024];
__device__ uint2 g_KVR[8 * 1024];
__device__ uint4 g_CS[784];
__device__ uint4 g_S2[16 * 8 * 8];
__device__ uint4 g_WQ[8 * 6 * (STAGE / 16)];
__device__ uint32_t g_WQF[8];
__device__ uint32_t g_H[16 * 8 * 8];
#define MARK(i)
#define GT(i)

__device__ __forceinline__ uint32_t s2u(const void* p) { return (uint32_t)__cvta_generic_to_shared(p); }
__device__ __forceinline__ void mbar_init(uint32_t b, uint32_t c) { asm volatile("mbarrier.init.shared::cta.b64 [%0], %1;" ::"r"(b), "r"(c)); }
__device__ __forceinline__ void mbar_expect(uint32_t b, uint32_t tx) { asm volatile("mbarrier.arrive.expect_tx.shared::cta.b64 _, [%0], %1;" ::"r"(b), "r"(tx) : "memory"); }
__device__ __forceinline__ void mbar_arrive_cl(uint32_t b, uint32_t rank) {
  asm volatile("{.reg .b32 r; mapa.shared::cluster.u32 r, %0, %1; mbarrier.arrive.shared::cluster.b64 _, [r];}" ::"r"(b), "r"(rank) : "memory");
}
__device__ __forceinline__ void mbar_wait(uint32_t b, uint32_t ph) {
  uint32_t ok = 0;
#pragma unroll 1
  for (int it = 0; it < SPIN && !ok; it++)
    asm volatile("{.reg .pred p; mbarrier.try_wait.parity.shared::cta.b64 p,[%1],%2; selp.u32 %0,1,0,p;}" : "=r"(ok) : "r"(b), "r"(ph) : "memory");
}
__device__ __forceinline__ void tma2d(uint32_t dst, const CUtensorMap* m, int c0, int c1, uint32_t bar) {
  asm volatile("cp.async.bulk.tensor.2d.shared::cluster.global.mbarrier::complete_tx::bytes" MCS " [%0], [%1, {%3, %4}], [%2]" MCA(5) ";"
               ::"r"(dst), "l"(m), "r"(bar), "r"(c0), "r"(c1), "h"((uint16_t)3) : "memory");
}
__device__ __forceinline__ void tma3d(uint32_t dst, const CUtensorMap* m, int c0, int c1, int c2, uint32_t bar) {
  asm volatile("cp.async.bulk.tensor.3d.shared::cluster.global.mbarrier::complete_tx::bytes" MCS " [%0], [%1, {%3, %4, %5}], [%2]" MCA(6) ";"
               ::"r"(dst), "l"(m), "r"(bar), "r"(c0), "r"(c1), "r"(c2), "h"((uint16_t)3) : "memory");
}
__device__ __forceinline__ void l2pf(const void* p, uint32_t bytes) { asm volatile("cp.async.bulk.prefetch.L2.global [%0], %1;" ::"l"(p), "r"(bytes) : "memory"); }
__device__ __forceinline__ void wg_fence() { asm volatile("wgmma.fence.sync.aligned;" ::: "memory"); }
__device__ __forceinline__ void wg_commit() { asm volatile("wgmma.commit_group.sync.aligned;" ::: "memory"); }
template <int N> __device__ __forceinline__ void wg_wait() { asm volatile("wgmma.wait_group.sync.aligned %0;" ::"n"(N) : "memory"); }
template <int N> __device__ __forceinline__ void regfence(float (&d)[N]) {
#pragma unroll
  for (int i = 0; i < N; i++) asm volatile("" : "+f"(d[i])::"memory");
}
__device__ __forceinline__ void bar_cons() { asm volatile("bar.sync 1, 256;" ::: "memory"); }
__device__ __forceinline__ void fence_async() { asm volatile("fence.proxy.async.shared::cta;" ::: "memory"); }
struct Desc { uint32_t lo, hi; };
__device__ __forceinline__ Desc mkdesc(uint32_t base16, uint32_t off, uint32_t lbo, uint32_t sbo, uint32_t swz) {
  return Desc{base16 + ((off >> 4) | ((lbo >> 4) << 16)), (sbo >> 4) | (swz << 30)};
}
__device__ __forceinline__ uint4 ldll(const uint4* p) {
  uint4 v; asm volatile("ld.relaxed.gpu.global.v4.u32 {%0,%1,%2,%3}, [%4];" : "=r"(v.x), "=r"(v.y), "=r"(v.z), "=r"(v.w) : "l"(p) : "memory"); return v;
}
__device__ __forceinline__ uint2 ldll2(const uint2* p) {
  uint2 v; asm volatile("ld.relaxed.gpu.global.v2.u32 {%0,%1}, [%2];" : "=r"(v.x), "=r"(v.y) : "l"(p) : "memory"); return v;
}
__device__ __forceinline__ void stll(uint4* p, uint32_t x, uint32_t y, uint32_t z, uint32_t w) {
  asm volatile("st.relaxed.gpu.global.v4.u32 [%0], {%1,%2,%3,%4};" ::"l"(p), "r"(x), "r"(y), "r"(z), "r"(w) : "memory");
}
__device__ __forceinline__ void stll2(void* p, uint32_t x, uint32_t y) {
  asm volatile("st.relaxed.gpu.global.v2.u32 [%0], {%1,%2};" ::"l"(p), "r"(x), "r"(y) : "memory");
}
__device__ __forceinline__ int laneid() { int l; asm volatile("mov.u32 %0, %%laneid;" : "=r"(l)); return l; }
__device__ __forceinline__ uint32_t tg(uint32_t w, uint32_t tag) { return (w & ~1u) | tag; }
__device__ __forceinline__ uint32_t pack(float lo, float hi) {
  uint32_t r; asm("cvt.rn.bf16x2.f32 %0, %1, %2;" : "=r"(r) : "f"(hi), "f"(lo)); return r;
}
__device__ __forceinline__ float blo(uint32_t w) { return __uint_as_float(w << 16); }
__device__ __forceinline__ float bhi(uint32_t w) { return __uint_as_float(w & 0xffff0000u); }
__device__ __forceinline__ float ex2(float x) { float r; asm("ex2.approx.ftz.f32 %0, %1;" : "=f"(r) : "f"(x)); return r; }
__device__ __forceinline__ float rcp(float x) { float r; asm("rcp.approx.ftz.f32 %0, %1;" : "=f"(r) : "f"(x)); return r; }
__device__ __forceinline__ float qsum(float v) { v += __shfl_xor_sync(~0u, v, 1); v += __shfl_xor_sync(~0u, v, 2); return v; }
__device__ __forceinline__ void sts32(uint32_t a, uint32_t v) { asm volatile("st.shared.u32 [%0], %1;" ::"r"(a), "r"(v) : "memory"); }
__device__ __forceinline__ void sts16(uint32_t a, uint32_t v) { asm volatile("st.shared.u16 [%0], %1;" ::"r"(a), "h"((uint16_t)v) : "memory"); }
__device__ __forceinline__ void sts128(uint32_t a, uint32_t x, uint32_t y, uint32_t z, uint32_t w) {
  asm volatile("st.shared.v4.u32 [%0], {%1,%2,%3,%4};" ::"r"(a), "r"(x), "r"(y), "r"(z), "r"(w) : "memory");
}
__device__ __forceinline__ uint32_t sw128(int row, int col) { return row * 128 + ((((col >> 3) ^ row) & 7) << 4) + (col & 7) * 2; }

__device__ __forceinline__ void wgmma_rs56(float (&d)[28], const uint32_t a0, const uint32_t a1, const uint32_t a2, const uint32_t a3, Desc db, int sd) {
  asm volatile("{.reg .pred p; .reg .b64 da, db; setp.ne.b32 p, %33, 0; mov.b64 db, {%32, %34};\n wgmma.mma_async.sync.aligned.m64n56k16.f32.bf16.bf16 {%0,%1,%2,%3,%4,%5,%6,%7,%8,%9,%10,%11,%12,%13,%14,%15,%16,%17,%18,%19,%20,%21,%22,%23,%24,%25,%26,%27}, {%28,%29,%30,%31}, db, p, 1, 1, 1;}"
   : "+f"(d[0]),"+f"(d[1]),"+f"(d[2]),"+f"(d[3]),"+f"(d[4]),"+f"(d[5]),"+f"(d[6]),"+f"(d[7]),"+f"(d[8]),"+f"(d[9]),"+f"(d[10]),"+f"(d[11]),"+f"(d[12]),"+f"(d[13]),"+f"(d[14]),"+f"(d[15]),"+f"(d[16]),"+f"(d[17]),"+f"(d[18]),"+f"(d[19]),"+f"(d[20]),"+f"(d[21]),"+f"(d[22]),"+f"(d[23]),"+f"(d[24]),"+f"(d[25]),"+f"(d[26]),"+f"(d[27])
   : "r"(a0),"r"(a1),"r"(a2),"r"(a3),"r"(db.lo),"r"(sd),"r"(db.hi));
}
__device__ __forceinline__ void wgmma_rs64(float (&d)[32], const uint32_t a0, const uint32_t a1, const uint32_t a2, const uint32_t a3, Desc db, int sd) {
  asm volatile("{.reg .pred p; .reg .b64 da, db; setp.ne.b32 p, %37, 0; mov.b64 db, {%36, %38};\n wgmma.mma_async.sync.aligned.m64n64k16.f32.bf16.bf16 {%0,%1,%2,%3,%4,%5,%6,%7,%8,%9,%10,%11,%12,%13,%14,%15,%16,%17,%18,%19,%20,%21,%22,%23,%24,%25,%26,%27,%28,%29,%30,%31}, {%32,%33,%34,%35}, db, p, 1, 1, 1;}"
   : "+f"(d[0]),"+f"(d[1]),"+f"(d[2]),"+f"(d[3]),"+f"(d[4]),"+f"(d[5]),"+f"(d[6]),"+f"(d[7]),"+f"(d[8]),"+f"(d[9]),"+f"(d[10]),"+f"(d[11]),"+f"(d[12]),"+f"(d[13]),"+f"(d[14]),"+f"(d[15]),"+f"(d[16]),"+f"(d[17]),"+f"(d[18]),"+f"(d[19]),"+f"(d[20]),"+f"(d[21]),"+f"(d[22]),"+f"(d[23]),"+f"(d[24]),"+f"(d[25]),"+f"(d[26]),"+f"(d[27]),"+f"(d[28]),"+f"(d[29]),"+f"(d[30]),"+f"(d[31])
   : "r"(a0),"r"(a1),"r"(a2),"r"(a3),"r"(db.lo),"r"(sd),"r"(db.hi));
}
__device__ __forceinline__ void wgmma_rs192(float (&d)[96], const uint32_t a0, const uint32_t a1, const uint32_t a2, const uint32_t a3, Desc db, int sd) {
  asm volatile("{.reg .pred p; .reg .b64 db; setp.ne.b32 p, %101, 0; mov.b64 db, {%100, %102};\n wgmma.mma_async.sync.aligned.m64n192k16.f32.bf16.bf16 {%0,%1,%2,%3,%4,%5,%6,%7,%8,%9,%10,%11,%12,%13,%14,%15,%16,%17,%18,%19,%20,%21,%22,%23,%24,%25,%26,%27,%28,%29,%30,%31,%32,%33,%34,%35,%36,%37,%38,%39,%40,%41,%42,%43,%44,%45,%46,%47,%48,%49,%50,%51,%52,%53,%54,%55,%56,%57,%58,%59,%60,%61,%62,%63,%64,%65,%66,%67,%68,%69,%70,%71,%72,%73,%74,%75,%76,%77,%78,%79,%80,%81,%82,%83,%84,%85,%86,%87,%88,%89,%90,%91,%92,%93,%94,%95}, {%96,%97,%98,%99}, db, p, 1, 1, 1;}"
   : "+f"(d[0]),"+f"(d[1]),"+f"(d[2]),"+f"(d[3]),"+f"(d[4]),"+f"(d[5]),"+f"(d[6]),"+f"(d[7]),"+f"(d[8]),"+f"(d[9]),"+f"(d[10]),"+f"(d[11]),"+f"(d[12]),"+f"(d[13]),"+f"(d[14]),"+f"(d[15]),"+f"(d[16]),"+f"(d[17]),"+f"(d[18]),"+f"(d[19]),"+f"(d[20]),"+f"(d[21]),"+f"(d[22]),"+f"(d[23]),"+f"(d[24]),"+f"(d[25]),"+f"(d[26]),"+f"(d[27]),"+f"(d[28]),"+f"(d[29]),"+f"(d[30]),"+f"(d[31]),"+f"(d[32]),"+f"(d[33]),"+f"(d[34]),"+f"(d[35]),"+f"(d[36]),"+f"(d[37]),"+f"(d[38]),"+f"(d[39]),"+f"(d[40]),"+f"(d[41]),"+f"(d[42]),"+f"(d[43]),"+f"(d[44]),"+f"(d[45]),"+f"(d[46]),"+f"(d[47]),"+f"(d[48]),"+f"(d[49]),"+f"(d[50]),"+f"(d[51]),"+f"(d[52]),"+f"(d[53]),"+f"(d[54]),"+f"(d[55]),"+f"(d[56]),"+f"(d[57]),"+f"(d[58]),"+f"(d[59]),"+f"(d[60]),"+f"(d[61]),"+f"(d[62]),"+f"(d[63]),"+f"(d[64]),"+f"(d[65]),"+f"(d[66]),"+f"(d[67]),"+f"(d[68]),"+f"(d[69]),"+f"(d[70]),"+f"(d[71]),"+f"(d[72]),"+f"(d[73]),"+f"(d[74]),"+f"(d[75]),"+f"(d[76]),"+f"(d[77]),"+f"(d[78]),"+f"(d[79]),"+f"(d[80]),"+f"(d[81]),"+f"(d[82]),"+f"(d[83]),"+f"(d[84]),"+f"(d[85]),"+f"(d[86]),"+f"(d[87]),"+f"(d[88]),"+f"(d[89]),"+f"(d[90]),"+f"(d[91]),"+f"(d[92]),"+f"(d[93]),"+f"(d[94]),"+f"(d[95])
   : "r"(a0),"r"(a1),"r"(a2),"r"(a3),"r"(db.lo),"r"(sd),"r"(db.hi));
}
__device__ __forceinline__ void wgmma_rs32(float (&d)[16], const uint32_t a0, const uint32_t a1, const uint32_t a2, const uint32_t a3, Desc db, int sd) {
  asm volatile("{.reg .pred p; .reg .b64 db; setp.ne.b32 p, %21, 0; mov.b64 db, {%20, %22};\n wgmma.mma_async.sync.aligned.m64n32k16.f32.bf16.bf16 {%0,%1,%2,%3,%4,%5,%6,%7,%8,%9,%10,%11,%12,%13,%14,%15}, {%16,%17,%18,%19}, db, p, 1, 1, 1;}"
   : "+f"(d[0]),"+f"(d[1]),"+f"(d[2]),"+f"(d[3]),"+f"(d[4]),"+f"(d[5]),"+f"(d[6]),"+f"(d[7]),"+f"(d[8]),"+f"(d[9]),"+f"(d[10]),"+f"(d[11]),"+f"(d[12]),"+f"(d[13]),"+f"(d[14]),"+f"(d[15])
   : "r"(a0),"r"(a1),"r"(a2),"r"(a3),"r"(db.lo),"r"(sd),"r"(db.hi));
}
__device__ __forceinline__ void wgmma_ss32(float (&d)[16], Desc da, Desc db, int sd) {
  asm volatile("{.reg .pred p; .reg .b64 da, db; setp.ne.b32 p, %18, 0; mov.b64 da, {%16, %19}; mov.b64 db, {%17, %19};\n wgmma.mma_async.sync.aligned.m64n32k16.f32.bf16.bf16 {%0,%1,%2,%3,%4,%5,%6,%7,%8,%9,%10,%11,%12,%13,%14,%15}, da, db, p, 1, 1, 1, 1;}"
   : "+f"(d[0]),"+f"(d[1]),"+f"(d[2]),"+f"(d[3]),"+f"(d[4]),"+f"(d[5]),"+f"(d[6]),"+f"(d[7]),"+f"(d[8]),"+f"(d[9]),"+f"(d[10]),"+f"(d[11]),"+f"(d[12]),"+f"(d[13]),"+f"(d[14]),"+f"(d[15])
   : "r"(da.lo),"r"(db.lo),"r"(sd),"r"(db.hi));
}

__device__ __forceinline__ uint4 ldsm4(uint32_t a) {
  uint4 v; asm volatile("ldmatrix.sync.aligned.m8n8.x4.shared.b16 {%0,%1,%2,%3}, [%4];" : "=r"(v.x), "=r"(v.y), "=r"(v.z), "=r"(v.w) : "r"(a) : "memory"); return v;
}
__device__ __forceinline__ void mma16816(float (&d)[4], const uint4& a, uint32_t b0, uint32_t b1) {
  asm("mma.sync.aligned.m16n8k16.row.col.f32.bf16.bf16.f32 {%0,%1,%2,%3}, {%4,%5,%6,%7}, {%8,%9}, {%0,%1,%2,%3};"
      : "+f"(d[0]), "+f"(d[1]), "+f"(d[2]), "+f"(d[3]) : "r"(a.x), "r"(a.y), "r"(a.z), "r"(a.w), "r"(b0), "r"(b1));
}
__device__ __forceinline__ uint32_t bsub(uint32_t a, uint32_t b) { uint32_t r; asm("sub.bf16x2 %0, %1, %2;" : "=r"(r) : "r"(a), "r"(b)); return r; }
__device__ __forceinline__ uint32_t hint_ld(const uint32_t* p) { uint32_t v; asm volatile("ld.relaxed.gpu.global.u32 %0, [%1];" : "=r"(v) : "l"(p) : "memory"); return v; }
template <int S, int N, bool SPL = false, int T> __device__ __forceinline__ void ll_issue(uint4 (&v)[T], const uint4* p, int stride, const uint2* p2 = nullptr) {
#pragma unroll
  for (int i = S; i < S + N; i++) {
    if (SPL && i % 7 == 3) { const uint2 lo = ldll2(p2 + i * 64), hi = ldll2(p2 + i * 64 + 32); v[i] = make_uint4(lo.x, lo.y, hi.x, hi.y); }
    else v[i] = ldll(p + i * stride);
  }
}
template <int S, int N, bool SPL, int T> __device__ __forceinline__ void ll_check(uint4 (&v)[T], const uint4* p, int stride, uint32_t tag, const uint2* p2 = nullptr) {
#pragma unroll 1
  for (int it = 0; it < SPIN; it++) {
    uint32_t bad = 0;
#pragma unroll
    for (int i = S; i < S + N; i++) bad |= (v[i].x ^ tag) | ((SPL && i % 7 == 3) ? (v[i].z ^ tag) : 0u);
    if (!__any_sync(~0u, bad & 1)) break;
    ll_issue<S, N, SPL>(v, p, stride, p2);
  }
}
__device__ __forceinline__ void hint_post(uint32_t* p, uint32_t v, int lane) {
  if (lane == 0) asm volatile("st.relaxed.gpu.global.u32 [%0], %1;" ::"l"(p), "r"(v) : "memory");
}
__device__ __forceinline__ void hint_wait(const uint32_t* p, uint32_t s, uint32_t v = 0xffffu) {
#pragma unroll 1
  for (int it = 0; it < SPIN; it++) {
    if (__all_sync(~0u, v - s < 10u)) break;
    v = hint_ld(p);
  }
}
__device__ __forceinline__ void slice_store(uint4* pf, uint2* ph, const uint32_t (&w)[14], bool odd) {
#pragma unroll
  for (int u = 0; u < 3; u++)
    stll(pf + u * 32, odd ? w[4 * u + 2] : w[4 * u], odd ? w[4 * u + 3] : w[4 * u + 1], odd ? w[4 * u + 4] : w[4 * u + 2], odd ? w[4 * u + 5] : w[4 * u + 3]);
  stll2(ph, odd ? w[0] : w[12], odd ? w[1] : w[13]);
}
template <class F, class M> __device__ __forceinline__ void hedgehog(const float (&d)[28], F sink, M mid) {
  const float L2E = 1.4426950408889634f;
#define HX(G, p) ((p) < 6 ? d[((G) & 1) * 16 + ((p) >> 1) * 4 + ((p) & 1) + ((G) & 2)] : d[12 + (G)])
  float mx[4], mn[4], sp[4], sn[4], ep[4][7], en[4][7];
#pragma unroll
  for (int G = 0; G < 4; G++) {
    mx[G] = mn[G] = HX(G, 0);
#pragma unroll
    for (int p = 1; p < 7; p++) { mx[G] = fmaxf(mx[G], HX(G, p)); mn[G] = fminf(mn[G], HX(G, p)); }
  }
#pragma unroll
  for (int o = 1; o < 4; o <<= 1)
#pragma unroll
    for (int G = 0; G < 4; G++) { mx[G] = fmaxf(mx[G], __shfl_xor_sync(~0u, mx[G], o)); mn[G] = fminf(mn[G], __shfl_xor_sync(~0u, mn[G], o)); }
#pragma unroll
  for (int G = 0; G < 4; G++) {
    const float a = -mx[G] * L2E, b = mn[G] * L2E;
#pragma unroll
    for (int p = 0; p < 7; p++) { ep[G][p] = ex2(fmaf(HX(G, p), L2E, a)); en[G][p] = ex2(fmaf(HX(G, p), -L2E, b)); }
    sp[G] = ((ep[G][0] + ep[G][1]) + (ep[G][2] + ep[G][3])) + ((ep[G][4] + ep[G][5]) + ep[G][6]);
    sn[G] = ((en[G][0] + en[G][1]) + (en[G][2] + en[G][3])) + ((en[G][4] + en[G][5]) + en[G][6]);
    if (G == 1) mid();
  }
#pragma unroll
  for (int o = 1; o < 4; o <<= 1)
#pragma unroll
    for (int G = 0; G < 4; G++) { sp[G] += __shfl_xor_sync(~0u, sp[G], o); sn[G] += __shfl_xor_sync(~0u, sn[G], o); }
#pragma unroll
  for (int G = 0; G < 4; G++) {
    const float a = rcp(sp[G]), b = rcp(sn[G]);
#pragma unroll
    for (int p = 0; p < 7; p++) sink(G >> 1, G & 1, p, pack(ep[G][p] * a, en[G][p] * b));
  }
}
__device__ __forceinline__ void phi_gemm(const float (&x)[28], float (&y)[28], uint32_t wphi, float r0, float r1) {
  uint32_t f[14];
#pragma unroll
  for (int j = 0; j < 14; j++) f[j] = pack(x[2 * j] * (j & 1 ? r1 : r0), x[2 * j + 1] * (j & 1 ? r1 : r0));
  wg_fence();
#pragma unroll
  for (int ks = 0; ks < 3; ks++) wgmma_rs56(y, f[4 * ks], f[4 * ks + 1], f[4 * ks + 2], f[4 * ks + 3], mkdesc(wphi, ks * 2048, 1024, 1024, 1), ks);
  wgmma_rs56(y, f[12], f[13], 0u, 0u, mkdesc(wphi, 3 * 2048, 1024, 1024, 1), 1);
  wg_commit();
}
__device__ __forceinline__ void ln_stats(uint32_t (&xw)[4][4], float* sLN, int warp, int lane, uint4* dst) {
  const int g = lane >> 2; const bool full = warp < 4;
  float s0 = 0.f, s1 = 0.f;
#pragma unroll
  for (int u = 0; u < 4; u++) {
    s0 += (blo(xw[u][0]) + bhi(xw[u][0])) + (blo(xw[u][2]) + bhi(xw[u][2]));
    s1 += (blo(xw[u][1]) + bhi(xw[u][1])) + (blo(xw[u][3]) + bhi(xw[u][3]));
  }
  const float rc = full ? 1.f / 64 : 1.f / 48;
  s0 = qsum(s0); s1 = qsum(s1);
  const float a0 = s0 * rc, a1 = s1 * rc;
  float v0 = 0.f, v1 = 0.f;
#pragma unroll
  for (int u = 0; u < 4; u++)
    if (u < 3 || full) {
#pragma unroll
      for (int k = 0; k < 4; k += 2) {
        float a = blo(xw[u][k]) - a0, b = bhi(xw[u][k]) - a0, c2 = blo(xw[u][k + 1]) - a1, d2 = bhi(xw[u][k + 1]) - a1;
        v0 += a * a + b * b; v1 += c2 * c2 + d2 * d2;
      }
    }
  v0 = qsum(v0); v1 = qsum(v1);
  if ((lane & 3) == 0) *(float4*)(sLN + (g * 8 + warp) * 4) = make_float4(s0, v0, s1, v1);
  if (warp) { asm volatile("bar.arrive 7, 256;" ::: "memory"); return; }
  asm volatile("bar.sync 7, 256;" ::: "memory");
  const float4 ea = *(const float4*)(sLN + (g * 8 + (lane & 3)) * 4), eb = *(const float4*)(sLN + (g * 8 + 4 + (lane & 3)) * 4);
  const float m0 = qsum(ea.x + eb.x) * (1.f / 448), m1 = qsum(ea.z + eb.z) * (1.f / 448);
  const float d0 = ea.x * (1.f / 64) - m0, d1 = eb.x * (1.f / 48) - m0, d2 = ea.z * (1.f / 64) - m1, d3 = eb.z * (1.f / 48) - m1;
  v0 = qsum(ea.y + eb.y + 64.f * d0 * d0 + 48.f * d1 * d1); v1 = qsum(ea.w + eb.w + 64.f * d2 * d2 + 48.f * d3 * d3);
  if ((lane & 3) == 0) stll(dst + g, tg(__float_as_uint(m0), 1), __float_as_uint(rsqrtf(v0 * (1.f / 448) + 1e-5f)), __float_as_uint(m1), __float_as_uint(rsqrtf(v1 * (1.f / 448) + 1e-5f)));
}

__global__ void CLUSTER __launch_bounds__(384, 1)
fused_kernel(const __grid_constant__ CUtensorMap mQKV, const __grid_constant__ CUtensorMap mWO, const __grid_constant__ CUtensorMap mW1,
             const __grid_constant__ CUtensorMap mW1b, const __grid_constant__ CUtensorMap mW2, const __grid_constant__ CUtensorMap mW2b,
             const __grid_constant__ CUtensorMap mX, const __nv_bfloat16* __restrict__ wqkv, const __nv_bfloat16* __restrict__ wphi,
             const __nv_bfloat16* __restrict__ wo, const __nv_bfloat16* __restrict__ w1, const __nv_bfloat16* __restrict__ b1,
             const __nv_bfloat16* __restrict__ w2, const __nv_bfloat16* __restrict__ b2, __nv_bfloat16* __restrict__ out) {
  extern __shared__ __align__(1024) uint8_t sm[];
  const uint32_t sb = s2u(sm);
  const int tid = threadIdx.x, warp = __shfl_sync(~0u, tid >> 5, 0), lane = tid & 31,
            t = MAPPING ? (blockIdx.x >> 4) * 2 + (blockIdx.x & 1) : blockIdx.x >> 3, c = MAPPING ? (blockIdx.x >> 1) & 7 : blockIdx.x & 7;
  const uint32_t bfull = sb + OFF_BAR, bempty = bfull + 8 * NST;

#define XOFF(l) ((t * 128 + c * 16 + ((l) >> 2)) * 448 + warp * 16 + 2 * ((l) & 3))
  if (warp < 8) { MARK(0); GT(19); }
  if (tid == 256) {
    for (int s = 0; s < NST; s++) { mbar_init(bfull + 8 * s, 1); mbar_init(bempty + 8 * s, MC ? 16 : 8); }
    mbar_init(bempty + 8 * NST, 1);
    asm volatile("fence.mbarrier_init.release.cluster;" ::: "memory");
    fence_async();
    mbar_expect(bempty + 8 * NST, 114688);
    for (int i = 0; i < 7; i++)
      asm volatile("cp.async.bulk.tensor.2d.shared::cluster.global.mbarrier::complete_tx::bytes [%0], [%1, {%3, %4}], [%2];"
                   ::"r"(sb + 2 * STAGE + i * 16384), "l"(&mX), "r"(bempty + 8 * NST), "r"(64 * i), "r"(128 * t) : "memory");
  }
  asm volatile("barrier.cluster.arrive.release.aligned; barrier.cluster.wait.acquire.aligned;" ::: "memory");
  if (warp >= 8) {
    asm volatile("setmaxnreg.dec.sync.aligned.u32 24;");
    auto issue = [&](int i, int s) {
      const uint32_t dst = sb + s * STAGE, bar = bfull + 8 * s;
      mbar_expect(bar, STAGE);
#pragma unroll 1
      for (int rk = MC ? (blockIdx.x & 1) : 0; rk < (MC ? (blockIdx.x & 1) + 1 : 2); rk++)
      if (i < 4) tma2d(dst + rk * 14336, &mQKV, 448 + 448 * rk + 56 * c, 112 * i, bar);
      else if (i < 8) tma2d(dst + rk * 14336, i < 6 ? &mQKV : &mWO, (i < 6 ? 56 : 64) * c, 224 * (i & 1) + 112 * rk, bar);
      else if (i < 15) { const int k0 = 64 * ((i - 8 + c) % 7) + 32 * rk;
        tma3d(dst + rk * 12288, &mW1, 0, k0, 3 * c, bar); tma2d(dst + 24576 + rk * 2048, &mW1b, 1536 + 32 * c, k0, bar); }
      else { tma2d(dst + rk * 12288, &mW2, 64 * (i - 15), 192 * c + 96 * rk, bar); tma2d(dst + 24576 + rk * 2048, &mW2b, 64 * (i - 15), 1536 + 32 * c + 16 * rk, bar); }
    };
    auto colsum = [&](int job) {
        const int ld4 = job < 112 ? 448 : 336;
        const uint2* wp = (job < 112 ? (const uint2*)w1 + job * 4 : (const uint2*)wqkv + (job - 112) * 4) + (lane >> 2) * ld4 + (lane & 3);
        float s0 = 0.f, s1 = 0.f, s2 = 0.f, s3 = 0.f;
#pragma unroll 8
        for (int i = 0; i < 56; i++) { const uint2 v = __ldg(wp + i * 8 * ld4); s0 += blo(v.x); s1 += bhi(v.x); s2 += blo(v.y); s3 += bhi(v.y); }
#pragma unroll 1
        for (int o = 4; o < 32; o <<= 1) { s0 += __shfl_xor_sync(~0u, s0, o); s1 += __shfl_xor_sync(~0u, s1, o); s2 += __shfl_xor_sync(~0u, s2, o); s3 += __shfl_xor_sync(~0u, s3, o); }
        if (lane < 4) stll(g_CS + job * 4 + lane, tg(__float_as_uint(s0), 1), __float_as_uint(s1), __float_as_uint(s2), __float_as_uint(s3));
      };
    if (warp == 8) {
      int s = 0; uint32_t ph = 1;
      for (int n = 0; n < 44; n++) {
        if (n == PACE) asm volatile("bar.sync 2, 288;" ::: "memory");
        mbar_wait(bempty + 8 * s, ph);
        if (n == 22) {
          uint32_t v = 0;
#pragma unroll 1
          for (int it = 0; it < SPIN && v < 32; it++) asm volatile("ld.acquire.gpu.global.u32 %0, [%1];" : "=r"(v) : "l"(g_WQF + c) : "memory");
          asm volatile("fence.proxy.async.global;" ::: "memory");
        }
        if (lane == 0) {
          if (n >= 22 && n < 28) {
            mbar_expect(bfull + 8 * s, STAGE);
            asm volatile("cp.async.bulk.shared::cluster.global.mbarrier::complete_tx::bytes [%0], [%1], %2, [%3];"
                         ::"r"(sb + s * STAGE), "l"(g_WQ + c * 10752 + (n - 22) * (STAGE / 16)), "r"(STAGE), "r"(bfull + 8 * s) : "memory");
          } else issue(n >= 22 ? n - 22 : n, s);
        }
        __syncwarp();
        if (++s == NST) { s = 0; ph ^= 1; }
      }
    } else if (warp == 9) {
      mbar_wait(bfull + 8 * 1, 0);
      if (lane == 0) {
        l2pf((const uint8_t*)wo + blockIdx.x * 3136, 3136);
        l2pf((const uint8_t*)w1 + blockIdx.x * 12544, 12544);
        l2pf((const uint8_t*)w2 + blockIdx.x * 12544, 12544);
      }
      if (blockIdx.x < 112) colsum(blockIdx.x);
      asm volatile("bar.sync 6, 96;" ::: "memory");
#pragma unroll 1
      for (int i = 0; i < 4; i++) {
        const int e = lane < 28 ? lane + 28 * (i & 1) : 0;
        const bool ok = i < 2 || (e < 48 && (e & 15) < 14);
        const int e4 = i < 2 ? (e < 48 ? 48 * c + e : 336 + 8 * c + e) : ok ? 448 + 112 * (e >> 4) + 14 * c + (e & 15) : 448;
        uint4 cv[1];
        ll_issue<0, 1>(cv, g_CS + e4, 0); ll_check<0, 1, false>(cv, g_CS + e4, 0, 1u);
        const uint2 bb = __ldg((const uint2*)b1 + (i < 2 ? e4 : 0));
        const uint32_t h0 = pack(__uint_as_float(cv[0].x), __uint_as_float(cv[0].y)), h1 = pack(__uint_as_float(cv[0].z), __uint_as_float(cv[0].w));
        const uint32_t l0 = pack(__uint_as_float(cv[0].x) - blo(h0), __uint_as_float(cv[0].y) - bhi(h0)), l1 = pack(__uint_as_float(cv[0].z) - blo(h1), __uint_as_float(cv[0].w) - bhi(h1));
#pragma unroll 1
        for (int j = 0; j < (i < 2 ? 5 : 3); j++) {
          const int r = i < 2 ? j : j + 5;
          const uint32_t ad = sb + OFF_CB + (e >> 3) * 512 + r * 64 + ((((e >> 1) ^ (r >> 1)) & 3) << 4) + (e & 1) * 8;
          sts32(ad, j < 2 ? h0 : j == 2 ? l0 : bb.x); sts32(ad + 4, j < 2 ? h1 : j == 2 ? l1 : bb.y);
        }
        if (i & 1) { fence_async(); asm volatile("bar.arrive %0, 288;" ::"r"(i == 1 ? 4 : 8) : "memory"); }
      }
    } else if (warp >= 10) {
      const int h = warp - 10;
      uint32_t wv[13];
#pragma unroll
      for (int i = 0; i < 13; i++) { const int e = lane + 32 * i; wv[i] = e < 392 ? __ldg((const uint32_t*)wphi + (2 * c + h) * 392 + e) : 0u; }
#pragma unroll 1
      for (int e = h * 32 + lane; e < 672; e += 64) sts128(sb + OFF_WPHI + e * 16, 0, 0, 0, 0);
      asm volatile("bar.arrive 6, 96;" ::: "memory");
#pragma unroll 1
      for (int i = 0; i < 4; i++) sts128(sb + OFF_PHIK + sw128(h * 128 + i * 32 + lane, 56), 0, 0, 0, 0);
      asm volatile("bar.sync 5, 64;" ::: "memory");
#pragma unroll
      for (int i = 0; i < 13; i++) {
        const int e = lane + 32 * i, d = e / 14, f2 = 2 * (e - 14 * d), k = 28 * h + d;
        if (e < 392) {
          if (f2 < 24) sts32(sb + OFF_WPHI + sw128(k, 32 * h + f2), wv[i]);
          else { sts16(sb + OFF_WPHI + sw128(k, 2 * f2 - 24 + h), wv[i]); sts16(sb + OFF_WPHI + sw128(k, 2 * f2 - 22 + h), wv[i] >> 16); }
        }
      }
      fence_async();
      asm volatile("bar.arrive 3, 320;" ::: "memory");
      mbar_wait(bfull + 8 * 5, 0);
#pragma unroll 2
      for (int e = t * 672 + h * 32 + lane; e < t * 672 + 672; e += 64) {
        const int r = e >> 3, st = r / 224, rr = r - st * 224, ch = (e & 7) ^ (rr & 7);
        const int k = st < 4 ? 112 * st + (rr >= 112 ? rr - 112 : rr) : 224 * (st - 4) + rr, col = (st < 4 ? (rr >= 112 ? 896 : 448) : 0) + 56 * c + 8 * ch;
        g_WQ[c * 10752 + e] = ch < 7 ? __ldg((const uint4*)(wqkv + k * 1344 + col)) : make_uint4(0, 0, 0, 0);
      }
      __syncwarp();
      if (lane == 0) asm volatile("red.release.gpu.global.add.u32 [%0], 1;" ::"l"(g_WQF + c) : "memory");
      if (h == 0 && blockIdx.x < 84) colsum(112 + blockIdx.x);
    }
  } else {
  asm volatile("setmaxnreg.inc.sync.aligned.u32 240;");

  const int wg = warp >> 2, g = lane >> 2, q = lane & 3;
  const int row0 = warp * 16 + g;
#define PTRS const int ln_ = laneid(); \
  uint4* const fm = g_F + ((t * 8 + warp) * 28) * 32 + ln_;            \
  uint4* const fr = g_F + ((t * 8 + c) * 28 + warp) * 32 + ln_;        \
  uint4* const sf = fm + (7 * (c >> 1) + 4 * (c & 1)) * 32;             \
  uint2* const f2 = (uint2*)(fm - ln_) + ln_;                           \
  uint2* const sh = f2 + (7 * (c >> 1) + 3) * 64 + 32 * (c & 1);        \
  uint32_t* const hme = g_H + (t * 8 + warp) * 8 + c; \
  const uint32_t* const hrow = g_H + (t * 8 + warp) * 8 + (ln_ & 7); \
  (void)fm; (void)fr; (void)sf; (void)f2; (void)sh; (void)hme; (void)hrow;
  float* sLN = (float*)(sm + OFF_V);
  const uint32_t sPK = sb + OFF_PHIK, sV = sb + OFF_V, d16 = (sb & 0x3FFFF) >> 4;
    uint32_t xw[4][4];
#pragma unroll
  for (int i = 0; i < 16; i++) xw[i >> 2][i & 3] = 0;
  int cs = 0, rs = 0; uint32_t cph = 0;
  auto acquire = [&]() -> uint32_t { mbar_wait(bfull + 8 * cs, cph); const uint32_t a = d16 + cs * (STAGE >> 4); if (++cs == NST) { cs = 0; cph ^= 1; } return a; };
  int nrel = 44 - NST;
  auto release = [&]() { if (lane < 1 + MC && nrel > 0) mbar_arrive_cl(bempty + 8 * rs, lane); nrel--; if (++rs == NST) rs = 0; };

#define RISSUE(m, P, XA, XB, BA, BB) { ll_issue<0, 8>(P, pr + (m) * 256, 896); \
      { const uint4 v_ = ldll(fr + X1 + (m) * 256); XA = make_uint2(v_.x, v_.y); XB = make_uint2(v_.z, v_.w); } \
      const uint32_t* bp = (const uint32_t*)(b2 + 128 * (m) + 16 * warp) + (ln_ & 3); BA = __ldg(bp); BB = __ldg(bp + 4); }
#define REDU(m, P, XA, XB, BA, BB) { ll_check<0, 8, false>(P, pr + (m) * 256, 896, ptag); \
      float e[8] = {blo(XA.x) + blo(BA), bhi(XA.x) + bhi(BA), blo(XA.y) + blo(BA), bhi(XA.y) + bhi(BA), blo(XB.x) + blo(BB), bhi(XB.x) + bhi(BB), blo(XB.y) + blo(BB), bhi(XB.y) + bhi(BB)}; \
      _Pragma("unroll") for (int i = 0; i < 8; i++) { e[0] += blo(P[i].x); e[1] += bhi(P[i].x); e[2] += blo(P[i].y); e[3] += bhi(P[i].y); \
        e[4] += blo(P[i].z); e[5] += bhi(P[i].z); e[6] += blo(P[i].w); e[7] += bhi(P[i].w); } \
      xw[m][0] = pack(e[0], e[1]); xw[m][1] = pack(e[2], e[3]); xw[m][2] = pack(e[4], e[5]); xw[m][3] = pack(e[6], e[7]); }
#define RPUB(m) stll(fr + XR + (m) * 256, tg(xw[m][0], 0), xw[m][1], xw[m][2], xw[m][3]);
#define RLAST(ptag_, hv) { const uint32_t ptag = ptag_; const uint4* pr = g_P + ((t * 8 + c) * 8 * 28 + warp) * 32 + ln_; uint4 p[8]; uint2 xa, xb; uint32_t ba, bb; \
      hint_wait(g_H + (t * 8 + c) * 8 + (ln_ & 7), hv); RISSUE(3, p, xa, xb, ba, bb) REDU(3, p, xa, xb, ba, bb) }
#pragma unroll 1
  for (int L = 0; L < 2; L++) {
    const uint32_t tag = 1 - L;
    uint32_t phq[2][2][7];
    const uint32_t hs = 10 * L;
    {
      PTRS
      uint4 a[28];
      const uint4* pa = fm + XR;
      uint32_t fa = 0, fb = 0;
      float r0 = 1.f, r1 = 1.f;
      if (L == 0) {
        mbar_wait(bempty + 8 * NST, 0);
        MARK(1);
        const int row = warp * 16 + (ln_ & 15);
        const uint32_t xb = sb + 2 * STAGE + row * 128;
        float cs_[4][4] = {}, c0[2][4] = {}, c1[2][4] = {};
#pragma unroll
        for (int ks = 0; ks < 28; ks++) { a[ks] = ldsm4(xb + (ks >> 2) * 16384 + (((2 * (ks & 3) + (ln_ >> 4)) ^ (row & 7)) << 4)); mma16816(cs_[ks & 3], a[ks], 0x3F803F80u, 0x3F803F80u); }
        if (c < 7) {
#pragma unroll
          for (int u = 0; u < 4; u++) { const uint4 v = ldsm4(xb + c * 16384 + (((2 * u + (ln_ >> 4)) ^ (row & 7)) << 4)); stll(fm + XR + 128 * c + u * 32, tg(v.x, tag), v.y, v.z, v.w); }
        }
        const float m0 = ((cs_[0][0] + cs_[1][0]) + (cs_[2][0] + cs_[3][0])) * (1.f / 448), m1 = ((cs_[0][2] + cs_[1][2]) + (cs_[2][2] + cs_[3][2])) * (1.f / 448);
        const uint32_t mb0 = pack(m0, m0), mb1 = pack(m1, m1);
        asm volatile("bar.arrive 2, 288;" ::"r"(mb0) : "memory");
#pragma unroll
        for (int ks = 0; ks < 28; ks++) {
          a[ks].x = bsub(a[ks].x, mb0); a[ks].y = bsub(a[ks].y, mb1); a[ks].z = bsub(a[ks].z, mb0); a[ks].w = bsub(a[ks].w, mb1);
          mma16816(c0[ks & 1], a[ks], a[ks].x, a[ks].z); mma16816(c1[ks & 1], a[ks], a[ks].y, a[ks].w);
        }
        const int src = (ln_ & 28) | (g >> 1);
        const float q0 = __shfl_sync(~0u, (g & 1) ? c0[0][1] + c0[1][1] : c0[0][0] + c0[1][0], src), q1 = __shfl_sync(~0u, (g & 1) ? c1[0][3] + c1[1][3] : c1[0][2] + c1[1][2], src);
        const float e0 = m0 - blo(mb0), e1 = m1 - blo(mb1);
        r0 = rsqrtf(fmaxf(q0 * (1.f / 448) - e0 * e0, 0.f) + 1e-5f); r1 = rsqrtf(fmaxf(q1 * (1.f / 448) - e1 * e1, 0.f) + 1e-5f);
      } else {
        ll_issue<0, 14>(a, pa, 32);
        if (wg == 0) { RLAST(1u, 10u) xw[3][0] = tg(xw[3][0], 0); RPUB(3) } else { xw[3][0] = xw[3][1] = xw[3][2] = xw[3][3] = 0; }
        MARK(20);
        ll_issue<14, 7>(a, pa, 32);
        ln_stats(xw, sLN, warp, lane, g_S2 + (t * 8 + c) * 8);
      }
      MARK(2 + L * 19);
      float ak[28], av[28], aq[28], pp[28];
#define KVSTAGE(i) { if (L) ll_check<7 * i, 7, false>(a, pa, 32, tag); const uint32_t st = acquire(); wg_fence(); \
      _Pragma("unroll") for (int ks = 0; ks < 7; ks++) { const uint4 f = a[7 * i + ks]; \
        wgmma_rs56(ak, f.x, f.y, f.z, f.w, mkdesc(st, ks * 2048, 1024, 1024, 1), i | ks); \
        wgmma_rs56(av, f.x, f.y, f.z, f.w, mkdesc(st, 14336 + ks * 2048, 1024, 1024, 1), i | ks); } \
      wg_commit(); if (i > 0) { wg_wait<1>(); release(); } }
      KVSTAGE(0) KVSTAGE(1)
      uint4 sv[1];
      const uint4* ps = g_S2 + (t * 8 + warp) * 8 + (ln_ >> 2);
      if (L) { ll_issue<21, 7>(a, pa, 32); ll_issue<0, 1>(sv, ps, 0); }
      KVSTAGE(2) KVSTAGE(3)
      if (L) {
        asm volatile("bar.sync 8, 288;" ::: "memory");
        ll_check<0, 1, false>(sv, ps, 0, 1u);
        const float m0 = -__uint_as_float(sv[0].x), m1 = -__uint_as_float(sv[0].z), h0 = blo(pack(m0, 0.f)), h1 = blo(pack(m1, 0.f));
        r0 = __uint_as_float(sv[0].y); r1 = __uint_as_float(sv[0].w);
        fa = q == 2 ? pack(0.f, h0) : q == 3 ? pack(m0 - h0, h0) : 0u; fb = q == 2 ? pack(0.f, h1) : q == 3 ? pack(m1 - h1, h1) : 0u;
      } else asm volatile("bar.sync 3, 320;" ::: "memory");
      wg_fence();
      wgmma_rs56(ak, fa, fb, 0u, 0u, mkdesc(d16, OFF_CB + 1024, 512, 0, 2), 1);
      wgmma_rs56(av, fa, fb, 0u, 0u, mkdesc(d16, OFF_CB + 2048, 512, 0, 2), 1);
      wg_commit();
      wg_wait<0>(); release(); regfence(ak); regfence(av);
      MARK(3 + L * 19);
      phi_gemm(ak, pp, d16 + (OFF_WPHI >> 4), r0, r1);
#pragma unroll
      for (int j = 0; j < 7; j++) {
        const int n = 8 * j + 2 * q, n2 = n < 28 ? n : n + 4;
        sts32(sV + sw128(row0, n2), pack(av[4 * j] * r0, av[4 * j + 1] * r0)); sts32(sV + sw128(row0 + 8, n2), pack(av[4 * j + 2] * r1, av[4 * j + 3] * r1));
      }
      { const int n2 = 28 + 2 * (q & 1) + 32 * (q >> 1); const uint32_t v = (q & 1) ? 0u : 0x3F80u; sts32(sV + sw128(row0, n2), v); sts32(sV + sw128(row0 + 8, n2), v); }
      wg_wait<0>(); regfence(pp);
      hedgehog(pp, [&](int r, int h, int p, uint32_t v) { sts32(sPK + h * 16384 + sw128(row0 + 8 * r, 8 * p + 2 * q), v); }, [] {});
      fence_async();
      bar_cons();
      MARK(4 + L * 19);
      float kv[16];
      wg_fence();
#pragma unroll
      for (int ks = 0; ks < 8; ks++) wgmma_ss32(kv, mkdesc(d16 + wg * 1024, OFF_PHIK + ks * 2048, 1024, 1024, 1), mkdesc(d16 + wg * 4, OFF_V + ks * 2048, 1024, 1024, 1), ks);
      wg_commit(); wg_wait<0>(); regfence(kv);
      const int ln2 = laneid();
#pragma unroll
      for (int u = 0; u < 4; u++) {
        float e[4];
#pragma unroll
        for (int i = 0; i < 4; i++) e[i] = kv[4 * u + i];
        stll(g_KVP + (c * 16 + t) * 1024 + wg * 512 + u * 128 + (warp & 3) * 32 + ln2, tg(__float_as_uint(e[0]), tag), __float_as_uint(e[1]), __float_as_uint(e[2]), __float_as_uint(e[3]));
      }
      MARK(5 + L * 19);
      uint4 k4[4];
      const uint4* pk = g_KVP + (c * 16 + 4 * (ln2 & 3)) * 1024 + 64 * t + warp * 8 + (ln2 >> 2);
#pragma unroll
      for (int i = 0; i < 2; i++) {
        const uint32_t st = acquire(); wg_fence();
#pragma unroll
        for (int ks = 0; ks < 14; ks++) { const uint4 f = a[14 * i + ks]; wgmma_rs56(aq, f.x, f.y, f.z, f.w, mkdesc(st, ks * 2048, 1024, 1024, 1), i | ks); }
        if (i == 1) wgmma_rs56(aq, fa, fb, 0u, 0u, mkdesc(d16, OFF_CB, 512, 0, 2), 1);
        wg_commit();
        if (i == 0) ll_issue<0, 4>(k4, pk, 1024);
      }
      ll_check<0, 4, false>(k4, pk, 1024, tag);
      float s0 = 0, s1 = 0, s2 = 0, s3 = 0;
#pragma unroll
      for (int i = 0; i < 4; i++) { s0 += __uint_as_float(k4[i].x); s1 += __uint_as_float(k4[i].y); s2 += __uint_as_float(k4[i].z); s3 += __uint_as_float(k4[i].w); }
      s0 = qsum(s0); s1 = qsum(s1); s2 = qsum(s2); s3 = qsum(s3);
      if (q == 0) stll2(g_KVR + c * 1024 + 64 * t + warp * 8 + (ln2 >> 2), tg(pack(s0, s1), tag), pack(s2, s3));
      MARK(6 + L * 19);
      wg_wait<0>(); release(); release(); regfence(aq);
      phi_gemm(aq, pp, d16 + (OFF_WPHI >> 4), r0, r1);
      bar_cons();
#pragma unroll
      for (int i = 0; i < 4; i++) sts128(sV + warp * 2048 + (lane + i * 32) * 16, 0, 0, 0, 0);
      wg_wait<0>(); regfence(pp);
      uint2 r[4];
      const uint2* pr = g_KVR + c * 1024 + wg * 512 + (warp & 3) * 32 + ln2;
      hedgehog(pp, [&](int r, int h, int p, uint32_t v) { phq[r][h][p] = v; }, [&] {
#pragma unroll
        for (int u = 0; u < 4; u++) r[u] = ldll2(pr + u * 128); });
      MARK(7 + L * 19);
#pragma unroll 1
      for (int it = 0; it < SPIN; it++) {
        if (!__any_sync(~0u, ((r[0].x ^ tag) | (r[1].x ^ tag) | (r[2].x ^ tag) | (r[3].x ^ tag)) & 1)) break;
#pragma unroll
        for (int u = 0; u < 4; u++) r[u] = ldll2(pr + u * 128);
      }
#pragma unroll
      for (int u = 0; u < 4; u++) {
        const int d = 8 * u + 2 * q;
        if (d < 28) { sts32(sV + sw128(row0, 28 * wg + d), r[u].x); sts32(sV + sw128(row0 + 8, 28 * wg + d), r[u].y); }
        else if (d == 28) {
#pragma unroll
          for (int j = 0; j < 4; j++) { sts16(sV + sw128(row0, 56 + 2 * j + wg), r[u].x); sts16(sV + sw128(row0 + 8, 56 + 2 * j + wg), r[u].y); }
        }
      }
      fence_async();
      bar_cons();
      MARK(8 + L * 19);
      float o[32];
      wg_fence();
#pragma unroll
      for (int ks = 0; ks < 8; ks++) {
        const int h = ks >> 2, p = 2 * (ks & 3);
        wgmma_rs64(o, phq[0][h][p], phq[1][h][p], p < 6 ? phq[0][h][p < 6 ? p + 1 : 0] : 0u, p < 6 ? phq[1][h][p < 6 ? p + 1 : 0] : 0u, mkdesc(d16, OFF_V + ks * 2048, 1024, 1024, 1), ks);
      }
      wg_commit(); wg_wait<0>(); regfence(o);
      const float iA0 = rcp(o[28] + 1e-6f), iB0 = rcp(o[29] + 1e-6f), iA1 = rcp(o[30] + 1e-6f), iB1 = rcp(o[31] + 1e-6f);
      uint32_t w[14];
      { PTRS
#pragma unroll
      for (int j = 0; j < 7; j++) {
        const bool hb = 8 * j + 2 * q >= 28; const float i0 = hb ? iB0 : iA0, i1 = hb ? iB1 : iA1;
        w[2 * j] = pack(o[4 * j] * i0, o[4 * j + 1] * i0); w[2 * j + 1] = pack(o[4 * j + 2] * i1, o[4 * j + 3] * i1);
        if (j == 0 || ((j ^ c) & 1) == 0) w[2 * j] = tg(w[2 * j], tag);
      }
      slice_store(sf + OO, sh + 2 * OO, w, c & 1);
      hint_post(hme, hs + 2, lane); }
    }
    MARK(9 + L * 19);
    uint4 xr[4];
    if (c < 7) {
      PTRS
      ll_issue<0, 4>(xr, fm + XR + 128 * c, 32);
      uint4 a[28];
      const uint4* pa = fm + OO;
      hint_wait(hrow, hs + 2);
      MARK(10 + L * 19);
      ll_issue<0, 28, true>(a, pa, 32, f2 + 2 * OO);
      float y[32];
      uint32_t st;
#define WOSTEP(i) { ll_check<7 * i, 7, true>(a, pa, 32, tag, f2 + 2 * OO); if (!(i & 1)) st = acquire(); wg_fence(); \
      _Pragma("unroll") for (int ks = 0; ks < 7; ks++) { const uint4 f = a[7 * i + ks]; \
        wgmma_rs64(y, f.x, f.y, f.z, f.w, mkdesc(st, ((i & 1) * 7 + ks) * 2048, 1024, 1024, 1), i | ks); } wg_commit(); }
      WOSTEP(0) WOSTEP(1) WOSTEP(2) WOSTEP(3)
      ll_check<0, 4, false>(xr, fm + XR + 128 * c, 32, tag);
      wg_wait<0>(); regfence(y);
      MARK(11 + L * 19);
#pragma unroll
      for (int u = 0; u < 4; u++) {
        xr[u].x = tg(pack(blo(xr[u].x) + y[8 * u], bhi(xr[u].x) + y[8 * u + 1]), tag); xr[u].y = pack(blo(xr[u].y) + y[8 * u + 2], bhi(xr[u].y) + y[8 * u + 3]);
        xr[u].z = pack(blo(xr[u].z) + y[8 * u + 4], bhi(xr[u].z) + y[8 * u + 5]); xr[u].w = pack(blo(xr[u].w) + y[8 * u + 6], bhi(xr[u].w) + y[8 * u + 7]);
        stll(fm + X1 + 128 * c + u * 32, xr[u].x, xr[u].y, xr[u].z, xr[u].w);
      }
      hint_post(hme, hs + 3, lane);
    } else {
      PTRS
      hint_post(hme, hs + 3, lane);
      acquire(); acquire();
      hint_wait(g_H + (t * 8 + warp) * 8, hs + 3);
      ll_issue<0, 4>(xr, fm + X1, 32); ll_check<0, 4, false>(xr, fm + X1, 32, tag);
      MARK(10 + L * 19); MARK(11 + L * 19);
    }
    uint32_t hf[56];
    float rr0, rr1;
    {
      PTRS
      uint4 a[28];
      const uint4* pa = fm + X1;
      auto grp = [&](int i) -> const uint4* { const int k = i + c; return pa + ((k >= 7 ? k - 7 : k) - i) * 128; };
#pragma unroll
      for (int u = 0; u < 4; u++) a[u] = xr[u];
      float y[96], z[16];
#define F1STAGE(i) { if (i > 0) ll_check<4 * i, 4, false>(a, grp(i), 32, tag); const uint32_t st = acquire(); wg_fence(); \
      _Pragma("unroll") for (int ks = 0; ks < 4; ks++) { const uint4 f = a[4 * i + ks]; \
        wgmma_rs192(y, f.x, f.y, f.z, f.w, mkdesc(st, (ks >> 1) * 12288 + (ks & 1) * 2048, 4096, 1024, 1), i | ks); \
        wgmma_rs32(z, f.x, f.y, f.z, f.w, mkdesc(st, 24576 + ks * 1024, 512, 512, 2), i | ks); } \
      wg_commit(); if (i > 0) { wg_wait<1>(); release(); if (i < 4) ll_issue<(i < 4 ? 4 * i + 12 : 0), 4>(a, grp(i + 3), 32); } }
      F1STAGE(0)
      hint_wait(hrow, hs + 3);
      MARK(12 + L * 19);
      ll_issue<4, 4>(a, grp(1), 32); ll_issue<8, 4>(a, grp(2), 32); ll_issue<12, 4>(a, grp(3), 32);
      if (c < 7) {
        float s0 = 0.f, s1 = 0.f, v0 = 0.f, v1 = 0.f;
#pragma unroll
        for (int u = 0; u < 4; u++) { s0 += (blo(xr[u].x) + bhi(xr[u].x)) + (blo(xr[u].z) + bhi(xr[u].z)); s1 += (blo(xr[u].y) + bhi(xr[u].y)) + (blo(xr[u].w) + bhi(xr[u].w)); }
        s0 = qsum(s0) * (1.f / 64); s1 = qsum(s1) * (1.f / 64);
#pragma unroll
        for (int u = 0; u < 4; u++) {
          const float d0 = blo(xr[u].x) - s0, d1 = bhi(xr[u].x) - s0, d2 = blo(xr[u].z) - s0, d3 = bhi(xr[u].z) - s0;
          const float d4 = blo(xr[u].y) - s1, d5 = bhi(xr[u].y) - s1, d6 = blo(xr[u].w) - s1, d7 = bhi(xr[u].w) - s1;
          v0 += (d0 * d0 + d1 * d1) + (d2 * d2 + d3 * d3); v1 += (d4 * d4 + d5 * d5) + (d6 * d6 + d7 * d7);
        }
        v0 = qsum(v0); v1 = qsum(v1);
        if (q == 0) stll(g_ST + ((t * 8 + warp) * 8 + c) * 8 + (ln_ >> 2), tg(__float_as_uint(s0), tag), __float_as_uint(v0), __float_as_uint(s1), __float_as_uint(v1));
      }
      release(); release();
      F1STAGE(1) MARK(13 + L * 19); F1STAGE(2) F1STAGE(3)
      uint4 sv[2];
      const uint4* ps = g_ST + ((t * 8 + warp) * 8 + 2 * (laneid() & 3)) * 8 + (laneid() >> 2);
      ll_issue<0, 2>(sv, ps, q < 3 ? 8 : 0);
      F1STAGE(4)
      ll_check<0, 2, false>(sv, ps, q < 3 ? 8 : 0, tag);
      const float wb = q < 3 ? 1.f : 0.f;
      const float ma = __uint_as_float(sv[0].x), mb = __uint_as_float(sv[1].x), mc = __uint_as_float(sv[0].z), md = __uint_as_float(sv[1].z);
      const float m0 = qsum(ma + wb * mb) * (1.f / 7), m1 = qsum(mc + wb * md) * (1.f / 7);
      const float v0 = qsum(__uint_as_float(sv[0].y) + 64.f * (ma - m0) * (ma - m0) + wb * (__uint_as_float(sv[1].y) + 64.f * (mb - m0) * (mb - m0)));
      const float v1 = qsum(__uint_as_float(sv[0].w) + 64.f * (mc - m1) * (mc - m1) + wb * (__uint_as_float(sv[1].w) + 64.f * (md - m1) * (md - m1)));
      const float e0 = v0 * (1.f / 448) + 1e-5f, e1 = v1 * (1.f / 448) + 1e-5f;
      rr0 = 1.f / e0; rr1 = 1.f / e1;
      auto fold = [&](float m, float sd) -> uint32_t {
        const float mh = blo(pack(-m, 0.f)), sh_ = blo(pack(sd, 0.f));
        return q == 0 ? pack(mh, -m - mh) : q == 1 ? pack(mh, sh_) : q == 2 ? pack(sd - sh_, 0.f) : 0u;
      };
      const uint32_t fa = fold(m0, sqrtf(e0)), fb = fold(m1, sqrtf(e1));
      if (L == 0) asm volatile("bar.sync 4, 288;" ::: "memory");
      wg_fence();
      wgmma_rs192(y, fa, fb, 0u, 0u, mkdesc(d16, OFF_CB + 0, 512, 0, 2), 1);
      wgmma_rs32(z, fa, fb, 0u, 0u, mkdesc(d16, OFF_CB + 3072, 512, 0, 2), 1);
      F1STAGE(5) F1STAGE(6)
      wg_wait<0>(); release(); regfence(y); regfence(z);
      MARK(14 + L * 19);
#pragma unroll
      for (int j = 0; j < 56; j++) {
        uint32_t r; asm("cvt.rn.relu.bf16x2.f32 %0, %1, %2;" : "=r"(r) : "f"(j < 48 ? y[j < 48 ? 2 * j + 1 : 0] : z[j < 48 ? 0 : 2 * j - 95]), "f"(j < 48 ? y[j < 48 ? 2 * j : 0] : z[j < 48 ? 0 : 2 * j - 96]));
        asm("mul.bf16x2 %0, %1, %1;" : "=r"(hf[j]) : "r"(r));
      }
    }
    MARK(15 + L * 19);
    {
      PTRS
      float ya[32], yb[32];
      uint4* pp = g_P + ((t * 8 + warp) * 8 + c) * 28 * 32 + ln_;
#define F2STORE(j, Y) { regfence(Y); _Pragma("unroll") for (int u = 0; u < 4; u++) \
      stll(pp + (4 * (j) + u) * 32, tg(pack(Y[8 * u] * rr0, Y[8 * u + 1] * rr0), tag), pack(Y[8 * u + 2] * rr1, Y[8 * u + 3] * rr1), \
           pack(Y[8 * u + 4] * rr0, Y[8 * u + 5] * rr0), pack(Y[8 * u + 6] * rr1, Y[8 * u + 7] * rr1)); if ((j) >= 5) hint_post(hme, hs + (4 + (j)), lane); }
#define F2PASS(j, Y, Z) { const uint32_t st = acquire(); wg_fence(); \
      _Pragma("unroll") for (int ks = 0; ks < 14; ks++) wgmma_rs64(Y, hf[4 * ks], hf[4 * ks + 1], hf[4 * ks + 2], hf[4 * ks + 3], mkdesc(st, ks * 2048, 1024, 1024, 1), ks); \
      wg_commit(); if (j > 0) { wg_wait<1>(); release(); F2STORE(j - 1, Z) } }
      const uint4* pr = g_P + ((t * 8 + c) * 8 * 28 + warp) * 32 + ln_;
      uint4 p[8], p2[8]; uint2 xa, xb, xc, xd; uint32_t ba, bb, bc, bd;
      const uint32_t ptag = tag;
      const uint32_t* hred = g_H + (t * 8 + c) * 8 + (ln_ & 7);
      F2PASS(0, ya, yb) F2PASS(1, yb, ya) F2PASS(2, ya, yb) F2PASS(3, yb, ya)
      F2PASS(4, ya, yb)
      RISSUE(0, p, xa, xb, ba, bb)
      F2PASS(5, yb, ya)
      REDU(0, p, xa, xb, ba, bb)
      if (L == 0) { xw[0][0] = tg(xw[0][0], 0); RPUB(0) }
      F2PASS(6, ya, yb)
      RISSUE(1, p, xa, xb, ba, bb)
      wg_wait<0>(); release(); F2STORE(6, ya)
      MARK(16 + L * 19);
      if (wg) hint_wait(hred, hs + 9);
      RISSUE(2, p2, xc, xd, bc, bd)
      REDU(1, p, xa, xb, ba, bb)
      if (L == 0) { xw[1][0] = tg(xw[1][0], 0); RPUB(1) }
      MARK(17 + L * 19);
      REDU(2, p2, xc, xd, bc, bd)
      if (L == 0) { xw[2][0] = tg(xw[2][0], 0); RPUB(2) }
    }
    MARK(18 + L * 19);
  }
  {
    PTRS
    uint32_t* op = (uint32_t*)(out + XOFF(ln_));
#define OUT(u) { op[u * 64] = xw[u][0]; op[u * 64 + 1792] = xw[u][1]; op[u * 64 + 4] = xw[u][2]; op[u * 64 + 1796] = xw[u][3]; }
    OUT(0) OUT(1) OUT(2)
    if (wg == 0) { RLAST(0u, 20u) OUT(3) }
    else if (warp == 7) {
      if (t == 0 && lane == 0) g_WQF[c] = 0;
      if (lane < 8) stll(g_S2 + (t * 8 + c) * 8 + lane, 0, 0, 0, 0);
      if (lane < 4) { stll(g_CS + blockIdx.x * 4 + lane, 0, 0, 0, 0); if (blockIdx.x < 68) stll(g_CS + 512 + blockIdx.x * 4 + lane, 0, 0, 0, 0); }
    }
  }
  MARK(38); GT(39);
  }
}

typedef CUresult (*EncFn)(CUtensorMap*, CUtensorMapDataType, cuuint32_t, void*, const cuuint64_t*, const cuuint64_t*, const cuuint32_t*, const cuuint32_t*,
                          CUtensorMapInterleave, CUtensorMapSwizzle, CUtensorMapL2promotion, CUtensorMapFloatOOBfill);

extern "C" void kernel_launch(void* const* d_in, const int* in_sizes, int n_in, void* d_out, int out_size) {
  static EncFn enc = nullptr;
  if (!enc) {
    void* fn = nullptr; cudaDriverEntryPointQueryResult qr;
    cudaGetDriverEntryPoint("cuTensorMapEncodeTiled", &fn, cudaEnableDefault, &qr);
    enc = (EncFn)fn;
    cudaFuncSetAttribute(fused_kernel, cudaFuncAttributeMaxDynamicSharedMemorySize, SMEM_BYTES);
  }
  CUtensorMap mQKV, mWO, mW1, mW1b, mW2, mW2b, mX;
  const cuuint32_t es[3] = {1, 1, 1};
  auto enc2 = [&](CUtensorMap* m, void* p, cuuint64_t cols, cuuint64_t rows, cuuint32_t bc, cuuint32_t br) {
    const cuuint64_t dims[2] = {cols, rows}, str[1] = {cols * 2}; const cuuint32_t box[2] = {bc, br};
    enc(m, CU_TENSOR_MAP_DATA_TYPE_BFLOAT16, 2, p, dims, str, box, es, CU_TENSOR_MAP_INTERLEAVE_NONE,
        bc == 64 ? CU_TENSOR_MAP_SWIZZLE_128B : CU_TENSOR_MAP_SWIZZLE_64B, CU_TENSOR_MAP_L2_PROMOTION_L2_128B, CU_TENSOR_MAP_FLOAT_OOB_FILL_NONE);
  };
  enc2(&mQKV, d_in[1], 1344, 448, 64, 112); enc2(&mWO, d_in[3], 448, 448, 64, 112); enc2(&mW1b, d_in[5], 1792, 448, 32, 32);
  enc2(&mX, d_in[0], 448, 2048, 64, 128);
  enc2(&mW2, d_in[7], 448, 1792, 64, 96); enc2(&mW2b, d_in[7], 448, 1792, 64, 16);
  {
    const cuuint64_t dims[3] = {64, 448, 28}, str[2] = {3584, 128}; const cuuint32_t box[3] = {64, 32, 3};
    enc(&mW1, CU_TENSOR_MAP_DATA_TYPE_BFLOAT16, 3, d_in[5], dims, str, box, es, CU_TENSOR_MAP_INTERLEAVE_NONE, CU_TENSOR_MAP_SWIZZLE_128B,
        CU_TENSOR_MAP_L2_PROMOTION_L2_128B, CU_TENSOR_MAP_FLOAT_OOB_FILL_NONE);
  }
  typedef const __nv_bfloat16* BP;
  fused_kernel<<<128, 384, SMEM_BYTES>>>(mQKV, mWO, mW1, mW1b, mW2, mW2b, mX, (BP)d_in[1], (BP)d_in[2], (BP)d_in[3], (BP)d_in[5], (BP)d_in[6], (BP)d_in[7], (BP)d_in[8],
                                         (__nv_bfloat16*)d_out);
}
```

```cpp
#include <cuda_runtime.h>
#include <cuda_bf16.h>
#include <cuda.h>
#include <stdint.h>

constexpr int NST = 6, STAGE = 28672;
constexpr int OFF_PHIK = NST * STAGE;
constexpr int OFF_V = OFF_PHIK + 32768;
constexpr int OFF_WPHI = OFF_V + 16384;
constexpr int OFF_CB = OFF_WPHI + 7168;
constexpr int OFF_BAR = OFF_CB + 3584;
constexpr int SMEM_BYTES = OFF_BAR + 16 * NST + 8;
constexpr int FR = 16 * 8 * 28 * 32;
constexpr int SPIN = 1 << 18;
#define MC 0
#define MAPPING MC
#define MCS
#define MCA(n)
#define CLUSTER
#define PACE 2

__device__ uint4 g_F[3 * FR];
constexpr int XR = 0, OO = FR, X1 = 2 * FR;
__device__ uint4 g_P[8 * FR];
__device__ uint4 g_ST[16 * 8 * 8 * 8];
__device__ uint4 g_KVP[8 * 16 * 1024];
__device__ uint2 g_KVR[8 * 1024];
__device__ uint4 g_CS[784];
__device__ uint4 g_S2[16 * 8 * 8];
__device__ uint4 g_WQ[8 * 6 * (STAGE / 16)];
__device__ uint32_t g_WQF[8];
__device__ uint32_t g_H[16 * 8 * 8];
#define MARK(i)
#define GT(i)

__device__ __forceinline__ uint32_t s2u(const void* p) { return (uint32_t)__cvta_generic_to_shared(p); }
__device__ __forceinline__ void mbar_init(uint32_t b, uint32_t c) { asm volatile("mbarrier.init.shared::cta.b64 [%0], %1;" ::"r"(b), "r"(c)); }
__device__ __forceinline__ void mbar_expect(uint32_t b, uint32_t tx) { asm volatile("mbarrier.arrive.expect_tx.shared::cta.b64 _, [%0], %1;" ::"r"(b), "r"(tx) : "memory"); }
__device__ __forceinline__ void mbar_arrive_cl(uint32_t b, uint32_t rank) {
  asm volatile("{.reg .b32 r; mapa.shared::cluster.u32 r, %0, %1; mbarrier.arrive.shared::cluster.b64 _, [r];}" ::"r"(b), "r"(rank) : "memory");
}
__device__ __forceinline__ void mbar_wait(uint32_t b, uint32_t ph) {
  uint32_t ok = 0;
#pragma unroll 1
  for (int it = 0; it < SPIN && !ok; it++)
    asm volatile("{.reg .pred p; mbarrier.try_wait.parity.shared::cta.b64 p,[%1],%2; selp.u32 %0,1,0,p;}" : "=r"(ok) : "r"(b), "r"(ph) : "memory");
}
__device__ __forceinline__ void tma2d(uint32_t dst, const CUtensorMap* m, int c0, int c1, uint32_t bar) {
  asm volatile("cp.async.bulk.tensor.2d.shared::cluster.global.mbarrier::complete_tx::bytes" MCS " [%0], [%1, {%3, %4}], [%2]" MCA(5) ";"
               ::"r"(dst), "l"(m), "r"(bar), "r"(c0), "r"(c1), "h"((uint16_t)3) : "memory");
}
__device__ __forceinline__ void tma3d(uint32_t dst, const CUtensorMap* m, int c0, int c1, int c2, uint32_t bar) {
  asm volatile("cp.async.bulk.tensor.3d.shared::cluster.global.mbarrier::complete_tx::bytes" MCS " [%0], [%1, {%3, %4, %5}], [%2]" MCA(6) ";"
               ::"r"(dst), "l"(m), "r"(bar), "r"(c0), "r"(c1), "r"(c2), "h"((uint16_t)3) : "memory");
}
__device__ __forceinline__ void l2pf(const void* p, uint32_t bytes) { asm volatile("cp.async.bulk.prefetch.L2.global [%0], %1;" ::"l"(p), "r"(bytes) : "memory"); }
__device__ __forceinline__ void wg_fence() { asm volatile("wgmma.fence.sync.aligned;" ::: "memory"); }
__device__ __forceinline__ void wg_commit() { asm volatile("wgmma.commit_group.sync.aligned;" ::: "memory"); }
template <int N> __device__ __forceinline__ void wg_wait() { asm volatile("wgmma.wait_group.sync.aligned %0;" ::"n"(N) : "memory"); }
template <int N> __device__ __forceinline__ void regfence(float (&d)[N]) {
#pragma unroll
  for (int i = 0; i < N; i++) asm volatile("" : "+f"(d[i])::"memory");
}
__device__ __forceinline__ void bar_cons() { asm volatile("bar.sync 1, 256;" ::: "memory"); }
__device__ __forceinline__ void fence_async() { asm volatile("fence.proxy.async.shared::cta;" ::: "memory"); }
struct Desc { uint32_t lo, hi; };
__device__ __forceinline__ Desc mkdesc(uint32_t base16, uint32_t off, uint32_t lbo, uint32_t sbo, uint32_t swz) {
  return Desc{base16 + ((off >> 4) | ((lbo >> 4) << 16)), (sbo >> 4) | (swz << 30)};
}
__device__ __forceinline__ uint4 ldll(const uint4* p) {
  uint4 v; asm volatile("ld.relaxed.gpu.global.v4.u32 {%0,%1,%2,%3}, [%4];" : "=r"(v.x), "=r"(v.y), "=r"(v.z), "=r"(v.w) : "l"(p) : "memory"); return v;
}
#define WEAK 1
__device__ __forceinline__ uint4 ldwk(const uint4* p) {
  uint4 v; asm volatile("ld.global.L1::no_allocate.v4.u32 {%0,%1,%2,%3}, [%4];" : "=r"(v.x), "=r"(v.y), "=r"(v.z), "=r"(v.w) : "l"(p) : "memory"); return v;
}
__device__ __forceinline__ uint2 ldll2(const uint2* p) {
  uint2 v; asm volatile("ld.relaxed.gpu.global.v2.u32 {%0,%1}, [%2];" : "=r"(v.x), "=r"(v.y) : "l"(p) : "memory"); return v;
}
__device__ __forceinline__ void stll(uint4* p, uint32_t x, uint32_t y, uint32_t z, uint32_t w) {
  asm volatile("st.relaxed.gpu.global.v4.u32 [%0], {%1,%2,%3,%4};" ::"l"(p), "r"(x), "r"(y), "r"(z), "r"(w) : "memory");
}
__device__ __forceinline__ void stll2(void* p, uint32_t x, uint32_t y) {
  asm volatile("st.relaxed.gpu.global.v2.u32 [%0], {%1,%2};" ::"l"(p), "r"(x), "r"(y) : "memory");
}
__device__ __forceinline__ int laneid() { int l; asm volatile("mov.u32 %0, %%laneid;" : "=r"(l)); return l; }
__device__ __forceinline__ uint32_t tg(uint32_t w, uint32_t tag) { return (w & ~1u) | tag; }
__device__ __forceinline__ uint32_t pack(float lo, float hi) {
  uint32_t r; asm("cvt.rn.bf16x2.f32 %0, %1, %2;" : "=r"(r) : "f"(hi), "f"(lo)); return r;
}
__device__ __forceinline__ float blo(uint32_t w) { return __uint_as_float(w << 16); }
__device__ __forceinline__ float bhi(uint32_t w) { return __uint_as_float(w & 0xffff0000u); }
__device__ __forceinline__ float ex2(float x) { float r; asm("ex2.approx.ftz.f32 %0, %1;" : "=f"(r) : "f"(x)); return r; }
__device__ __forceinline__ float rcp(float x) { float r; asm("rcp.approx.ftz.f32 %0, %1;" : "=f"(r) : "f"(x)); return r; }
__device__ __forceinline__ float qsum(float v) { v += __shfl_xor_sync(~0u, v, 1); v += __shfl_xor_sync(~0u, v, 2); return v; }
__device__ __forceinline__ void sts32(uint32_t a, uint32_t v) { asm volatile("st.shared.u32 [%0], %1;" ::"r"(a), "r"(v) : "memory"); }
__device__ __forceinline__ void sts16(uint32_t a, uint32_t v) { asm volatile("st.shared.u16 [%0], %1;" ::"r"(a), "h"((uint16_t)v) : "memory"); }
__device__ __forceinline__ void sts128(uint32_t a, uint32_t x, uint32_t y, uint32_t z, uint32_t w) {
  asm volatile("st.shared.v4.u32 [%0], {%1,%2,%3,%4};" ::"r"(a), "r"(x), "r"(y), "r"(z), "r"(w) : "memory");
}
__device__ __forceinline__ uint32_t sw128(int row, int col) { return row * 128 + ((((col >> 3) ^ row) & 7) << 4) + (col & 7) * 2; }

__device__ __forceinline__ void wgmma_rs56(float (&d)[28], const uint32_t a0, const uint32_t a1, const uint32_t a2, const uint32_t a3, Desc db, int sd) {
  asm volatile("{.reg .pred p; .reg .b64 da, db; setp.ne.b32 p, %33, 0; mov.b64 db, {%32, %34};\n wgmma.mma_async.sync.aligned.m64n56k16.f32.bf16.bf16 {%0,%1,%2,%3,%4,%5,%6,%7,%8,%9,%10,%11,%12,%13,%14,%15,%16,%17,%18,%19,%20,%21,%22,%23,%24,%25,%26,%27}, {%28,%29,%30,%31}, db, p, 1, 1, 1;}"
   : "+f"(d[0]),"+f"(d[1]),"+f"(d[2]),"+f"(d[3]),"+f"(d[4]),"+f"(d[5]),"+f"(d[6]),"+f"(d[7]),"+f"(d[8]),"+f"(d[9]),"+f"(d[10]),"+f"(d[11]),"+f"(d[12]),"+f"(d[13]),"+f"(d[14]),"+f"(d[15]),"+f"(d[16]),"+f"(d[17]),"+f"(d[18]),"+f"(d[19]),"+f"(d[20]),"+f"(d[21]),"+f"(d[22]),"+f"(d[23]),"+f"(d[24]),"+f"(d[25]),"+f"(d[26]),"+f"(d[27])
   : "r"(a0),"r"(a1),"r"(a2),"r"(a3),"r"(db.lo),"r"(sd),"r"(db.hi));
}
__device__ __forceinline__ void wgmma_rs64(float (&d)[32], const uint32_t a0, const uint32_t a1, const uint32_t a2, const uint32_t a3, Desc db, int sd) {
  asm volatile("{.reg .pred p; .reg .b64 da, db; setp.ne.b32 p, %37, 0; mov.b64 db, {%36, %38};\n wgmma.mma_async.sync.aligned.m64n64k16.f32.bf16.bf16 {%0,%1,%2,%3,%4,%5,%6,%7,%8,%9,%10,%11,%12,%13,%14,%15,%16,%17,%18,%19,%20,%21,%22,%23,%24,%25,%26,%27,%28,%29,%30,%31}, {%32,%33,%34,%35}, db, p, 1, 1, 1;}"
   : "+f"(d[0]),"+f"(d[1]),"+f"(d[2]),"+f"(d[3]),"+f"(d[4]),"+f"(d[5]),"+f"(d[6]),"+f"(d[7]),"+f"(d[8]),"+f"(d[9]),"+f"(d[10]),"+f"(d[11]),"+f"(d[12]),"+f"(d[13]),"+f"(d[14]),"+f"(d[15]),"+f"(d[16]),"+f"(d[17]),"+f"(d[18]),"+f"(d[19]),"+f"(d[20]),"+f"(d[21]),"+f"(d[22]),"+f"(d[23]),"+f"(d[24]),"+f"(d[25]),"+f"(d[26]),"+f"(d[27]),"+f"(d[28]),"+f"(d[29]),"+f"(d[30]),"+f"(d[31])
   : "r"(a0),"r"(a1),"r"(a2),"r"(a3),"r"(db.lo),"r"(sd),"r"(db.hi));
}
__device__ __forceinline__ void wgmma_rs192(float (&d)[96], const uint32_t a0, const uint32_t a1, const uint32_t a2, const uint32_t a3, Desc db, int sd) {
  asm volatile("{.reg .pred p; .reg .b64 db; setp.ne.b32 p, %101, 0; mov.b64 db, {%100, %102};\n wgmma.mma_async.sync.aligned.m64n192k16.f32.bf16.bf16 {%0,%1,%2,%3,%4,%5,%6,%7,%8,%9,%10,%11,%12,%13,%14,%15,%16,%17,%18,%19,%20,%21,%22,%23,%24,%25,%26,%27,%28,%29,%30,%31,%32,%33,%34,%35,%36,%37,%38,%39,%40,%41,%42,%43,%44,%45,%46,%47,%48,%49,%50,%51,%52,%53,%54,%55,%56,%57,%58,%59,%60,%61,%62,%63,%64,%65,%66,%67,%68,%69,%70,%71,%72,%73,%74,%75,%76,%77,%78,%79,%80,%81,%82,%83,%84,%85,%86,%87,%88,%89,%90,%91,%92,%93,%94,%95}, {%96,%97,%98,%99}, db, p, 1, 1, 1;}"
   : "+f"(d[0]),"+f"(d[1]),"+f"(d[2]),"+f"(d[3]),"+f"(d[4]),"+f"(d[5]),"+f"(d[6]),"+f"(d[7]),"+f"(d[8]),"+f"(d[9]),"+f"(d[10]),"+f"(d[11]),"+f"(d[12]),"+f"(d[13]),"+f"(d[14]),"+f"(d[15]),"+f"(d[16]),"+f"(d[17]),"+f"(d[18]),"+f"(d[19]),"+f"(d[20]),"+f"(d[21]),"+f"(d[22]),"+f"(d[23]),"+f"(d[24]),"+f"(d[25]),"+f"(d[26]),"+f"(d[27]),"+f"(d[28]),"+f"(d[29]),"+f"(d[30]),"+f"(d[31]),"+f"(d[32]),"+f"(d[33]),"+f"(d[34]),"+f"(d[35]),"+f"(d[36]),"+f"(d[37]),"+f"(d[38]),"+f"(d[39]),"+f"(d[40]),"+f"(d[41]),"+f"(d[42]),"+f"(d[43]),"+f"(d[44]),"+f"(d[45]),"+f"(d[46]),"+f"(d[47]),"+f"(d[48]),"+f"(d[49]),"+f"(d[50]),"+f"(d[51]),"+f"(d[52]),"+f"(d[53]),"+f"(d[54]),"+f"(d[55]),"+f"(d[56]),"+f"(d[57]),"+f"(d[58]),"+f"(d[59]),"+f"(d[60]),"+f"(d[61]),"+f"(d[62]),"+f"(d[63]),"+f"(d[64]),"+f"(d[65]),"+f"(d[66]),"+f"(d[67]),"+f"(d[68]),"+f"(d[69]),"+f"(d[70]),"+f"(d[71]),"+f"(d[72]),"+f"(d[73]),"+f"(d[74]),"+f"(d[75]),"+f"(d[76]),"+f"(d[77]),"+f"(d[78]),"+f"(d[79]),"+f"(d[80]),"+f"(d[81]),"+f"(d[82]),"+f"(d[83]),"+f"(d[84]),"+f"(d[85]),"+f"(d[86]),"+f"(d[87]),"+f"(d[88]),"+f"(d[89]),"+f"(d[90]),"+f"(d[91]),"+f"(d[92]),"+f"(d[93]),"+f"(d[94]),"+f"(d[95])
   : "r"(a0),"r"(a1),"r"(a2),"r"(a3),"r"(db.lo),"r"(sd),"r"(db.hi));
}
__device__ __forceinline__ void wgmma_rs32(float (&d)[16], const uint32_t a0, const uint32_t a1, const uint32_t a2, const uint32_t a3, Desc db, int sd) {
  asm volatile("{.reg .pred p; .reg .b64 db; setp.ne.b32 p, %21, 0; mov.b64 db, {%20, %22};\n wgmma.mma_async.sync.aligned.m64n32k16.f32.bf16.bf16 {%0,%1,%2,%3,%4,%5,%6,%7,%8,%9,%10,%11,%12,%13,%14,%15}, {%16,%17,%18,%19}, db, p, 1, 1, 1;}"
   : "+f"(d[0]),"+f"(d[1]),"+f"(d[2]),"+f"(d[3]),"+f"(d[4]),"+f"(d[5]),"+f"(d[6]),"+f"(d[7]),"+f"(d[8]),"+f"(d[9]),"+f"(d[10]),"+f"(d[11]),"+f"(d[12]),"+f"(d[13]),"+f"(d[14]),"+f"(d[15])
   : "r"(a0),"r"(a1),"r"(a2),"r"(a3),"r"(db.lo),"r"(sd),"r"(db.hi));
}
__device__ __forceinline__ void wgmma_ss32(float (&d)[16], Desc da, Desc db, int sd) {
  asm volatile("{.reg .pred p; .reg .b64 da, db; setp.ne.b32 p, %18, 0; mov.b64 da, {%16, %19}; mov.b64 db, {%17, %19};\n wgmma.mma_async.sync.aligned.m64n32k16.f32.bf16.bf16 {%0,%1,%2,%3,%4,%5,%6,%7,%8,%9,%10,%11,%12,%13,%14,%15}, da, db, p, 1, 1, 1, 1;}"
   : "+f"(d[0]),"+f"(d[1]),"+f"(d[2]),"+f"(d[3]),"+f"(d[4]),"+f"(d[5]),"+f"(d[6]),"+f"(d[7]),"+f"(d[8]),"+f"(d[9]),"+f"(d[10]),"+f"(d[11]),"+f"(d[12]),"+f"(d[13]),"+f"(d[14]),"+f"(d[15])
   : "r"(da.lo),"r"(db.lo),"r"(sd),"r"(db.hi));
}

__device__ __forceinline__ uint4 ldsm4(uint32_t a) {
  uint4 v; asm volatile("ldmatrix.sync.aligned.m8n8.x4.shared.b16 {%0,%1,%2,%3}, [%4];" : "=r"(v.x), "=r"(v.y), "=r"(v.z), "=r"(v.w) : "r"(a) : "memory"); return v;
}
__device__ __forceinline__ void mma16816(float (&d)[4], const uint4& a, uint32_t b0, uint32_t b1) {
  asm("mma.sync.aligned.m16n8k16.row.col.f32.bf16.bf16.f32 {%0,%1,%2,%3}, {%4,%5,%6,%7}, {%8,%9}, {%0,%1,%2,%3};"
      : "+f"(d[0]), "+f"(d[1]), "+f"(d[2]), "+f"(d[3]) : "r"(a.x), "r"(a.y), "r"(a.z), "r"(a.w), "r"(b0), "r"(b1));
}
__device__ __forceinline__ uint32_t bsub(uint32_t a, uint32_t b) { uint32_t r; asm("sub.bf16x2 %0, %1, %2;" : "=r"(r) : "r"(a), "r"(b)); return r; }
__device__ __forceinline__ uint32_t hint_ld(const uint32_t* p) { uint32_t v; asm volatile("ld.relaxed.gpu.global.u32 %0, [%1];" : "=r"(v) : "l"(p) : "memory"); return v; }
template <int S, int N, bool SPL = false, bool WK = WEAK, int T> __device__ __forceinline__ void ll_issue(uint4 (&v)[T], const uint4* p, int stride, const uint2* p2 = nullptr) {
#pragma unroll
  for (int i = S; i < S + N; i++) {
    if (SPL && i % 7 == 3) { const uint2 lo = ldll2(p2 + i * 64), hi = ldll2(p2 + i * 64 + 32); v[i] = make_uint4(lo.x, lo.y, hi.x, hi.y); }
    else v[i] = WK ? ldwk(p + i * stride) : ldll(p + i * stride);
  }
}
template <int S, int N, bool SPL, int T> __device__ __forceinline__ void ll_check(uint4 (&v)[T], const uint4* p, int stride, uint32_t tag, const uint2* p2 = nullptr) {
#pragma unroll 1
  for (int it = 0; it < SPIN; it++) {
    uint32_t bad = 0;
#pragma unroll
    for (int i = S; i < S + N; i++) bad |= (v[i].x ^ tag) | ((SPL && i % 7 == 3) ? (v[i].z ^ tag) : 0u);
    if (!__any_sync(~0u, bad & 1)) break;
    ll_issue<S, N, SPL, false>(v, p, stride, p2);
  }
}
__device__ __forceinline__ void hint_post(uint32_t* p, uint32_t v, int lane) {
  if (lane == 0) asm volatile("st.relaxed.gpu.global.u32 [%0], %1;" ::"l"(p), "r"(v) : "memory");
}
__device__ __forceinline__ void hint_wait(const uint32_t* p, uint32_t s, uint32_t v = 0xffffu) {
#pragma unroll 1
  for (int it = 0; it < SPIN; it++) {
    if (__all_sync(~0u, v - s < 10u)) break;
    v = hint_ld(p);
  }
}
__device__ __forceinline__ void slice_store(uint4* pf, uint2* ph, const uint32_t (&w)[14], bool odd) {
#pragma unroll
  for (int u = 0; u < 3; u++)
    stll(pf + u * 32, odd ? w[4 * u + 2] : w[4 * u], odd ? w[4 * u + 3] : w[4 * u + 1], odd ? w[4 * u + 4] : w[4 * u + 2], odd ? w[4 * u + 5] : w[4 * u + 3]);
  stll2(ph, odd ? w[0] : w[12], odd ? w[1] : w[13]);
}
template <class F, class M> __device__ __forceinline__ void hedgehog(const float (&d)[28], F sink, M mid) {
  const float L2E = 1.4426950408889634f;
#define HX(G, p) ((p) < 6 ? d[((G) & 1) * 16 + ((p) >> 1) * 4 + ((p) & 1) + ((G) & 2)] : d[12 + (G)])
  float mx[4], mn[4], sp[4], sn[4], ep[4][7], en[4][7];
#pragma unroll
  for (int G = 0; G < 4; G++) {
    mx[G] = mn[G] = HX(G, 0);
#pragma unroll
    for (int p = 1; p < 7; p++) { mx[G] = fmaxf(mx[G], HX(G, p)); mn[G] = fminf(mn[G], HX(G, p)); }
  }
#pragma unroll
  for (int o = 1; o < 4; o <<= 1)
#pragma unroll
    for (int G = 0; G < 4; G++) { mx[G] = fmaxf(mx[G], __shfl_xor_sync(~0u, mx[G], o)); mn[G] = fminf(mn[G], __shfl_xor_sync(~0u, mn[G], o)); }
#pragma unroll
  for (int G = 0; G < 4; G++) {
    const float a = -mx[G] * L2E, b = mn[G] * L2E;
#pragma unroll
    for (int p = 0; p < 7; p++) { ep[G][p] = ex2(fmaf(HX(G, p), L2E, a)); en[G][p] = ex2(fmaf(HX(G, p), -L2E, b)); }
    sp[G] = ((ep[G][0] + ep[G][1]) + (ep[G][2] + ep[G][3])) + ((ep[G][4] + ep[G][5]) + ep[G][6]);
    sn[G] = ((en[G][0] + en[G][1]) + (en[G][2] + en[G][3])) + ((en[G][4] + en[G][5]) + en[G][6]);
    if (G == 1) mid();
  }
#pragma unroll
  for (int o = 1; o < 4; o <<= 1)
#pragma unroll
    for (int G = 0; G < 4; G++) { sp[G] += __shfl_xor_sync(~0u, sp[G], o); sn[G] += __shfl_xor_sync(~0u, sn[G], o); }
#pragma unroll
  for (int G = 0; G < 4; G++) {
    const float a = rcp(sp[G]), b = rcp(sn[G]);
#pragma unroll
    for (int p = 0; p < 7; p++) sink(G >> 1, G & 1, p, pack(ep[G][p] * a, en[G][p] * b));
  }
}
__device__ __forceinline__ void phi_gemm(const float (&x)[28], float (&y)[28], uint32_t wphi, float r0, float r1) {
  uint32_t f[14];
#pragma unroll
  for (int j = 0; j < 14; j++) f[j] = pack(x[2 * j] * (j & 1 ? r1 : r0), x[2 * j + 1] * (j & 1 ? r1 : r0));
  wg_fence();
#pragma unroll
  for (int ks = 0; ks < 3; ks++) wgmma_rs56(y, f[4 * ks], f[4 * ks + 1], f[4 * ks + 2], f[4 * ks + 3], mkdesc(wphi, ks * 2048, 1024, 1024, 1), ks);
  wgmma_rs56(y, f[12], f[13], 0u, 0u, mkdesc(wphi, 3 * 2048, 1024, 1024, 1), 1);
  wg_commit();
}
__device__ __forceinline__ void ln_stats(uint32_t (&xw)[4][4], float* sLN, int warp, int lane, uint4* dst) {
  const int g = lane >> 2; const bool full = warp < 4;
  float s0 = 0.f, s1 = 0.f;
#pragma unroll
  for (int u = 0; u < 4; u++) {
    s0 += (blo(xw[u][0]) + bhi(xw[u][0])) + (blo(xw[u][2]) + bhi(xw[u][2]));
    s1 += (blo(xw[u][1]) + bhi(xw[u][1])) + (blo(xw[u][3]) + bhi(xw[u][3]));
  }
  const float rc = full ? 1.f / 64 : 1.f / 48;
  s0 = qsum(s0); s1 = qsum(s1);
  const float a0 = s0 * rc, a1 = s1 * rc;
  float v0 = 0.f, v1 = 0.f;
#pragma unroll
  for (int u = 0; u < 4; u++)
    if (u < 3 || full) {
#pragma unroll
      for (int k = 0; k < 4; k += 2) {
        float a = blo(xw[u][k]) - a0, b = bhi(xw[u][k]) - a0, c2 = blo(xw[u][k + 1]) - a1, d2 = bhi(xw[u][k + 1]) - a1;
        v0 += a * a + b * b; v1 += c2 * c2 + d2 * d2;
      }
    }
  v0 = qsum(v0); v1 = qsum(v1);
  if ((lane & 3) == 0) *(float4*)(sLN + (g * 8 + warp) * 4) = make_float4(s0, v0, s1, v1);
  if (warp) { asm volatile("bar.arrive 7, 256;" ::: "memory"); return; }
  asm volatile("bar.sync 7, 256;" ::: "memory");
  const float4 ea = *(const float4*)(sLN + (g * 8 + (lane & 3)) * 4), eb = *(const float4*)(sLN + (g * 8 + 4 + (lane & 3)) * 4);
  const float m0 = qsum(ea.x + eb.x) * (1.f / 448), m1 = qsum(ea.z + eb.z) * (1.f / 448);
  const float d0 = ea.x * (1.f / 64) - m0, d1 = eb.x * (1.f / 48) - m0, d2 = ea.z * (1.f / 64) - m1, d3 = eb.z * (1.f / 48) - m1;
  v0 = qsum(ea.y + eb.y + 64.f * d0 * d0 + 48.f * d1 * d1); v1 = qsum(ea.w + eb.w + 64.f * d2 * d2 + 48.f * d3 * d3);
  if ((lane & 3) == 0) stll(dst + g, tg(__float_as_uint(m0), 1), __float_as_uint(rsqrtf(v0 * (1.f / 448) + 1e-5f)), __float_as_uint(m1), __float_as_uint(rsqrtf(v1 * (1.f / 448) + 1e-5f)));
}

__global__ void CLUSTER __launch_bounds__(384, 1)
fused_kernel(const __grid_constant__ CUtensorMap mQKV, const __grid_constant__ CUtensorMap mWO, const __grid_constant__ CUtensorMap mW1,
             const __grid_constant__ CUtensorMap mW1b, const __grid_constant__ CUtensorMap mW2, const __grid_constant__ CUtensorMap mW2b,
             const __grid_constant__ CUtensorMap mX, const __nv_bfloat16* __restrict__ wqkv, const __nv_bfloat16* __restrict__ wphi,
             const __nv_bfloat16* __restrict__ wo, const __nv_bfloat16* __restrict__ w1, const __nv_bfloat16* __restrict__ b1,
             const __nv_bfloat16* __restrict__ w2, const __nv_bfloat16* __restrict__ b2, __nv_bfloat16* __restrict__ out) {
  extern __shared__ __align__(1024) uint8_t sm[];
  const uint32_t sb = s2u(sm);
  const int tid = threadIdx.x, warp = __shfl_sync(~0u, tid >> 5, 0), lane = tid & 31,
            t = MAPPING ? (blockIdx.x >> 4) * 2 + (blockIdx.x & 1) : blockIdx.x >> 3, c = MAPPING ? (blockIdx.x >> 1) & 7 : blockIdx.x & 7;
  const uint32_t bfull = sb + OFF_BAR, bempty = bfull + 8 * NST;

#define XOFF(l) ((t * 128 + c * 16 + ((l) >> 2)) * 448 + warp * 16 + 2 * ((l) & 3))
  if (warp < 8) { MARK(0); GT(19); }
  if (tid == 256) {
    for (int s = 0; s < NST; s++) { mbar_init(bfull + 8 * s, 1); mbar_init(bempty + 8 * s, MC ? 16 : 8); }
    mbar_init(bempty + 8 * NST, 1);
    asm volatile("fence.mbarrier_init.release.cluster;" ::: "memory");
    fence_async();
    mbar_expect(bempty + 8 * NST, 114688);
    for (int i = 0; i < 7; i++)
      asm volatile("cp.async.bulk.tensor.2d.shared::cluster.global.mbarrier::complete_tx::bytes [%0], [%1, {%3, %4}], [%2];"
                   ::"r"(sb + 2 * STAGE + i * 16384), "l"(&mX), "r"(bempty + 8 * NST), "r"(64 * i), "r"(128 * t) : "memory");
  }
  asm volatile("barrier.cluster.arrive.release.aligned; barrier.cluster.wait.acquire.aligned;" ::: "memory");
  if (warp >= 8) {
    asm volatile("setmaxnreg.dec.sync.aligned.u32 24;");
    auto issue = [&](int i, int s) {
      const uint32_t dst = sb + s * STAGE, bar = bfull + 8 * s;
      mbar_expect(bar, STAGE);
#pragma unroll 1
      for (int rk = MC ? (blockIdx.x & 1) : 0; rk < (MC ? (blockIdx.x & 1) + 1 : 2); rk++)
      if (i < 4) tma2d(dst + rk * 14336, &mQKV, 448 + 448 * rk + 56 * c, 112 * i, bar);
      else if (i < 8) tma2d(dst + rk * 14336, i < 6 ? &mQKV : &mWO, (i < 6 ? 56 : 64) * c, 224 * (i & 1) + 112 * rk, bar);
      else if (i < 15) { const int k0 = 64 * ((i - 8 + c) % 7) + 32 * rk;
        tma3d(dst + rk * 12288, &mW1, 0, k0, 3 * c, bar); tma2d(dst + 24576 + rk * 2048, &mW1b, 1536 + 32 * c, k0, bar); }
      else { tma2d(dst + rk * 12288, &mW2, 64 * (i - 15), 192 * c + 96 * rk, bar); tma2d(dst + 24576 + rk * 2048, &mW2b, 64 * (i - 15), 1536 + 32 * c + 16 * rk, bar); }
    };
    auto colsum = [&](int job) {
        const int ld4 = job < 112 ? 448 : 336;
        const uint2* wp = (job < 112 ? (const uint2*)w1 + job * 4 : (const uint2*)wqkv + (job - 112) * 4) + (lane >> 2) * ld4 + (lane & 3);
        float s0 = 0.f, s1 = 0.f, s2 = 0.f, s3 = 0.f;
#pragma unroll 8
        for (int i = 0; i < 56; i++) { const uint2 v = __ldg(wp + i * 8 * ld4); s0 += blo(v.x); s1 += bhi(v.x); s2 += blo(v.y); s3 += bhi(v.y); }
#pragma unroll 1
        for (int o = 4; o < 32; o <<= 1) { s0 += __shfl_xor_sync(~0u, s0, o); s1 += __shfl_xor_sync(~0u, s1, o); s2 += __shfl_xor_sync(~0u, s2, o); s3 += __shfl_xor_sync(~0u, s3, o); }
        if (lane < 4) stll(g_CS + job * 4 + lane, tg(__float_as_uint(s0), 1), __float_as_uint(s1), __float_as_uint(s2), __float_as_uint(s3));
      };
    if (warp == 8) {
      int s = 0; uint32_t ph = 1;
      for (int n = 0; n < 44; n++) {
        if (n == PACE) asm volatile("bar.sync 2, 288;" ::: "memory");
        mbar_wait(bempty + 8 * s, ph);
        if (n == 22) {
          uint32_t v = 0;
#pragma unroll 1
          for (int it = 0; it < SPIN && v < 32; it++) asm volatile("ld.acquire.gpu.global.u32 %0, [%1];" : "=r"(v) : "l"(g_WQF + c) : "memory");
          asm volatile("fence.proxy.async.global;" ::: "memory");
        }
        if (lane == 0) {
          if (n >= 22 && n < 28) {
            mbar_expect(bfull + 8 * s, STAGE);
            asm volatile("cp.async.bulk.shared::cluster.global.mbarrier::complete_tx::bytes [%0], [%1], %2, [%3];"
                         ::"r"(sb + s * STAGE), "l"(g_WQ + c * 10752 + (n - 22) * (STAGE / 16)), "r"(STAGE), "r"(bfull + 8 * s) : "memory");
          } else issue(n >= 22 ? n - 22 : n, s);
        }
        __syncwarp();
        if (++s == NST) { s = 0; ph ^= 1; }
      }
    } else if (warp == 9) {
      if (lane == 0) l2pf((const uint8_t*)wqkv + blockIdx.x * 9408, 9408);
      mbar_wait(bfull + 8 * 3, 0);
      if (lane == 0) {
        l2pf((const uint8_t*)wo + blockIdx.x * 3136, 3136);
        l2pf((const uint8_t*)w1 + blockIdx.x * 12544, 12544);
        l2pf((const uint8_t*)w2 + blockIdx.x * 12544, 12544);
      }
      if (blockIdx.x < 112) colsum(blockIdx.x);
      asm volatile("bar.sync 6, 96;" ::: "memory");
#pragma unroll 1
      for (int i = 0; i < 4; i++) {
        const int e = lane < 28 ? lane + 28 * (i & 1) : 0;
        const bool ok = i < 2 || (e < 48 && (e & 15) < 14);
        const int e4 = i < 2 ? (e < 48 ? 48 * c + e : 336 + 8 * c + e) : ok ? 448 + 112 * (e >> 4) + 14 * c + (e & 15) : 448;
        uint4 cv[1];
        ll_issue<0, 1>(cv, g_CS + e4, 0); ll_check<0, 1, false>(cv, g_CS + e4, 0, 1u);
        const uint2 bb = __ldg((const uint2*)b1 + (i < 2 ? e4 : 0));
        const uint32_t h0 = pack(__uint_as_float(cv[0].x), __uint_as_float(cv[0].y)), h1 = pack(__uint_as_float(cv[0].z), __uint_as_float(cv[0].w));
        const uint32_t l0 = pack(__uint_as_float(cv[0].x) - blo(h0), __uint_as_float(cv[0].y) - bhi(h0)), l1 = pack(__uint_as_float(cv[0].z) - blo(h1), __uint_as_float(cv[0].w) - bhi(h1));
#pragma unroll 1
        for (int j = 0; j < (i < 2 ? 5 : 3); j++) {
          const int r = i < 2 ? j : j + 5;
          const uint32_t ad = sb + OFF_CB + (e >> 3) * 512 + r * 64 + ((((e >> 1) ^ (r >> 1)) & 3) << 4) + (e & 1) * 8;
          sts32(ad, j < 2 ? h0 : j == 2 ? l0 : bb.x); sts32(ad + 4, j < 2 ? h1 : j == 2 ? l1 : bb.y);
        }
        if (i & 1) { fence_async(); if (i == 1) asm volatile("bar.arrive 4, 288;" ::: "memory"); else asm volatile("bar.arrive 8, 288;" ::: "memory"); }
      }
    } else if (warp >= 10) {
      const int h = warp - 10;
      uint32_t wv[13];
#pragma unroll
      for (int i = 0; i < 13; i++) { const int e = lane + 32 * i; wv[i] = e < 392 ? __ldg((const uint32_t*)wphi + (2 * c + h) * 392 + e) : 0u; }
#pragma unroll 1
      for (int e = h * 32 + lane; e < 672; e += 64) sts128(sb + OFF_WPHI + e * 16, 0, 0, 0, 0);
      asm volatile("bar.arrive 6, 96;" ::: "memory");
#pragma unroll 1
      for (int i = 0; i < 4; i++) sts128(sb + OFF_PHIK + sw128(h * 128 + i * 32 + lane, 56), 0, 0, 0, 0);
      asm volatile("bar.sync 5, 64;" ::: "memory");
#pragma unroll
      for (int i = 0; i < 13; i++) {
        const int e = lane + 32 * i, d = e / 14, f2 = 2 * (e - 14 * d), k = 28 * h + d;
        if (e < 392) {
          if (f2 < 24) sts32(sb + OFF_WPHI + sw128(k, 32 * h + f2), wv[i]);
          else { sts16(sb + OFF_WPHI + sw128(k, 2 * f2 - 24 + h), wv[i]); sts16(sb + OFF_WPHI + sw128(k, 2 * f2 - 22 + h), wv[i] >> 16); }
        }
      }
      fence_async();
      asm volatile("bar.arrive 3, 320;" ::: "memory");
      mbar_wait(bfull + 8 * 5, 0);
#pragma unroll 2
      for (int e = t * 672 + h * 32 + lane; e < t * 672 + 672; e += 64) {
        const int r = e >> 3, st = r / 224, rr = r - st * 224, ch = (e & 7) ^ (rr & 7);
        const int k = st < 4 ? 112 * st + (rr >= 112 ? rr - 112 : rr) : 224 * (st - 4) + rr, col = (st < 4 ? (rr >= 112 ? 896 : 448) : 0) + 56 * c + 8 * ch;
        g_WQ[c * 10752 + e] = ch < 7 ? __ldg((const uint4*)(wqkv + k * 1344 + col)) : make_uint4(0, 0, 0, 0);
      }
      __syncwarp();
      if (lane == 0) asm volatile("red.release.gpu.global.add.u32 [%0], 1;" ::"l"(g_WQF + c) : "memory");
      if (h == 0 && blockIdx.x < 84) colsum(112 + blockIdx.x);
    }
  } else {
  asm volatile("setmaxnreg.inc.sync.aligned.u32 240;");

  const int wg = warp >> 2, g = lane >> 2, q = lane & 3;
  const int row0 = warp * 16 + g;
#define PTRS const int ln_ = laneid(); \
  uint4* const fm = g_F + ((t * 8 + warp) * 28) * 32 + ln_;            \
  uint4* const fr = g_F + ((t * 8 + c) * 28 + warp) * 32 + ln_;        \
  uint4* const sf = fm + (7 * (c >> 1) + 4 * (c & 1)) * 32;             \
  uint2* const f2 = (uint2*)(fm - ln_) + ln_;                           \
  uint2* const sh = f2 + (7 * (c >> 1) + 3) * 64 + 32 * (c & 1);        \
  uint32_t* const hme = g_H + (t * 8 + warp) * 8 + c; \
  const uint32_t* const hrow = g_H + (t * 8 + warp) * 8 + (ln_ & 7); \
  (void)fm; (void)fr; (void)sf; (void)f2; (void)sh; (void)hme; (void)hrow;
  float* sLN = (float*)(sm + OFF_V);
  const uint32_t sPK = sb + OFF_PHIK, sV = sb + OFF_V, d16 = (sb & 0x3FFFF) >> 4;
    uint32_t xw[4][4];
#pragma unroll
  for (int i = 0; i < 16; i++) xw[i >> 2][i & 3] = 0;
  int cs = 0, rs = 0; uint32_t cph = 0;
  auto acquire = [&]() -> uint32_t { mbar_wait(bfull + 8 * cs, cph); const uint32_t a = d16 + cs * (STAGE >> 4); if (++cs == NST) { cs = 0; cph ^= 1; } return a; };
  int nrel = 44 - NST;
  auto release = [&]() { if (lane < 1 + MC && nrel > 0) mbar_arrive_cl(bempty + 8 * rs, lane); nrel--; if (++rs == NST) rs = 0; };

#define RISSUE(m, P, XA, XB, BA, BB) { ll_issue<0, 8>(P, pr + (m) * 256, 896); \
      { const uint4 v_ = ldll(fr + X1 + (m) * 256); XA = make_uint2(v_.x, v_.y); XB = make_uint2(v_.z, v_.w); } \
      const uint32_t* bp = (const uint32_t*)(b2 + 128 * (m) + 16 * warp) + (ln_ & 3); BA = __ldg(bp); BB = __ldg(bp + 4); }
#define REDU(m, P, XA, XB, BA, BB) { ll_check<0, 8, false>(P, pr + (m) * 256, 896, ptag); \
      float e[8] = {blo(XA.x) + blo(BA), bhi(XA.x) + bhi(BA), blo(XA.y) + blo(BA), bhi(XA.y) + bhi(BA), blo(XB.x) + blo(BB), bhi(XB.x) + bhi(BB), blo(XB.y) + blo(BB), bhi(XB.y) + bhi(BB)}; \
      _Pragma("unroll") for (int i = 0; i < 8; i++) { e[0] += blo(P[i].x); e[1] += bhi(P[i].x); e[2] += blo(P[i].y); e[3] += bhi(P[i].y); \
        e[4] += blo(P[i].z); e[5] += bhi(P[i].z); e[6] += blo(P[i].w); e[7] += bhi(P[i].w); } \
      xw[m][0] = pack(e[0], e[1]); xw[m][1] = pack(e[2], e[3]); xw[m][2] = pack(e[4], e[5]); xw[m][3] = pack(e[6], e[7]); }
#define RPUB(m) stll(fr + XR + (m) * 256, tg(xw[m][0], 0), xw[m][1], xw[m][2], xw[m][3]);
#define RLAST(ptag_, hv) { const uint32_t ptag = ptag_; const uint4* pr = g_P + ((t * 8 + c) * 8 * 28 + warp) * 32 + ln_; uint4 p[8]; uint2 xa, xb; uint32_t ba, bb; \
      hint_wait(g_H + (t * 8 + c) * 8 + (ln_ & 7), hv); RISSUE(3, p, xa, xb, ba, bb) REDU(3, p, xa, xb, ba, bb) }
#pragma unroll 1
  for (int L = 0; L < 2; L++) {
    const uint32_t tag = 1 - L;
    uint32_t phq[2][2][7];
    const uint32_t hs = 10 * L;
    {
      PTRS
      uint4 a[28];
      const uint4* pa = fm + XR;
      uint32_t fa = 0, fb = 0;
      float r0 = 1.f, r1 = 1.f;
      if (L == 0) {
        mbar_wait(bempty + 8 * NST, 0);
        MARK(1);
        const int row = warp * 16 + (ln_ & 15);
        const uint32_t xb = sb + 2 * STAGE + row * 128;
        float cs_[4][4] = {}, c0[2][4] = {}, c1[2][4] = {};
#pragma unroll
        for (int ks = 0; ks < 28; ks++) { a[ks] = ldsm4(xb + (ks >> 2) * 16384 + (((2 * (ks & 3) + (ln_ >> 4)) ^ (row & 7)) << 4)); mma16816(cs_[ks & 3], a[ks], 0x3F803F80u, 0x3F803F80u); }
        if (c < 7) {
#pragma unroll
          for (int u = 0; u < 4; u++) { const uint4 v = ldsm4(xb + c * 16384 + (((2 * u + (ln_ >> 4)) ^ (row & 7)) << 4)); stll(fm + XR + 128 * c + u * 32, tg(v.x, tag), v.y, v.z, v.w); }
        }
        const float m0 = ((cs_[0][0] + cs_[1][0]) + (cs_[2][0] + cs_[3][0])) * (1.f / 448), m1 = ((cs_[0][2] + cs_[1][2]) + (cs_[2][2] + cs_[3][2])) * (1.f / 448);
        const uint32_t mb0 = pack(m0, m0), mb1 = pack(m1, m1);
        asm volatile("bar.arrive 2, 288;" ::"r"(mb0) : "memory");
#pragma unroll
        for (int ks = 0; ks < 28; ks++) {
          a[ks].x = bsub(a[ks].x, mb0); a[ks].y = bsub(a[ks].y, mb1); a[ks].z = bsub(a[ks].z, mb0); a[ks].w = bsub(a[ks].w, mb1);
          mma16816(c0[ks & 1], a[ks], a[ks].x, a[ks].z); mma16816(c1[ks & 1], a[ks], a[ks].y, a[ks].w);
        }
        const int src = (ln_ & 28) | (g >> 1);
        const float q0 = __shfl_sync(~0u, (g & 1) ? c0[0][1] + c0[1][1] : c0[0][0] + c0[1][0], src), q1 = __shfl_sync(~0u, (g & 1) ? c1[0][3] + c1[1][3] : c1[0][2] + c1[1][2], src);
        const float e0 = m0 - blo(mb0), e1 = m1 - blo(mb1);
        r0 = rsqrtf(fmaxf(q0 * (1.f / 448) - e0 * e0, 0.f) + 1e-5f); r1 = rsqrtf(fmaxf(q1 * (1.f / 448) - e1 * e1, 0.f) + 1e-5f);
      } else {
        ll_issue<0, 14>(a, pa, 32);
        if (wg == 0) { RLAST(1u, 10u) xw[3][0] = tg(xw[3][0], 0); RPUB(3) } else { xw[3][0] = xw[3][1] = xw[3][2] = xw[3][3] = 0; }
        MARK(20);
        ll_issue<14, 7>(a, pa, 32);
        ln_stats(xw, sLN, warp, lane, g_S2 + (t * 8 + c) * 8);
      }
      MARK(2 + L * 19);
      float ak[28], av[28], aq[28], pp[28];
#define KVSTAGE(i) { if (L) ll_check<7 * i, 7, false>(a, pa, 32, tag); const uint32_t st = acquire(); wg_fence(); \
      _Pragma("unroll") for (int ks = 0; ks < 7; ks++) { const uint4 f = a[7 * i + ks]; \
        wgmma_rs56(ak, f.x, f.y, f.z, f.w, mkdesc(st, ks * 2048, 1024, 1024, 1), i | ks); \
        wgmma_rs56(av, f.x, f.y, f.z, f.w, mkdesc(st, 14336 + ks * 2048, 1024, 1024, 1), i | ks); } \
      wg_commit(); if (i > 0) { wg_wait<1>(); release(); } }
      KVSTAGE(0) KVSTAGE(1)
      uint4 sv[1];
      const uint4* ps = g_S2 + (t * 8 + warp) * 8 + (ln_ >> 2);
      if (L) { ll_issue<21, 7>(a, pa, 32); ll_issue<0, 1>(sv, ps, 0); }
      KVSTAGE(2) KVSTAGE(3)
      if (L) {
        ll_check<0, 1, false>(sv, ps, 0, 1u);
        const float m0 = -__uint_as_float(sv[0].x), m1 = -__uint_as_float(sv[0].z), h0 = blo(pack(m0, 0.f)), h1 = blo(pack(m1, 0.f));
        r0 = __uint_as_float(sv[0].y); r1 = __uint_as_float(sv[0].w);
        fa = q == 2 ? pack(0.f, h0) : q == 3 ? pack(m0 - h0, h0) : 0u; fb = q == 2 ? pack(0.f, h1) : q == 3 ? pack(m1 - h1, h1) : 0u;
      } else asm volatile("bar.sync 3, 320;" ::: "memory");
      wg_fence();
      wgmma_rs56(ak, fa, fb, 0u, 0u, mkdesc(d16, OFF_CB + 1024, 512, 0, 2), 1);
      wgmma_rs56(av, fa, fb, 0u, 0u, mkdesc(d16, OFF_CB + 2048, 512, 0, 2), 1);
      wg_commit();
      wg_wait<0>(); release(); regfence(ak); regfence(av);
      MARK(3 + L * 19);
      phi_gemm(ak, pp, d16 + (OFF_WPHI >> 4), r0, r1);
#pragma unroll
      for (int j = 0; j < 7; j++) {
        const int n = 8 * j + 2 * q, n2 = n < 28 ? n : n + 4;
        sts32(sV + sw128(row0, n2), pack(av[4 * j] * r0, av[4 * j + 1] * r0)); sts32(sV + sw128(row0 + 8, n2), pack(av[4 * j + 2] * r1, av[4 * j + 3] * r1));
      }
      { const int n2 = 28 + 2 * (q & 1) + 32 * (q >> 1); const uint32_t v = (q & 1) ? 0u : 0x3F80u; sts32(sV + sw128(row0, n2), v); sts32(sV + sw128(row0 + 8, n2), v); }
      wg_wait<0>(); regfence(pp);
      hedgehog(pp, [&](int r, int h, int p, uint32_t v) { sts32(sPK + h * 16384 + sw128(row0 + 8 * r, 8 * p + 2 * q), v); }, [] {});
      fence_async();
      bar_cons();
      MARK(4 + L * 19);
      float kv[16];
      wg_fence();
#pragma unroll
      for (int ks = 0; ks < 8; ks++) wgmma_ss32(kv, mkdesc(d16 + wg * 1024, OFF_PHIK + ks * 2048, 1024, 1024, 1), mkdesc(d16 + wg * 4, OFF_V + ks * 2048, 1024, 1024, 1), ks);
      wg_commit(); wg_wait<0>(); regfence(kv);
      const int ln2 = laneid();
#pragma unroll
      for (int u = 0; u < 4; u++) {
        float e[4];
#pragma unroll
        for (int i = 0; i < 4; i++) e[i] = kv[4 * u + i];
        stll(g_KVP + (c * 16 + t) * 1024 + wg * 512 + u * 128 + (warp & 3) * 32 + ln2, tg(__float_as_uint(e[0]), tag), __float_as_uint(e[1]), __float_as_uint(e[2]), __float_as_uint(e[3]));
      }
      MARK(5 + L * 19);
      uint4 k4[4];
      const uint4* pk = g_KVP + (c * 16 + 4 * (ln2 & 3)) * 1024 + 64 * t + warp * 8 + (ln2 >> 2);
#pragma unroll
      for (int i = 0; i < 2; i++) {
        const uint32_t st = acquire(); wg_fence();
#pragma unroll
        for (int ks = 0; ks < 14; ks++) { const uint4 f = a[14 * i + ks]; wgmma_rs56(aq, f.x, f.y, f.z, f.w, mkdesc(st, ks * 2048, 1024, 1024, 1), i | ks); }
        if (i == 1) wgmma_rs56(aq, fa, fb, 0u, 0u, mkdesc(d16, OFF_CB, 512, 0, 2), 1);
        wg_commit();
        if (i == 0) ll_issue<0, 4>(k4, pk, 1024);
      }
      ll_check<0, 4, false>(k4, pk, 1024, tag);
      float s0 = 0, s1 = 0, s2 = 0, s3 = 0;
#pragma unroll
      for (int i = 0; i < 4; i++) { s0 += __uint_as_float(k4[i].x); s1 += __uint_as_float(k4[i].y); s2 += __uint_as_float(k4[i].z); s3 += __uint_as_float(k4[i].w); }
      s0 = qsum(s0); s1 = qsum(s1); s2 = qsum(s2); s3 = qsum(s3);
      if (q == 0) stll2(g_KVR + c * 1024 + 64 * t + warp * 8 + (ln2 >> 2), tg(pack(s0, s1), tag), pack(s2, s3));
      MARK(6 + L * 19);
      wg_wait<0>(); release(); release(); regfence(aq);
      phi_gemm(aq, pp, d16 + (OFF_WPHI >> 4), r0, r1);
      bar_cons();
#pragma unroll
      for (int i = 0; i < 4; i++) sts128(sV + warp * 2048 + (lane + i * 32) * 16, 0, 0, 0, 0);
      wg_wait<0>(); regfence(pp);
      uint2 r[4];
      const uint2* pr = g_KVR + c * 1024 + wg * 512 + (warp & 3) * 32 + ln2;
      hedgehog(pp, [&](int r, int h, int p, uint32_t v) { phq[r][h][p] = v; }, [&] {
#pragma unroll
        for (int u = 0; u < 4; u++) r[u] = ldll2(pr + u * 128); });
      MARK(7 + L * 19);
#pragma unroll 1
      for (int it = 0; it < SPIN; it++) {
        if (!__any_sync(~0u, ((r[0].x ^ tag) | (r[1].x ^ tag) | (r[2].x ^ tag) | (r[3].x ^ tag)) & 1)) break;
#pragma unroll
        for (int u = 0; u < 4; u++) r[u] = ldll2(pr + u * 128);
      }
#pragma unroll
      for (int u = 0; u < 4; u++) {
        const int d = 8 * u + 2 * q;
        if (d < 28) { sts32(sV + sw128(row0, 28 * wg + d), r[u].x); sts32(sV + sw128(row0 + 8, 28 * wg + d), r[u].y); }
        else if (d == 28) {
#pragma unroll
          for (int j = 0; j < 4; j++) { sts16(sV + sw128(row0, 56 + 2 * j + wg), r[u].x); sts16(sV + sw128(row0 + 8, 56 + 2 * j + wg), r[u].y); }
        }
      }
      fence_async();
      bar_cons();
      MARK(8 + L * 19);
      float o[32];
      wg_fence();
#pragma unroll
      for (int ks = 0; ks < 8; ks++) {
        const int h = ks >> 2, p = 2 * (ks & 3);
        wgmma_rs64(o, phq[0][h][p], phq[1][h][p], p < 6 ? phq[0][h][p < 6 ? p + 1 : 0] : 0u, p < 6 ? phq[1][h][p < 6 ? p + 1 : 0] : 0u, mkdesc(d16, OFF_V + ks * 2048, 1024, 1024, 1), ks);
      }
      wg_commit(); wg_wait<0>(); regfence(o);
      const float iA0 = rcp(o[28] + 1e-6f), iB0 = rcp(o[29] + 1e-6f), iA1 = rcp(o[30] + 1e-6f), iB1 = rcp(o[31] + 1e-6f);
      uint32_t w[14];
      { PTRS
#pragma unroll
      for (int j = 0; j < 7; j++) {
        const bool hb = 8 * j + 2 * q >= 28; const float i0 = hb ? iB0 : iA0, i1 = hb ? iB1 : iA1;
        w[2 * j] = pack(o[4 * j] * i0, o[4 * j + 1] * i0); w[2 * j + 1] = pack(o[4 * j + 2] * i1, o[4 * j + 3] * i1);
        if (j == 0 || ((j ^ c) & 1) == 0) w[2 * j] = tg(w[2 * j], tag);
      }
      slice_store(sf + OO, sh + 2 * OO, w, c & 1);
      hint_post(hme, hs + 2, lane); }
    }
    MARK(9 + L * 19);
    uint4 xr[4];
    if (c < 7) {
      PTRS
      ll_issue<0, 4>(xr, fm + XR + 128 * c, 32);
      uint4 a[28];
      const uint4* pa = fm + OO;
      hint_wait(hrow, hs + 2);
      MARK(10 + L * 19);
      ll_issue<0, 28, true>(a, pa, 32, f2 + 2 * OO);
      float y[32];
      uint32_t st;
#define WOSTEP(i) { ll_check<7 * i, 7, true>(a, pa, 32, tag, f2 + 2 * OO); if (!(i & 1)) st = acquire(); wg_fence(); \
      _Pragma("unroll") for (int ks = 0; ks < 7; ks++) { const uint4 f = a[7 * i + ks]; \
        wgmma_rs64(y, f.x, f.y, f.z, f.w, mkdesc(st, ((i & 1) * 7 + ks) * 2048, 1024, 1024, 1), i | ks); } wg_commit(); }
      WOSTEP(0) WOSTEP(1) WOSTEP(2) WOSTEP(3)
      ll_check<0, 4, false>(xr, fm + XR + 128 * c, 32, tag);
      wg_wait<0>(); regfence(y);
      MARK(11 + L * 19);
#pragma unroll
      for (int u = 0; u < 4; u++) {
        xr[u].x = tg(pack(blo(xr[u].x) + y[8 * u], bhi(xr[u].x) + y[8 * u + 1]), tag); xr[u].y = pack(blo(xr[u].y) + y[8 * u + 2], bhi(xr[u].y) + y[8 * u + 3]);
        xr[u].z = pack(blo(xr[u].z) + y[8 * u + 4], bhi(xr[u].z) + y[8 * u + 5]); xr[u].w = pack(blo(xr[u].w) + y[8 * u + 6], bhi(xr[u].w) + y[8 * u + 7]);
        stll(fm + X1 + 128 * c + u * 32, xr[u].x, xr[u].y, xr[u].z, xr[u].w);
      }
      hint_post(hme, hs + 3, lane);
    } else {
      PTRS
      hint_post(hme, hs + 3, lane);
      acquire(); acquire();
      hint_wait(g_H + (t * 8 + warp) * 8, hs + 3);
      ll_issue<0, 4>(xr, fm + X1, 32); ll_check<0, 4, false>(xr, fm + X1, 32, tag);
      MARK(10 + L * 19); MARK(11 + L * 19);
    }
    uint32_t hf[56];
    float rr0, rr1;
    {
      PTRS
      uint4 a[28];
      const uint4* pa = fm + X1;
      auto grp = [&](int i) -> const uint4* { const int k = i + c; return pa + ((k >= 7 ? k - 7 : k) - i) * 128; };
#pragma unroll
      for (int u = 0; u < 4; u++) a[u] = xr[u];
      float y[96], z[16];
#define F1STAGE(i) { if (i > 0) ll_check<4 * i, 4, false>(a, grp(i), 32, tag); const uint32_t st = acquire(); wg_fence(); \
      _Pragma("unroll") for (int ks = 0; ks < 4; ks++) { const uint4 f = a[4 * i + ks]; \
        wgmma_rs192(y, f.x, f.y, f.z, f.w, mkdesc(st, (ks >> 1) * 12288 + (ks & 1) * 2048, 4096, 1024, 1), i | ks); \
        wgmma_rs32(z, f.x, f.y, f.z, f.w, mkdesc(st, 24576 + ks * 1024, 512, 512, 2), i | ks); } \
      wg_commit(); if (i > 0) { wg_wait<1>(); release(); if (i < 4) ll_issue<(i < 4 ? 4 * i + 12 : 0), 4>(a, grp(i + 3), 32); } }
      F1STAGE(0)
      hint_wait(hrow, hs + 3);
      MARK(12 + L * 19);
      ll_issue<4, 4>(a, grp(1), 32); ll_issue<8, 4>(a, grp(2), 32); ll_issue<12, 4>(a, grp(3), 32);
      if (c < 7) {
        float s0 = 0.f, s1 = 0.f, v0 = 0.f, v1 = 0.f;
#pragma unroll
        for (int u = 0; u < 4; u++) { s0 += (blo(xr[u].x) + bhi(xr[u].x)) + (blo(xr[u].z) + bhi(xr[u].z)); s1 += (blo(xr[u].y) + bhi(xr[u].y)) + (blo(xr[u].w) + bhi(xr[u].w)); }
        s0 = qsum(s0) * (1.f / 64); s1 = qsum(s1) * (1.f / 64);
#pragma unroll
        for (int u = 0; u < 4; u++) {
          const float d0 = blo(xr[u].x) - s0, d1 = bhi(xr[u].x) - s0, d2 = blo(xr[u].z) - s0, d3 = bhi(xr[u].z) - s0;
          const float d4 = blo(xr[u].y) - s1, d5 = bhi(xr[u].y) - s1, d6 = blo(xr[u].w) - s1, d7 = bhi(xr[u].w) - s1;
          v0 += (d0 * d0 + d1 * d1) + (d2 * d2 + d3 * d3); v1 += (d4 * d4 + d5 * d5) + (d6 * d6 + d7 * d7);
        }
        v0 = qsum(v0); v1 = qsum(v1);
        if (q == 0) stll(g_ST + ((t * 8 + warp) * 8 + c) * 8 + (ln_ >> 2), tg(__float_as_uint(s0), tag), __float_as_uint(v0), __float_as_uint(s1), __float_as_uint(v1));
      }
      release(); release();
      F1STAGE(1) MARK(13 + L * 19); F1STAGE(2) F1STAGE(3)
      uint4 sv[2];
      const uint4* ps = g_ST + ((t * 8 + warp) * 8 + 2 * (laneid() & 3)) * 8 + (laneid() >> 2);
      ll_issue<0, 2>(sv, ps, q < 3 ? 8 : 0);
      F1STAGE(4)
      ll_check<0, 2, false>(sv, ps, q < 3 ? 8 : 0, tag);
      const float wb = q < 3 ? 1.f : 0.f;
      const float ma = __uint_as_float(sv[0].x), mb = __uint_as_float(sv[1].x), mc = __uint_as_float(sv[0].z), md = __uint_as_float(sv[1].z);
      const float m0 = qsum(ma + wb * mb) * (1.f / 7), m1 = qsum(mc + wb * md) * (1.f / 7);
      const float v0 = qsum(__uint_as_float(sv[0].y) + 64.f * (ma - m0) * (ma - m0) + wb * (__uint_as_float(sv[1].y) + 64.f * (mb - m0) * (mb - m0)));
      const float v1 = qsum(__uint_as_float(sv[0].w) + 64.f * (mc - m1) * (mc - m1) + wb * (__uint_as_float(sv[1].w) + 64.f * (md - m1) * (md - m1)));
      const float e0 = v0 * (1.f / 448) + 1e-5f, e1 = v1 * (1.f / 448) + 1e-5f;
      rr0 = 1.f / e0; rr1 = 1.f / e1;
      auto fold = [&](float m, float sd) -> uint32_t {
        const float mh = blo(pack(-m, 0.f)), sh_ = blo(pack(sd, 0.f));
        return q == 0 ? pack(mh, -m - mh) : q == 1 ? pack(mh, sh_) : q == 2 ? pack(sd - sh_, 0.f) : 0u;
      };
      const uint32_t fa = fold(m0, sqrtf(e0)), fb = fold(m1, sqrtf(e1));
      if (L == 0) asm volatile("bar.sync 4, 288;" ::: "memory");
      wg_fence();
      wgmma_rs192(y, fa, fb, 0u, 0u, mkdesc(d16, OFF_CB + 0, 512, 0, 2), 1);
      wgmma_rs32(z, fa, fb, 0u, 0u, mkdesc(d16, OFF_CB + 3072, 512, 0, 2), 1);
      F1STAGE(5) F1STAGE(6)
      wg_wait<0>(); release(); regfence(y); regfence(z);
      MARK(14 + L * 19);
#pragma unroll
      for (int j = 0; j < 56; j++) {
        uint32_t r; asm("cvt.rn.relu.bf16x2.f32 %0, %1, %2;" : "=r"(r) : "f"(j < 48 ? y[j < 48 ? 2 * j + 1 : 0] : z[j < 48 ? 0 : 2 * j - 95]), "f"(j < 48 ? y[j < 48 ? 2 * j : 0] : z[j < 48 ? 0 : 2 * j - 96]));
        asm("mul.bf16x2 %0, %1, %1;" : "=r"(hf[j]) : "r"(r));
      }
    }
    MARK(15 + L * 19);
    {
      PTRS
      float ya[32], yb[32];
      uint4* pp = g_P + ((t * 8 + warp) * 8 + c) * 28 * 32 + ln_;
#define F2STORE(j, Y) { regfence(Y); _Pragma("unroll") for (int u = 0; u < 4; u++) \
      stll(pp + (4 * (j) + u) * 32, tg(pack(Y[8 * u] * rr0, Y[8 * u + 1] * rr0), tag), pack(Y[8 * u + 2] * rr1, Y[8 * u + 3] * rr1), \
           pack(Y[8 * u + 4] * rr0, Y[8 * u + 5] * rr0), pack(Y[8 * u + 6] * rr1, Y[8 * u + 7] * rr1)); if ((j) >= 5) hint_post(hme, hs + (4 + (j)), lane); }
#define F2PASS(j, Y, Z) { const uint32_t st = acquire(); wg_fence(); \
      _Pragma("unroll") for (int ks = 0; ks < 14; ks++) wgmma_rs64(Y, hf[4 * ks], hf[4 * ks + 1], hf[4 * ks + 2], hf[4 * ks + 3], mkdesc(st, ks * 2048, 1024, 1024, 1), ks); \
      wg_commit(); if (j > 0) { wg_wait<1>(); release(); F2STORE(j - 1, Z) } }
      const uint4* pr = g_P + ((t * 8 + c) * 8 * 28 + warp) * 32 + ln_;
      uint4 p[8], p2[8]; uint2 xa, xb, xc, xd; uint32_t ba, bb, bc, bd;
      const uint32_t ptag = tag;
      const uint32_t* hred = g_H + (t * 8 + c) * 8 + (ln_ & 7);
      F2PASS(0, ya, yb) F2PASS(1, yb, ya) F2PASS(2, ya, yb) F2PASS(3, yb, ya)
      F2PASS(4, ya, yb)
      RISSUE(0, p, xa, xb, ba, bb)
      F2PASS(5, yb, ya)
      REDU(0, p, xa, xb, ba, bb)
      if (L == 0) { xw[0][0] = tg(xw[0][0], 0); RPUB(0) }
      F2PASS(6, ya, yb)
      RISSUE(1, p, xa, xb, ba, bb)
      wg_wait<0>(); release(); F2STORE(6, ya)
      MARK(16 + L * 19);
      if (L == 0) asm volatile("bar.sync 8, 288;" ::: "memory");
      if (wg) hint_wait(hred, hs + 9);
      RISSUE(2, p2, xc, xd, bc, bd)
      REDU(1, p, xa, xb, ba, bb)
      if (L == 0) { xw[1][0] = tg(xw[1][0], 0); RPUB(1) }
      MARK(17 + L * 19);
      REDU(2, p2, xc, xd, bc, bd)
      if (L == 0) { xw[2][0] = tg(xw[2][0], 0); RPUB(2) }
    }
    MARK(18 + L * 19);
  }
  {
    PTRS
    uint32_t* op = (uint32_t*)(out + XOFF(ln_));
#define OUT(u) { op[u * 64] = xw[u][0]; op[u * 64 + 1792] = xw[u][1]; op[u * 64 + 4] = xw[u][2]; op[u * 64 + 1796] = xw[u][3]; }
    OUT(0) OUT(1) OUT(2)
    if (wg == 0) { RLAST(0u, 20u) OUT(3) }
    else if (warp == 7) {
      if (t == 0 && lane == 0) g_WQF[c] = 0;
      if (lane < 8) stll(g_S2 + (t * 8 + c) * 8 + lane, 0, 0, 0, 0);
      if (lane < 4) { stll(g_CS + blockIdx.x * 4 + lane, 0, 0, 0, 0); if (blockIdx.x < 68) stll(g_CS + 512 + blockIdx.x * 4 + lane, 0, 0, 0, 0); }
    }
  }
  MARK(38); GT(39);
  }
}

typedef CUresult (*EncFn)(CUtensorMap*, CUtensorMapDataType, cuuint32_t, void*, const cuuint64_t*, const cuuint64_t*, const cuuint32_t*, const cuuint32_t*,
                          CUtensorMapInterleave, CUtensorMapSwizzle, CUtensorMapL2promotion, CUtensorMapFloatOOBfill);

extern "C" void kernel_launch(void* const* d_in, const int* in_sizes, int n_in, void* d_out, int out_size) {
  static EncFn enc = nullptr;
  if (!enc) {
    void* fn = nullptr; cudaDriverEntryPointQueryResult qr;
    cudaGetDriverEntryPoint("cuTensorMapEncodeTiled", &fn, cudaEnableDefault, &qr);
    enc = (EncFn)fn;
    cudaFuncSetAttribute(fused_kernel, cudaFuncAttributeMaxDynamicSharedMemorySize, SMEM_BYTES);
  }
  CUtensorMap mQKV, mWO, mW1, mW1b, mW2, mW2b, mX;
  const cuuint32_t es[3] = {1, 1, 1};
  auto enc2 = [&](CUtensorMap* m, void* p, cuuint64_t cols, cuuint64_t rows, cuuint32_t bc, cuuint32_t br) {
    const cuuint64_t dims[2] = {cols, rows}, str[1] = {cols * 2}; const cuuint32_t box[2] = {bc, br};
    enc(m, CU_TENSOR_MAP_DATA_TYPE_BFLOAT16, 2, p, dims, str, box, es, CU_TENSOR_MAP_INTERLEAVE_NONE,
        bc == 64 ? CU_TENSOR_MAP_SWIZZLE_128B : CU_TENSOR_MAP_SWIZZLE_64B, CU_TENSOR_MAP_L2_PROMOTION_L2_128B, CU_TENSOR_MAP_FLOAT_OOB_FILL_NONE);
  };
  enc2(&mQKV, d_in[1], 1344, 448, 64, 112); enc2(&mWO, d_in[3], 448, 448, 64, 112); enc2(&mW1b, d_in[5], 1792, 448, 32, 32);
  enc2(&mX, d_in[0], 448, 2048, 64, 128);
  enc2(&mW2, d_in[7], 448, 1792, 64, 96); enc2(&mW2b, d_in[7], 448, 1792, 64, 16);
  {
    const cuuint64_t dims[3] = {64, 448, 28}, str[2] = {3584, 128}; const cuuint32_t box[3] = {64, 32, 3};
    enc(&mW1, CU_TENSOR_MAP_DATA_TYPE_BFLOAT16, 3, d_in[5], dims, str, box, es, CU_TENSOR_MAP_INTERLEAVE_NONE, CU_TENSOR_MAP_SWIZZLE_128B,
        CU_TENSOR_MAP_L2_PROMOTION_L2_128B, CU_TENSOR_MAP_FLOAT_OOB_FILL_NONE);
  }
  typedef const __nv_bfloat16* BP;
  fused_kernel<<<128, 384, SMEM_BYTES>>>(mQKV, mWO, mW1, mW1b, mW2, mW2b, mX, (BP)d_in[1], (BP)d_in[2], (BP)d_in[3], (BP)d_in[5], (BP)d_in[6], (BP)d_in[7], (BP)d_in[8],
                                         (__nv_bfloat16*)d_out);
}
```

```cpp
#include <cuda_runtime.h>
#include <cuda_bf16.h>
#include <cuda.h>
#include <stdint.h>

constexpr int NST = 6, STAGE = 28672;
constexpr int OFF_PHIK = NST * STAGE;
constexpr int OFF_V = OFF_PHIK + 32768;
constexpr int OFF_WPHI = OFF_V + 16384;
constexpr int OFF_CB = OFF_WPHI + 7168;
constexpr int OFF_BAR = OFF_CB + 3584;
constexpr int SMEM_BYTES = OFF_BAR + 16 * NST + 8;
constexpr int FR = 16 * 8 * 28 * 32;
constexpr int SPIN = 1 << 18;
#define MC 0
#define MAPPING MC
#define MCS
#define MCA(n)
#define CLUSTER
#define HOP 1
#define LATE 1
#define PACE 2

__device__ uint4 g_F[3 * FR];
constexpr int XR = 0, OO = FR, X1 = 2 * FR;
__device__ uint4 g_P[8 * FR];
__device__ uint4 g_ST[16 * 8 * 8 * 8];
__device__ uint4 g_KVP[8 * 16 * 1024];
__device__ uint2 g_KVR[8 * 1024];
__device__ uint4 g_CS[784];
__device__ uint4 g_S2[16 * 8 * 8];
__device__ uint4 g_WQ[8 * 6 * (STAGE / 16)];
__device__ uint32_t g_WQF[8];
__device__ uint32_t g_H[16 * 8 * 8];
#define MARK(i)
#define GT(i)

__device__ __forceinline__ uint32_t s2u(const void* p) { return (uint32_t)__cvta_generic_to_shared(p); }
__device__ __forceinline__ void mbar_init(uint32_t b, uint32_t c) { asm volatile("mbarrier.init.shared::cta.b64 [%0], %1;" ::"r"(b), "r"(c)); }
__device__ __forceinline__ void mbar_expect(uint32_t b, uint32_t tx) { asm volatile("mbarrier.arrive.expect_tx.shared::cta.b64 _, [%0], %1;" ::"r"(b), "r"(tx) : "memory"); }
__device__ __forceinline__ void mbar_arrive_cl(uint32_t b, uint32_t rank) {
  asm volatile("{.reg .b32 r; mapa.shared::cluster.u32 r, %0, %1; mbarrier.arrive.shared::cluster.b64 _, [r];}" ::"r"(b), "r"(rank) : "memory");
}
__device__ __forceinline__ void mbar_wait(uint32_t b, uint32_t ph) {
  uint32_t ok = 0;
#pragma unroll 1
  for (int it = 0; it < SPIN && !ok; it++)
    asm volatile("{.reg .pred p; mbarrier.try_wait.parity.shared::cta.b64 p,[%1],%2; selp.u32 %0,1,0,p;}" : "=r"(ok) : "r"(b), "r"(ph) : "memory");
}
__device__ __forceinline__ void tma2d(uint32_t dst, const CUtensorMap* m, int c0, int c1, uint32_t bar) {
  asm volatile("cp.async.bulk.tensor.2d.shared::cluster.global.mbarrier::complete_tx::bytes" MCS " [%0], [%1, {%3, %4}], [%2]" MCA(5) ";"
               ::"r"(dst), "l"(m), "r"(bar), "r"(c0), "r"(c1), "h"((uint16_t)3) : "memory");
}
__device__ __forceinline__ void tma3d(uint32_t dst, const CUtensorMap* m, int c0, int c1, int c2, uint32_t bar) {
  asm volatile("cp.async.bulk.tensor.3d.shared::cluster.global.mbarrier::complete_tx::bytes" MCS " [%0], [%1, {%3, %4, %5}], [%2]" MCA(6) ";"
               ::"r"(dst), "l"(m), "r"(bar), "r"(c0), "r"(c1), "r"(c2), "h"((uint16_t)3) : "memory");
}
__device__ __forceinline__ void l2pf(const void* p, uint32_t bytes) { asm volatile("cp.async.bulk.prefetch.L2.global [%0], %1;" ::"l"(p), "r"(bytes) : "memory"); }
__device__ __forceinline__ void wg_fence() { asm volatile("wgmma.fence.sync.aligned;" ::: "memory"); }
__device__ __forceinline__ void wg_commit() { asm volatile("wgmma.commit_group.sync.aligned;" ::: "memory"); }
template <int N> __device__ __forceinline__ void wg_wait() { asm volatile("wgmma.wait_group.sync.aligned %0;" ::"n"(N) : "memory"); }
template <int N> __device__ __forceinline__ void regfence(float (&d)[N]) {
#pragma unroll
  for (int i = 0; i < N; i++) asm volatile("" : "+f"(d[i])::"memory");
}
__device__ __forceinline__ void bar_cons() { asm volatile("bar.sync 1, 256;" ::: "memory"); }
__device__ __forceinline__ void fence_async() { asm volatile("fence.proxy.async.shared::cta;" ::: "memory"); }
struct Desc { uint32_t lo, hi; };
__device__ __forceinline__ Desc mkdesc(uint32_t base16, uint32_t off, uint32_t lbo, uint32_t sbo, uint32_t swz) {
  return Desc{base16 + ((off >> 4) | ((lbo >> 4) << 16)), (sbo >> 4) | (swz << 30)};
}
__device__ __forceinline__ uint4 ldll(const uint4* p) {
  uint4 v; asm volatile("ld.relaxed.gpu.global.v4.u32 {%0,%1,%2,%3}, [%4];" : "=r"(v.x), "=r"(v.y), "=r"(v.z), "=r"(v.w) : "l"(p) : "memory"); return v;
}
__device__ __forceinline__ uint2 ldll2(const uint2* p) {
  uint2 v; asm volatile("ld.relaxed.gpu.global.v2.u32 {%0,%1}, [%2];" : "=r"(v.x), "=r"(v.y) : "l"(p) : "memory"); return v;
}
__device__ __forceinline__ void stll(uint4* p, uint32_t x, uint32_t y, uint32_t z, uint32_t w) {
  asm volatile("st.relaxed.gpu.global.v4.u32 [%0], {%1,%2,%3,%4};" ::"l"(p), "r"(x), "r"(y), "r"(z), "r"(w) : "memory");
}
__device__ __forceinline__ void stll2(void* p, uint32_t x, uint32_t y) {
  asm volatile("st.relaxed.gpu.global.v2.u32 [%0], {%1,%2};" ::"l"(p), "r"(x), "r"(y) : "memory");
}
__device__ __forceinline__ int laneid() { int l; asm volatile("mov.u32 %0, %%laneid;" : "=r"(l)); return l; }
__device__ __forceinline__ uint32_t tg(uint32_t w, uint32_t tag) { return (w & ~1u) | tag; }
__device__ __forceinline__ uint32_t pack(float lo, float hi) {
  uint32_t r; asm("cvt.rn.bf16x2.f32 %0, %1, %2;" : "=r"(r) : "f"(hi), "f"(lo)); return r;
}
__device__ __forceinline__ float blo(uint32_t w) { return __uint_as_float(w << 16); }
__device__ __forceinline__ float bhi(uint32_t w) { return __uint_as_float(w & 0xffff0000u); }
__device__ __forceinline__ float ex2(float x) { float r; asm("ex2.approx.ftz.f32 %0, %1;" : "=f"(r) : "f"(x)); return r; }
__device__ __forceinline__ float rcp(float x) { float r; asm("rcp.approx.ftz.f32 %0, %1;" : "=f"(r) : "f"(x)); return r; }
__device__ __forceinline__ float qsum(float v) { v += __shfl_xor_sync(~0u, v, 1); v += __shfl_xor_sync(~0u, v, 2); return v; }
__device__ __forceinline__ void sts32(uint32_t a, uint32_t v) { asm volatile("st.shared.u32 [%0], %1;" ::"r"(a), "r"(v) : "memory"); }
__device__ __forceinline__ void sts16(uint32_t a, uint32_t v) { asm volatile("st.shared.u16 [%0], %1;" ::"r"(a), "h"((uint16_t)v) : "memory"); }
__device__ __forceinline__ void sts128(uint32_t a, uint32_t x, uint32_t y, uint32_t z, uint32_t w) {
  asm volatile("st.shared.v4.u32 [%0], {%1,%2,%3,%4};" ::"r"(a), "r"(x), "r"(y), "r"(z), "r"(w) : "memory");
}
__device__ __forceinline__ uint32_t sw128(int row, int col) { return row * 128 + ((((col >> 3) ^ row) & 7) << 4) + (col & 7) * 2; }

__device__ __forceinline__ void wgmma_rs56(float (&d)[28], const uint32_t a0, const uint32_t a1, const uint32_t a2, const uint32_t a3, Desc db, int sd) {
  asm volatile("{.reg .pred p; .reg .b64 da, db; setp.ne.b32 p, %33, 0; mov.b64 db, {%32, %34};\n wgmma.mma_async.sync.aligned.m64n56k16.f32.bf16.bf16 {%0,%1,%2,%3,%4,%5,%6,%7,%8,%9,%10,%11,%12,%13,%14,%15,%16,%17,%18,%19,%20,%21,%22,%23,%24,%25,%26,%27}, {%28,%29,%30,%31}, db, p, 1, 1, 1;}"
   : "+f"(d[0]),"+f"(d[1]),"+f"(d[2]),"+f"(d[3]),"+f"(d[4]),"+f"(d[5]),"+f"(d[6]),"+f"(d[7]),"+f"(d[8]),"+f"(d[9]),"+f"(d[10]),"+f"(d[11]),"+f"(d[12]),"+f"(d[13]),"+f"(d[14]),"+f"(d[15]),"+f"(d[16]),"+f"(d[17]),"+f"(d[18]),"+f"(d[19]),"+f"(d[20]),"+f"(d[21]),"+f"(d[22]),"+f"(d[23]),"+f"(d[24]),"+f"(d[25]),"+f"(d[26]),"+f"(d[27])
   : "r"(a0),"r"(a1),"r"(a2),"r"(a3),"r"(db.lo),"r"(sd),"r"(db.hi));
}
__device__ __forceinline__ void wgmma_rs64(float (&d)[32], const uint32_t a0, const uint32_t a1, const uint32_t a2, const uint32_t a3, Desc db, int sd) {
  asm volatile("{.reg .pred p; .reg .b64 da, db; setp.ne.b32 p, %37, 0; mov.b64 db, {%36, %38};\n wgmma.mma_async.sync.aligned.m64n64k16.f32.bf16.bf16 {%0,%1,%2,%3,%4,%5,%6,%7,%8,%9,%10,%11,%12,%13,%14,%15,%16,%17,%18,%19,%20,%21,%22,%23,%24,%25,%26,%27,%28,%29,%30,%31}, {%32,%33,%34,%35}, db, p, 1, 1, 1;}"
   : "+f"(d[0]),"+f"(d[1]),"+f"(d[2]),"+f"(d[3]),"+f"(d[4]),"+f"(d[5]),"+f"(d[6]),"+f"(d[7]),"+f"(d[8]),"+f"(d[9]),"+f"(d[10]),"+f"(d[11]),"+f"(d[12]),"+f"(d[13]),"+f"(d[14]),"+f"(d[15]),"+f"(d[16]),"+f"(d[17]),"+f"(d[18]),"+f"(d[19]),"+f"(d[20]),"+f"(d[21]),"+f"(d[22]),"+f"(d[23]),"+f"(d[24]),"+f"(d[25]),"+f"(d[26]),"+f"(d[27]),"+f"(d[28]),"+f"(d[29]),"+f"(d[30]),"+f"(d[31])
   : "r"(a0),"r"(a1),"r"(a2),"r"(a3),"r"(db.lo),"r"(sd),"r"(db.hi));
}
__device__ __forceinline__ void wgmma_rs224(float (&d)[112], const uint32_t a0, const uint32_t a1, const uint32_t a2, const uint32_t a3, Desc db, int sd) {
  asm volatile("{.reg .pred p; .reg .b64 db; setp.ne.b32 p, %117, 0; mov.b64 db, {%116, %118};\n wgmma.mma_async.sync.aligned.m64n224k16.f32.bf16.bf16 {%0,%1,%2,%3,%4,%5,%6,%7,%8,%9,%10,%11,%12,%13,%14,%15,%16,%17,%18,%19,%20,%21,%22,%23,%24,%25,%26,%27,%28,%29,%30,%31,%32,%33,%34,%35,%36,%37,%38,%39,%40,%41,%42,%43,%44,%45,%46,%47,%48,%49,%50,%51,%52,%53,%54,%55,%56,%57,%58,%59,%60,%61,%62,%63,%64,%65,%66,%67,%68,%69,%70,%71,%72,%73,%74,%75,%76,%77,%78,%79,%80,%81,%82,%83,%84,%85,%86,%87,%88,%89,%90,%91,%92,%93,%94,%95,%96,%97,%98,%99,%100,%101,%102,%103,%104,%105,%106,%107,%108,%109,%110,%111}, {%112,%113,%114,%115}, db, p, 1, 1, 1;}"
   : "+f"(d[0]),"+f"(d[1]),"+f"(d[2]),"+f"(d[3]),"+f"(d[4]),"+f"(d[5]),"+f"(d[6]),"+f"(d[7]),"+f"(d[8]),"+f"(d[9]),"+f"(d[10]),"+f"(d[11]),"+f"(d[12]),"+f"(d[13]),"+f"(d[14]),"+f"(d[15]),"+f"(d[16]),"+f"(d[17]),"+f"(d[18]),"+f"(d[19]),"+f"(d[20]),"+f"(d[21]),"+f"(d[22]),"+f"(d[23]),"+f"(d[24]),"+f"(d[25]),"+f"(d[26]),"+f"(d[27]),"+f"(d[28]),"+f"(d[29]),"+f"(d[30]),"+f"(d[31]),"+f"(d[32]),"+f"(d[33]),"+f"(d[34]),"+f"(d[35]),"+f"(d[36]),"+f"(d[37]),"+f"(d[38]),"+f"(d[39]),"+f"(d[40]),"+f"(d[41]),"+f"(d[42]),"+f"(d[43]),"+f"(d[44]),"+f"(d[45]),"+f"(d[46]),"+f"(d[47]),"+f"(d[48]),"+f"(d[49]),"+f"(d[50]),"+f"(d[51]),"+f"(d[52]),"+f"(d[53]),"+f"(d[54]),"+f"(d[55]),"+f"(d[56]),"+f"(d[57]),"+f"(d[58]),"+f"(d[59]),"+f"(d[60]),"+f"(d[61]),"+f"(d[62]),"+f"(d[63]),"+f"(d[64]),"+f"(d[65]),"+f"(d[66]),"+f"(d[67]),"+f"(d[68]),"+f"(d[69]),"+f"(d[70]),"+f"(d[71]),"+f"(d[72]),"+f"(d[73]),"+f"(d[74]),"+f"(d[75]),"+f"(d[76]),"+f"(d[77]),"+f"(d[78]),"+f"(d[79]),"+f"(d[80]),"+f"(d[81]),"+f"(d[82]),"+f"(d[83]),"+f"(d[84]),"+f"(d[85]),"+f"(d[86]),"+f"(d[87]),"+f"(d[88]),"+f"(d[89]),"+f"(d[90]),"+f"(d[91]),"+f"(d[92]),"+f"(d[93]),"+f"(d[94]),"+f"(d[95]),"+f"(d[96]),"+f"(d[97]),"+f"(d[98]),"+f"(d[99]),"+f"(d[100]),"+f"(d[101]),"+f"(d[102]),"+f"(d[103]),"+f"(d[104]),"+f"(d[105]),"+f"(d[106]),"+f"(d[107]),"+f"(d[108]),"+f"(d[109]),"+f"(d[110]),"+f"(d[111])
   : "r"(a0),"r"(a1),"r"(a2),"r"(a3),"r"(db.lo),"r"(sd),"r"(db.hi));
}
__device__ __forceinline__ void wgmma_ss32(float (&d)[16], Desc da, Desc db, int sd) {
  asm volatile("{.reg .pred p; .reg .b64 da, db; setp.ne.b32 p, %18, 0; mov.b64 da, {%16, %19}; mov.b64 db, {%17, %19};\n wgmma.mma_async.sync.aligned.m64n32k16.f32.bf16.bf16 {%0,%1,%2,%3,%4,%5,%6,%7,%8,%9,%10,%11,%12,%13,%14,%15}, da, db, p, 1, 1, 1, 1;}"
   : "+f"(d[0]),"+f"(d[1]),"+f"(d[2]),"+f"(d[3]),"+f"(d[4]),"+f"(d[5]),"+f"(d[6]),"+f"(d[7]),"+f"(d[8]),"+f"(d[9]),"+f"(d[10]),"+f"(d[11]),"+f"(d[12]),"+f"(d[13]),"+f"(d[14]),"+f"(d[15])
   : "r"(da.lo),"r"(db.lo),"r"(sd),"r"(db.hi));
}

__device__ __forceinline__ uint4 ldsm4(uint32_t a) {
  uint4 v; asm volatile("ldmatrix.sync.aligned.m8n8.x4.shared.b16 {%0,%1,%2,%3}, [%4];" : "=r"(v.x), "=r"(v.y), "=r"(v.z), "=r"(v.w) : "r"(a) : "memory"); return v;
}
__device__ __forceinline__ void mma16816(float (&d)[4], const uint4& a, uint32_t b0, uint32_t b1) {
  asm("mma.sync.aligned.m16n8k16.row.col.f32.bf16.bf16.f32 {%0,%1,%2,%3}, {%4,%5,%6,%7}, {%8,%9}, {%0,%1,%2,%3};"
      : "+f"(d[0]), "+f"(d[1]), "+f"(d[2]), "+f"(d[3]) : "r"(a.x), "r"(a.y), "r"(a.z), "r"(a.w), "r"(b0), "r"(b1));
}
__device__ __forceinline__ uint32_t bsub(uint32_t a, uint32_t b) { uint32_t r; asm("sub.bf16x2 %0, %1, %2;" : "=r"(r) : "r"(a), "r"(b)); return r; }
__device__ __forceinline__ uint32_t hint_ld(const uint32_t* p) { uint32_t v; asm volatile("ld.relaxed.gpu.global.u32 %0, [%1];" : "=r"(v) : "l"(p) : "memory"); return v; }
template <int S, int N, bool SPL = false, int T> __device__ __forceinline__ void ll_issue(uint4 (&v)[T], const uint4* p, int stride, const uint2* p2 = nullptr) {
#pragma unroll
  for (int i = S; i < S + N; i++) {
    if (SPL && i % 7 == 3) { const uint2 lo = ldll2(p2 + i * 64), hi = ldll2(p2 + i * 64 + 32); v[i] = make_uint4(lo.x, lo.y, hi.x, hi.y); }
    else v[i] = ldll(p + i * stride);
  }
}
template <int S, int N, bool SPL, int T> __device__ __forceinline__ void ll_check(uint4 (&v)[T], const uint4* p, int stride, uint32_t tag, const uint2* p2 = nullptr) {
#pragma unroll 1
  for (int it = 0; it < SPIN; it++) {
    uint32_t bad = 0;
#pragma unroll
    for (int i = S; i < S + N; i++) bad |= (v[i].x ^ tag) | ((SPL && i % 7 == 3) ? (v[i].z ^ tag) : 0u);
    if (!__any_sync(~0u, bad & 1)) break;
    ll_issue<S, N, SPL>(v, p, stride, p2);
  }
}
__device__ __forceinline__ void hint_post(uint32_t* p, uint32_t v, int lane) {
  if (lane == 0) asm volatile("st.relaxed.gpu.global.u32 [%0], %1;" ::"l"(p), "r"(v) : "memory");
}
__device__ __forceinline__ void hint_wait(const uint32_t* p, uint32_t s, uint32_t v = 0xffffu) {
#pragma unroll 1
  for (int it = 0; it < SPIN; it++) {
    if (__all_sync(~0u, v - s < 10u)) break;
    v = hint_ld(p);
  }
}
__device__ __forceinline__ void slice_store(uint4* pf, uint2* ph, const uint32_t (&w)[14], bool odd) {
#pragma unroll
  for (int u = 0; u < 3; u++)
    stll(pf + u * 32, odd ? w[4 * u + 2] : w[4 * u], odd ? w[4 * u + 3] : w[4 * u + 1], odd ? w[4 * u + 4] : w[4 * u + 2], odd ? w[4 * u + 5] : w[4 * u + 3]);
  stll2(ph, odd ? w[0] : w[12], odd ? w[1] : w[13]);
}
template <class F, class M> __device__ __forceinline__ void hedgehog(const float (&d)[28], F sink, M mid) {
  const float L2E = 1.4426950408889634f;
#define HX(G, p) ((p) < 6 ? d[((G) & 1) * 16 + ((p) >> 1) * 4 + ((p) & 1) + ((G) & 2)] : d[12 + (G)])
  float mx[4], mn[4], sp[4], sn[4], ep[4][7], en[4][7];
#pragma unroll
  for (int G = 0; G < 4; G++) {
    mx[G] = mn[G] = HX(G, 0);
#pragma unroll
    for (int p = 1; p < 7; p++) { mx[G] = fmaxf(mx[G], HX(G, p)); mn[G] = fminf(mn[G], HX(G, p)); }
  }
#pragma unroll
  for (int o = 1; o < 4; o <<= 1)
#pragma unroll
    for (int G = 0; G < 4; G++) { mx[G] = fmaxf(mx[G], __shfl_xor_sync(~0u, mx[G], o)); mn[G] = fminf(mn[G], __shfl_xor_sync(~0u, mn[G], o)); }
#pragma unroll
  for (int G = 0; G < 4; G++) {
    const float a = -mx[G] * L2E, b = mn[G] * L2E;
#pragma unroll
    for (int p = 0; p < 7; p++) { ep[G][p] = ex2(fmaf(HX(G, p), L2E, a)); en[G][p] = ex2(fmaf(HX(G, p), -L2E, b)); }
    sp[G] = ((ep[G][0] + ep[G][1]) + (ep[G][2] + ep[G][3])) + ((ep[G][4] + ep[G][5]) + ep[G][6]);
    sn[G] = ((en[G][0] + en[G][1]) + (en[G][2] + en[G][3])) + ((en[G][4] + en[G][5]) + en[G][6]);
    if (G == 1) mid();
  }
#pragma unroll
  for (int o = 1; o < 4; o <<= 1)
#pragma unroll
    for (int G = 0; G < 4; G++) { sp[G] += __shfl_xor_sync(~0u, sp[G], o); sn[G] += __shfl_xor_sync(~0u, sn[G], o); }
#pragma unroll
  for (int G = 0; G < 4; G++) {
    const float a = rcp(sp[G]), b = rcp(sn[G]);
#pragma unroll
    for (int p = 0; p < 7; p++) sink(G >> 1, G & 1, p, pack(ep[G][p] * a, en[G][p] * b));
  }
}
__device__ __forceinline__ void phi_gemm(const float (&x)[28], float (&y)[28], uint32_t wphi, float r0, float r1) {
  uint32_t f[14];
#pragma unroll
  for (int j = 0; j < 14; j++) f[j] = pack(x[2 * j] * (j & 1 ? r1 : r0), x[2 * j + 1] * (j & 1 ? r1 : r0));
  wg_fence();
#pragma unroll
  for (int ks = 0; ks < 3; ks++) wgmma_rs56(y, f[4 * ks], f[4 * ks + 1], f[4 * ks + 2], f[4 * ks + 3], mkdesc(wphi, ks * 2048, 1024, 1024, 1), ks);
  wgmma_rs56(y, f[12], f[13], 0u, 0u, mkdesc(wphi, 3 * 2048, 1024, 1024, 1), 1);
  wg_commit();
}
__device__ __forceinline__ void ln_stats(uint32_t (&xw)[4][4], float* sLN, int warp, int lane, uint4* dst) {
  const int g = lane >> 2; const bool full = warp < 4;
  float s0 = 0.f, s1 = 0.f;
#pragma unroll
  for (int u = 0; u < 4; u++) {
    s0 += (blo(xw[u][0]) + bhi(xw[u][0])) + (blo(xw[u][2]) + bhi(xw[u][2]));
    s1 += (blo(xw[u][1]) + bhi(xw[u][1])) + (blo(xw[u][3]) + bhi(xw[u][3]));
  }
  const float rc = full ? 1.f / 64 : 1.f / 48;
  s0 = qsum(s0); s1 = qsum(s1);
  const float a0 = s0 * rc, a1 = s1 * rc;
  float v0 = 0.f, v1 = 0.f;
#pragma unroll
  for (int u = 0; u < 4; u++)
    if (u < 3 || full) {
#pragma unroll
      for (int k = 0; k < 4; k += 2) {
        float a = blo(xw[u][k]) - a0, b = bhi(xw[u][k]) - a0, c2 = blo(xw[u][k + 1]) - a1, d2 = bhi(xw[u][k + 1]) - a1;
        v0 += a * a + b * b; v1 += c2 * c2 + d2 * d2;
      }
    }
  v0 = qsum(v0); v1 = qsum(v1);
  if ((lane & 3) == 0) *(float4*)(sLN + (g * 8 + warp) * 4) = make_float4(s0, v0, s1, v1);
  if (warp) { asm volatile("bar.arrive 7, 256;" ::: "memory"); return; }
  asm volatile("bar.sync 7, 256;" ::: "memory");
  const float4 ea = *(const float4*)(sLN + (g * 8 + (lane & 3)) * 4), eb = *(const float4*)(sLN + (g * 8 + 4 + (lane & 3)) * 4);
  const float m0 = qsum(ea.x + eb.x) * (1.f / 448), m1 = qsum(ea.z + eb.z) * (1.f / 448);
  const float d0 = ea.x * (1.f / 64) - m0, d1 = eb.x * (1.f / 48) - m0, d2 = ea.z * (1.f / 64) - m1, d3 = eb.z * (1.f / 48) - m1;
  v0 = qsum(ea.y + eb.y + 64.f * d0 * d0 + 48.f * d1 * d1); v1 = qsum(ea.w + eb.w + 64.f * d2 * d2 + 48.f * d3 * d3);
  if ((lane & 3) == 0) stll(dst + g, tg(__float_as_uint(m0), 1), __float_as_uint(rsqrtf(v0 * (1.f / 448) + 1e-5f)), __float_as_uint(m1), __float_as_uint(rsqrtf(v1 * (1.f / 448) + 1e-5f)));
}

__global__ void CLUSTER __launch_bounds__(384, 1)
fused_kernel(const __grid_constant__ CUtensorMap mQKV, const __grid_constant__ CUtensorMap mWO, const __grid_constant__ CUtensorMap mW1,
             const __grid_constant__ CUtensorMap mW1b, const __grid_constant__ CUtensorMap mW2, const __grid_constant__ CUtensorMap mW2b,
             const __grid_constant__ CUtensorMap mX, const __nv_bfloat16* __restrict__ wqkv, const __nv_bfloat16* __restrict__ wphi,
             const __nv_bfloat16* __restrict__ wo, const __nv_bfloat16* __restrict__ w1, const __nv_bfloat16* __restrict__ b1,
             const __nv_bfloat16* __restrict__ w2, const __nv_bfloat16* __restrict__ b2, __nv_bfloat16* __restrict__ out) {
  extern __shared__ __align__(1024) uint8_t sm[];
  const uint32_t sb = s2u(sm);
  const int tid = threadIdx.x, warp = __shfl_sync(~0u, tid >> 5, 0), lane = tid & 31,
            t = MAPPING ? (blockIdx.x >> 4) * 2 + (blockIdx.x & 1) : blockIdx.x >> 3, c = MAPPING ? (blockIdx.x >> 1) & 7 : blockIdx.x & 7;
  const uint32_t bfull = sb + OFF_BAR, bempty = bfull + 8 * NST;

#define XOFF(l) ((t * 128 + c * 16 + ((l) >> 2)) * 448 + warp * 16 + 2 * ((l) & 3))
  if (warp < 8) { MARK(0); GT(19); }
  if (tid == 256) {
    for (int s = 0; s < NST; s++) { mbar_init(bfull + 8 * s, 1); mbar_init(bempty + 8 * s, MC ? 16 : 8); }
    mbar_init(bempty + 8 * NST, 1);
    asm volatile("fence.mbarrier_init.release.cluster;" ::: "memory");
    fence_async();
    mbar_expect(bempty + 8 * NST, 114688);
    for (int i = 0; i < 7; i++)
      asm volatile("cp.async.bulk.tensor.2d.shared::cluster.global.mbarrier::complete_tx::bytes [%0], [%1, {%3, %4}], [%2];"
                   ::"r"(sb + 2 * STAGE + i * 16384), "l"(&mX), "r"(bempty + 8 * NST), "r"(64 * i), "r"(128 * t) : "memory");
  }
  asm volatile("barrier.cluster.arrive.release.aligned; barrier.cluster.wait.acquire.aligned;" ::: "memory");
  if (warp >= 8) {
    asm volatile("setmaxnreg.dec.sync.aligned.u32 24;");
    auto issue = [&](int i, int s) {
      const uint32_t dst = sb + s * STAGE, bar = bfull + 8 * s;
      mbar_expect(bar, STAGE);
#pragma unroll 1
      for (int rk = MC ? (blockIdx.x & 1) : 0; rk < (MC ? (blockIdx.x & 1) + 1 : 2); rk++)
      if (i < 4) tma2d(dst + rk * 14336, &mQKV, 448 + 448 * rk + 56 * c, 112 * i, bar);
      else if (i < 8) tma2d(dst + rk * 14336, i < 6 ? &mQKV : &mWO, (i < 6 ? 56 : 64) * c, 224 * (i & 1) + 112 * rk, bar);
      else if (i < 15) { const int k0 = 64 * ((i - 8 + c) % 7) + 32 * rk;
        tma3d(dst + rk * 14336, &mW1, 0, k0, 6 * c, bar); tma2d(dst + rk * 14336 + 12288, &mW1b, 1536 + 32 * c, k0, bar); }
      else { tma2d(dst + rk * 12288, &mW2, 64 * (i - 15), 192 * c + 96 * rk, bar); tma2d(dst + 24576 + rk * 2048, &mW2b, 64 * (i - 15), 1536 + 32 * c + 16 * rk, bar); }
    };
    auto colsum = [&](int job) {
        const int ld4 = job < 112 ? 448 : 336;
        const uint2* wp = (job < 112 ? (const uint2*)w1 + job * 4 : (const uint2*)wqkv + (job - 112) * 4) + (lane >> 2) * ld4 + (lane & 3);
        float s0 = 0.f, s1 = 0.f, s2 = 0.f, s3 = 0.f;
#pragma unroll 8
        for (int i = 0; i < 56; i++) { const uint2 v = __ldg(wp + i * 8 * ld4); s0 += blo(v.x); s1 += bhi(v.x); s2 += blo(v.y); s3 += bhi(v.y); }
#pragma unroll 1
        for (int o = 4; o < 32; o <<= 1) { s0 += __shfl_xor_sync(~0u, s0, o); s1 += __shfl_xor_sync(~0u, s1, o); s2 += __shfl_xor_sync(~0u, s2, o); s3 += __shfl_xor_sync(~0u, s3, o); }
        if (lane < 4) stll(g_CS + job * 4 + lane, tg(__float_as_uint(s0), 1), __float_as_uint(s1), __float_as_uint(s2), __float_as_uint(s3));
      };
    if (warp == 8) {
      int s = 0; uint32_t ph = 1;
      for (int n = 0; n < 44; n++) {
        if (n == PACE) asm volatile("bar.sync 2, 288;" ::: "memory");
        mbar_wait(bempty + 8 * s, ph);
        if (n == 22) {
          uint32_t v = 0;
#pragma unroll 1
          for (int it = 0; it < SPIN && v < 32; it++) asm volatile("ld.acquire.gpu.global.u32 %0, [%1];" : "=r"(v) : "l"(g_WQF + c) : "memory");
          asm volatile("fence.proxy.async.global;" ::: "memory");
        }
        if (lane == 0) {
          if (n >= 22 && n < 28) {
            mbar_expect(bfull + 8 * s, STAGE);
            asm volatile("cp.async.bulk.shared::cluster.global.mbarrier::complete_tx::bytes [%0], [%1], %2, [%3];"
                         ::"r"(sb + s * STAGE), "l"(g_WQ + c * 10752 + (n - 22) * (STAGE / 16)), "r"(STAGE), "r"(bfull + 8 * s) : "memory");
          } else issue(n >= 22 ? n - 22 : n, s);
        }
        __syncwarp();
        if (++s == NST) { s = 0; ph ^= 1; }
      }
    } else if (warp == 9) {
      mbar_wait(bfull + 8 * 3, 0);
      if (lane == 0) {
        l2pf((const uint8_t*)wo + blockIdx.x * 3136, 3136);
        l2pf((const uint8_t*)w1 + blockIdx.x * 12544, 12544);
        l2pf((const uint8_t*)w2 + blockIdx.x * 12544, 12544);
      }
      if (blockIdx.x < 112) colsum(blockIdx.x);
      asm volatile("bar.sync 6, 96;" ::: "memory");
#pragma unroll 1
      for (int i = 0; i < 4; i++) {
        const int e = lane < 28 ? lane + 28 * (i & 1) : 0;
        const bool ok = i < 2 || (e < 48 && (e & 15) < 14);
        const int e4 = i < 2 ? (e < 48 ? 48 * c + e : 336 + 8 * c + e) : ok ? 448 + 112 * (e >> 4) + 14 * c + (e & 15) : 448;
        uint4 cv[1];
        ll_issue<0, 1>(cv, g_CS + e4, 0); ll_check<0, 1, false>(cv, g_CS + e4, 0, 1u);
        const uint2 bb = __ldg((const uint2*)b1 + (i < 2 ? e4 : 0));
        const uint32_t h0 = pack(__uint_as_float(cv[0].x), __uint_as_float(cv[0].y)), h1 = pack(__uint_as_float(cv[0].z), __uint_as_float(cv[0].w));
        const uint32_t l0 = pack(__uint_as_float(cv[0].x) - blo(h0), __uint_as_float(cv[0].y) - bhi(h0)), l1 = pack(__uint_as_float(cv[0].z) - blo(h1), __uint_as_float(cv[0].w) - bhi(h1));
#pragma unroll 1
        for (int j = 0; j < (i < 2 ? 5 : 3); j++) {
          const int r = i < 2 ? j : j + 5;
          const uint32_t ad = sb + OFF_CB + (e >> 3) * 512 + r * 64 + ((((e >> 1) ^ (r >> 1)) & 3) << 4) + (e & 1) * 8;
          sts32(ad, j < 2 ? h0 : j == 2 ? l0 : bb.x); sts32(ad + 4, j < 2 ? h1 : j == 2 ? l1 : bb.y);
        }
        if (i & 1) { fence_async(); if (i == 1) asm volatile("bar.arrive 4, 288;" ::: "memory"); else asm volatile("bar.arrive 8, 288;" ::: "memory"); }
      }
    } else if (warp >= 10) {
      const int h = warp - 10;
      uint32_t wv[13];
#pragma unroll
      for (int i = 0; i < 13; i++) { const int e = lane + 32 * i; wv[i] = e < 392 ? __ldg((const uint32_t*)wphi + (2 * c + h) * 392 + e) : 0u; }
#pragma unroll 1
      for (int e = h * 32 + lane; e < 672; e += 64) sts128(sb + OFF_WPHI + e * 16, 0, 0, 0, 0);
      asm volatile("bar.arrive 6, 96;" ::: "memory");
#pragma unroll 1
      for (int i = 0; i < 4; i++) sts128(sb + OFF_PHIK + sw128(h * 128 + i * 32 + lane, 56), 0, 0, 0, 0);
      asm volatile("bar.sync 5, 64;" ::: "memory");
#pragma unroll
      for (int i = 0; i < 13; i++) {
        const int e = lane + 32 * i, d = e / 14, f2 = 2 * (e - 14 * d), k = 28 * h + d;
        if (e < 392) {
          if (f2 < 24) sts32(sb + OFF_WPHI + sw128(k, 32 * h + f2), wv[i]);
          else { sts16(sb + OFF_WPHI + sw128(k, 2 * f2 - 24 + h), wv[i]); sts16(sb + OFF_WPHI + sw128(k, 2 * f2 - 22 + h), wv[i] >> 16); }
        }
      }
      fence_async();
      asm volatile("bar.arrive 3, 320;" ::: "memory");
      mbar_wait(bfull + 8 * 5, 0);
#pragma unroll 2
      for (int e = t * 672 + h * 32 + lane; e < t * 672 + 672; e += 64) {
        const int r = e >> 3, st = r / 224, rr = r - st * 224, ch = (e & 7) ^ (rr & 7);
        const int k = st < 4 ? 112 * st + (rr >= 112 ? rr - 112 : rr) : 224 * (st - 4) + rr, col = (st < 4 ? (rr >= 112 ? 896 : 448) : 0) + 56 * c + 8 * ch;
        g_WQ[c * 10752 + e] = ch < 7 ? __ldg((const uint4*)(wqkv + k * 1344 + col)) : make_uint4(0, 0, 0, 0);
      }
      __syncwarp();
      if (lane == 0) asm volatile("red.release.gpu.global.add.u32 [%0], 1;" ::"l"(g_WQF + c) : "memory");
      if (h == 0 && blockIdx.x < 84) colsum(112 + blockIdx.x);
    }
  } else {
  asm volatile("setmaxnreg.inc.sync.aligned.u32 240;");

  const int wg = warp >> 2, g = lane >> 2, q = lane & 3;
  const int row0 = warp * 16 + g;
#define PTRS const int ln_ = laneid(); \
  uint4* const fm = g_F + ((t * 8 + warp) * 28) * 32 + ln_;            \
  uint4* const fr = g_F + ((t * 8 + c) * 28 + warp) * 32 + ln_;        \
  uint4* const sf = fm + (7 * (c >> 1) + 4 * (c & 1)) * 32;             \
  uint2* const f2 = (uint2*)(fm - ln_) + ln_;                           \
  uint2* const sh = f2 + (7 * (c >> 1) + 3) * 64 + 32 * (c & 1);        \
  uint32_t* const hme = g_H + (t * 8 + warp) * 8 + c; \
  const uint32_t* const hrow = g_H + (t * 8 + warp) * 8 + (ln_ & 7); \
  (void)fm; (void)fr; (void)sf; (void)f2; (void)sh; (void)hme; (void)hrow;
  float* sLN = (float*)(sm + OFF_V);
  const uint32_t sPK = sb + OFF_PHIK, sV = sb + OFF_V, d16 = (sb & 0x3FFFF) >> 4;
    uint32_t xw[4][4];
#pragma unroll
  for (int i = 0; i < 16; i++) xw[i >> 2][i & 3] = 0;
  int cs = 0, rs = 0; uint32_t cph = 0;
  auto acquire = [&]() -> uint32_t { mbar_wait(bfull + 8 * cs, cph); const uint32_t a = d16 + cs * (STAGE >> 4); if (++cs == NST) { cs = 0; cph ^= 1; } return a; };
  int nrel = 44 - NST;
  auto release = [&]() { if (lane < 1 + MC && nrel > 0) mbar_arrive_cl(bempty + 8 * rs, lane); nrel--; if (++rs == NST) rs = 0; };

#define RISSUE(m, P, XA, XB, BA, BB) { ll_issue<0, 8>(P, pr + (m) * 256, 896); \
      { const uint4 v_ = ldll(fr + X1 + (m) * 256); XA = make_uint2(v_.x, v_.y); XB = make_uint2(v_.z, v_.w); } \
      const uint32_t* bp = (const uint32_t*)(b2 + 128 * (m) + 16 * warp) + (ln_ & 3); BA = __ldg(bp); BB = __ldg(bp + 4); }
#define REDU(m, P, XA, XB, BA, BB) { ll_check<0, 8, false>(P, pr + (m) * 256, 896, ptag); \
      float e[8] = {blo(XA.x) + blo(BA), bhi(XA.x) + bhi(BA), blo(XA.y) + blo(BA), bhi(XA.y) + bhi(BA), blo(XB.x) + blo(BB), bhi(XB.x) + bhi(BB), blo(XB.y) + blo(BB), bhi(XB.y) + bhi(BB)}; \
      _Pragma("unroll") for (int i = 0; i < 8; i++) { e[0] += blo(P[i].x); e[1] += bhi(P[i].x); e[2] += blo(P[i].y); e[3] += bhi(P[i].y); \
        e[4] += blo(P[i].z); e[5] += bhi(P[i].z); e[6] += blo(P[i].w); e[7] += bhi(P[i].w); } \
      xw[m][0] = pack(e[0], e[1]); xw[m][1] = pack(e[2], e[3]); xw[m][2] = pack(e[4], e[5]); xw[m][3] = pack(e[6], e[7]); }
#define RPUB(m) stll(fr + XR + (m) * 256, tg(xw[m][0], 0), xw[m][1], xw[m][2], xw[m][3]);
#define RLAST(ptag_, hv) { const uint32_t ptag = ptag_; const uint4* pr = g_P + ((t * 8 + c) * 8 * 28 + warp) * 32 + ln_; uint4 p[8]; uint2 xa, xb; uint32_t ba, bb; \
      hint_wait(g_H + (t * 8 + c) * 8 + (ln_ & 7), hv); RISSUE(3, p, xa, xb, ba, bb) REDU(3, p, xa, xb, ba, bb) }
#pragma unroll 1
  for (int L = 0; L < 2; L++) {
    const uint32_t tag = 1 - L;
    uint32_t phq[2][2][7];
    const uint32_t hs = 10 * L;
    {
      PTRS
      uint4 a[28];
      const uint4* pa = fm + XR;
      uint32_t fa = 0, fb = 0;
      float r0 = 1.f, r1 = 1.f;
      if (L == 0) {
        hint_post(hme, 1, lane);
        mbar_wait(bempty + 8 * NST, 0);
        MARK(1);
        const int row = warp * 16 + (ln_ & 15);
        const uint32_t xb = sb + 2 * STAGE + row * 128;
        float cs_[4][4] = {};
#pragma unroll
        for (int ks = 0; ks < 28; ks++) { a[ks] = ldsm4(xb + (ks >> 2) * 16384 + (((2 * (ks & 3) + (ln_ >> 4)) ^ (row & 7)) << 4)); mma16816(cs_[ks & 3], a[ks], 0x3F803F80u, 0x3F803F80u); }
        if (c < 7) {
#pragma unroll
          for (int u = 0; u < 4; u++) { const uint4 v = ldsm4(xb + c * 16384 + (((2 * u + (ln_ >> 4)) ^ (row & 7)) << 4)); stll(fm + XR + 128 * c + u * 32, tg(v.x, tag), v.y, v.z, v.w); }
        }
        const float m0 = ((cs_[0][0] + cs_[1][0]) + (cs_[2][0] + cs_[3][0])) * (1.f / 448), m1 = ((cs_[0][2] + cs_[1][2]) + (cs_[2][2] + cs_[3][2])) * (1.f / 448);
        const uint32_t mb0 = pack(m0, m0), mb1 = pack(m1, m1);
        asm volatile("bar.arrive 2, 288;" ::"r"(mb0) : "memory");
#pragma unroll
        for (int ks = 0; ks < 28; ks++) {
          a[ks].x = bsub(a[ks].x, mb0); a[ks].y = bsub(a[ks].y, mb1); a[ks].z = bsub(a[ks].z, mb0); a[ks].w = bsub(a[ks].w, mb1);
        }
        r0 = m0 - blo(mb0); r1 = m1 - blo(mb1);
      } else {
        ll_issue<0, 14>(a, pa, 32);
        if (wg == 0) { RLAST(1u, 10u) xw[3][0] = tg(xw[3][0], 0); RPUB(3) } else { xw[3][0] = xw[3][1] = xw[3][2] = xw[3][3] = 0; }
        MARK(20);
        ll_issue<14, 7>(a, pa, 32);
        ln_stats(xw, sLN, warp, lane, g_S2 + (t * 8 + c) * 8);
      }
      MARK(2 + L * 19);
      float ak[28], av[28], aq[28], pp[28];
#define KVSTAGE(i) { if (L) ll_check<7 * i, 7, false>(a, pa, 32, tag); const uint32_t st = acquire(); wg_fence(); \
      _Pragma("unroll") for (int ks = 0; ks < 7; ks++) { const uint4 f = a[7 * i + ks]; \
        wgmma_rs56(ak, f.x, f.y, f.z, f.w, mkdesc(st, ks * 2048, 1024, 1024, 1), i | ks); \
        wgmma_rs56(av, f.x, f.y, f.z, f.w, mkdesc(st, 14336 + ks * 2048, 1024, 1024, 1), i | ks); } \
      wg_commit(); if (i > 0) { wg_wait<1>(); release(); } }
      KVSTAGE(0) KVSTAGE(1)
      uint4 sv[1];
      const uint4* ps = g_S2 + (t * 8 + warp) * 8 + (ln_ >> 2);
      if (L) { ll_issue<21, 7>(a, pa, 32); ll_issue<0, 1>(sv, ps, 0); }
      KVSTAGE(2) KVSTAGE(3)
      if (L) {
        ll_check<0, 1, false>(sv, ps, 0, 1u);
        const float m0 = -__uint_as_float(sv[0].x), m1 = -__uint_as_float(sv[0].z), h0 = blo(pack(m0, 0.f)), h1 = blo(pack(m1, 0.f));
        r0 = __uint_as_float(sv[0].y); r1 = __uint_as_float(sv[0].w);
        fa = q == 2 ? pack(0.f, h0) : q == 3 ? pack(m0 - h0, h0) : 0u; fb = q == 2 ? pack(0.f, h1) : q == 3 ? pack(m1 - h1, h1) : 0u;
      } else {
        float c0[2][4] = {}, c1[2][4] = {};
#pragma unroll
        for (int ks = 0; ks < 28; ks++) { mma16816(c0[ks & 1], a[ks], a[ks].x, a[ks].z); mma16816(c1[ks & 1], a[ks], a[ks].y, a[ks].w); }
        const int src = (ln_ & 28) | (g >> 1);
        const float q0 = __shfl_sync(~0u, (g & 1) ? c0[0][1] + c0[1][1] : c0[0][0] + c0[1][0], src), q1 = __shfl_sync(~0u, (g & 1) ? c1[0][3] + c1[1][3] : c1[0][2] + c1[1][2], src);
        r0 = rsqrtf(fmaxf(q0 * (1.f / 448) - r0 * r0, 0.f) + 1e-5f); r1 = rsqrtf(fmaxf(q1 * (1.f / 448) - r1 * r1, 0.f) + 1e-5f);
        asm volatile("bar.sync 3, 320;" ::: "memory");
      }
      wg_fence();
      wgmma_rs56(ak, fa, fb, 0u, 0u, mkdesc(d16, OFF_CB + 1024, 512, 0, 2), 1);
      wgmma_rs56(av, fa, fb, 0u, 0u, mkdesc(d16, OFF_CB + 2048, 512, 0, 2), 1);
      wg_commit();
      wg_wait<0>(); release(); regfence(ak); regfence(av);
      MARK(3 + L * 19);
      phi_gemm(ak, pp, d16 + (OFF_WPHI >> 4), r0, r1);
#pragma unroll
      for (int j = 0; j < 7; j++) {
        const int n = 8 * j + 2 * q, n2 = n < 28 ? n : n + 4;
        sts32(sV + sw128(row0, n2), pack(av[4 * j] * r0, av[4 * j + 1] * r0)); sts32(sV + sw128(row0 + 8, n2), pack(av[4 * j + 2] * r1, av[4 * j + 3] * r1));
      }
      { const int n2 = 28 + 2 * (q & 1) + 32 * (q >> 1); const uint32_t v = (q & 1) ? 0u : 0x3F80u; sts32(sV + sw128(row0, n2), v); sts32(sV + sw128(row0 + 8, n2), v); }
      wg_wait<0>(); regfence(pp);
      hedgehog(pp, [&](int r, int h, int p, uint32_t v) { sts32(sPK + h * 16384 + sw128(row0 + 8 * r, 8 * p + 2 * q), v); }, [] {});
      fence_async();
      bar_cons();
      MARK(4 + L * 19);
      float kv[16];
      wg_fence();
#pragma unroll
      for (int ks = 0; ks < 8; ks++) wgmma_ss32(kv, mkdesc(d16 + wg * 1024, OFF_PHIK + ks * 2048, 1024, 1024, 1), mkdesc(d16 + wg * 4, OFF_V + ks * 2048, 1024, 1024, 1), ks);
      wg_commit(); wg_wait<0>(); regfence(kv);
      const int ln2 = laneid();
#pragma unroll
      for (int u = 0; u < 4; u++) {
        float e[4];
#pragma unroll
        for (int i = 0; i < 4; i++) e[i] = kv[4 * u + i];
        stll(g_KVP + (c * 16 + t) * 1024 + wg * 512 + u * 128 + (warp & 3) * 32 + ln2, tg(__float_as_uint(e[0]), tag), __float_as_uint(e[1]), __float_as_uint(e[2]), __float_as_uint(e[3]));
      }
      MARK(5 + L * 19);
      uint4 k4[4];
      const uint4* pk = g_KVP + (c * 16 + 4 * (ln2 & 3)) * 1024 + 64 * t + warp * 8 + (ln2 >> 2);
#pragma unroll
      for (int i = 0; i < 2; i++) {
        const uint32_t st = acquire(); wg_fence();
#pragma unroll
        for (int ks = 0; ks < 14; ks++) { const uint4 f = a[14 * i + ks]; wgmma_rs56(aq, f.x, f.y, f.z, f.w, mkdesc(st, ks * 2048, 1024, 1024, 1), i | ks); }
        if (i == 1) wgmma_rs56(aq, fa, fb, 0u, 0u, mkdesc(d16, OFF_CB, 512, 0, 2), 1);
        wg_commit();
        if (i == HOP) ll_issue<0, 4>(k4, pk, 1024);
      }
      ll_check<0, 4, false>(k4, pk, 1024, tag);
      float s0 = 0, s1 = 0, s2 = 0, s3 = 0;
#pragma unroll
      for (int i = 0; i < 4; i++) { s0 += __uint_as_float(k4[i].x); s1 += __uint_as_float(k4[i].y); s2 += __uint_as_float(k4[i].z); s3 += __uint_as_float(k4[i].w); }
      s0 = qsum(s0); s1 = qsum(s1); s2 = qsum(s2); s3 = qsum(s3);
      if (q == 0) stll2(g_KVR + c * 1024 + 64 * t + warp * 8 + (ln2 >> 2), tg(pack(s0, s1), tag), pack(s2, s3));
      MARK(6 + L * 19);
      wg_wait<0>(); release(); release(); regfence(aq);
      phi_gemm(aq, pp, d16 + (OFF_WPHI >> 4), r0, r1);
      bar_cons();
#pragma unroll
      for (int i = 0; i < 4; i++) sts128(sV + warp * 2048 + (lane + i * 32) * 16, 0, 0, 0, 0);
      wg_wait<0>(); regfence(pp);
      uint2 r[4];
      const uint2* pr = g_KVR + c * 1024 + wg * 512 + (warp & 3) * 32 + ln2;
      hedgehog(pp, [&](int r, int h, int p, uint32_t v) { phq[r][h][p] = v; }, [&] {
#pragma unroll
        for (int u = 0; u < 4; u++) r[u] = ldll2(pr + u * 128); });
      MARK(7 + L * 19);
#pragma unroll 1
      for (int it = 0; it < SPIN; it++) {
        if (!__any_sync(~0u, ((r[0].x ^ tag) | (r[1].x ^ tag) | (r[2].x ^ tag) | (r[3].x ^ tag)) & 1)) break;
#pragma unroll
        for (int u = 0; u < 4; u++) r[u] = ldll2(pr + u * 128);
      }
#pragma unroll
      for (int u = 0; u < 4; u++) {
        const int d = 8 * u + 2 * q;
        if (d < 28) { sts32(sV + sw128(row0, 28 * wg + d), r[u].x); sts32(sV + sw128(row0 + 8, 28 * wg + d), r[u].y); }
        else if (d == 28) {
#pragma unroll
          for (int j = 0; j < 4; j++) { sts16(sV + sw128(row0, 56 + 2 * j + wg), r[u].x); sts16(sV + sw128(row0 + 8, 56 + 2 * j + wg), r[u].y); }
        }
      }
      fence_async();
      bar_cons();
      MARK(8 + L * 19);
      float o[32];
      wg_fence();
#pragma unroll
      for (int ks = 0; ks < 8; ks++) {
        const int h = ks >> 2, p = 2 * (ks & 3);
        wgmma_rs64(o, phq[0][h][p], phq[1][h][p], p < 6 ? phq[0][h][p < 6 ? p + 1 : 0] : 0u, p < 6 ? phq[1][h][p < 6 ? p + 1 : 0] : 0u, mkdesc(d16, OFF_V + ks * 2048, 1024, 1024, 1), ks);
      }
      wg_commit(); wg_wait<0>(); regfence(o);
      const float iA0 = rcp(o[28] + 1e-6f), iB0 = rcp(o[29] + 1e-6f), iA1 = rcp(o[30] + 1e-6f), iB1 = rcp(o[31] + 1e-6f);
      uint32_t w[14];
      { PTRS
#pragma unroll
      for (int j = 0; j < 7; j++) {
        const bool hb = 8 * j + 2 * q >= 28; const float i0 = hb ? iB0 : iA0, i1 = hb ? iB1 : iA1;
        w[2 * j] = pack(o[4 * j] * i0, o[4 * j + 1] * i0); w[2 * j + 1] = pack(o[4 * j + 2] * i1, o[4 * j + 3] * i1);
        if (j == 0 || ((j ^ c) & 1) == 0) w[2 * j] = tg(w[2 * j], tag);
      }
      slice_store(sf + OO, sh + 2 * OO, w, c & 1);
      hint_post(hme, hs + 2, lane); }
    }
    MARK(9 + L * 19);
    uint4 xr[4];
    if (c < 7) {
      PTRS
      ll_issue<0, 4>(xr, fm + XR + 128 * c, 32);
      uint4 a[28];
      const uint4* pa = fm + OO;
      hint_wait(hrow, hs + 2);
      MARK(10 + L * 19);
      ll_issue<0, 28, true>(a, pa, 32, f2 + 2 * OO);
      float y[32];
      uint32_t st;
#define WOSTEP(i) { ll_check<7 * i, 7, true>(a, pa, 32, tag, f2 + 2 * OO); if (!(i & 1)) st = acquire(); wg_fence(); \
      _Pragma("unroll") for (int ks = 0; ks < 7; ks++) { const uint4 f = a[7 * i + ks]; \
        wgmma_rs64(y, f.x, f.y, f.z, f.w, mkdesc(st, ((i & 1) * 7 + ks) * 2048, 1024, 1024, 1), i | ks); } wg_commit(); }
      WOSTEP(0) WOSTEP(1) WOSTEP(2) WOSTEP(3)
      ll_check<0, 4, false>(xr, fm + XR + 128 * c, 32, tag);
      wg_wait<0>(); regfence(y);
      MARK(11 + L * 19);
#pragma unroll
      for (int u = 0; u < 4; u++) {
        xr[u].x = tg(pack(blo(xr[u].x) + y[8 * u], bhi(xr[u].x) + y[8 * u + 1]), tag); xr[u].y = pack(blo(xr[u].y) + y[8 * u + 2], bhi(xr[u].y) + y[8 * u + 3]);
        xr[u].z = pack(blo(xr[u].z) + y[8 * u + 4], bhi(xr[u].z) + y[8 * u + 5]); xr[u].w = pack(blo(xr[u].w) + y[8 * u + 6], bhi(xr[u].w) + y[8 * u + 7]);
        stll(fm + X1 + 128 * c + u * 32, xr[u].x, xr[u].y, xr[u].z, xr[u].w);
      }
      hint_post(hme, hs + 3, lane);
    } else {
      PTRS
      hint_post(hme, hs + 3, lane);
      acquire(); acquire();
      hint_wait(g_H + (t * 8 + warp) * 8, hs + 3);
      ll_issue<0, 4>(xr, fm + X1, 32); ll_check<0, 4, false>(xr, fm + X1, 32, tag);
      MARK(10 + L * 19); MARK(11 + L * 19);
    }
    uint32_t hf[56];
    float rr0, rr1;
    {
      PTRS
      uint4 a[28];
      const uint4* pa = fm + X1;
      auto grp = [&](int i) -> const uint4* { const int k = i + c; return pa + ((k >= 7 ? k - 7 : k) - i) * 128; };
#pragma unroll
      for (int u = 0; u < 4; u++) a[u] = xr[u];
      float y[112];
#define F1STAGE(i) { if (i > 0) ll_check<4 * i, 4, false>(a, grp(i), 32, tag); const uint32_t st = acquire(); wg_fence(); \
      _Pragma("unroll") for (int ks = 0; ks < 4; ks++) { const uint4 f = a[4 * i + ks]; \
        wgmma_rs224(y, f.x, f.y, f.z, f.w, mkdesc(st, (ks >> 1) * 14336 + (ks & 1) * 1024, 2048, 512, 2), i | ks); } \
      wg_commit(); if (i > 0) { wg_wait<1>(); release(); if (i < 4) ll_issue<(i < 4 ? 4 * i + 12 : 0), 4>(a, grp(i + 3), 32); } }
      F1STAGE(0)
      hint_wait(hrow, hs + 3);
      MARK(12 + L * 19);
      ll_issue<4, 4>(a, grp(1), 32); ll_issue<8, 4>(a, grp(2), 32); ll_issue<12, 4>(a, grp(3), 32);
      if (c < 7) {
        float s0 = 0.f, s1 = 0.f, v0 = 0.f, v1 = 0.f;
#pragma unroll
        for (int u = 0; u < 4; u++) { s0 += (blo(xr[u].x) + bhi(xr[u].x)) + (blo(xr[u].z) + bhi(xr[u].z)); s1 += (blo(xr[u].y) + bhi(xr[u].y)) + (blo(xr[u].w) + bhi(xr[u].w)); }
        s0 = qsum(s0) * (1.f / 64); s1 = qsum(s1) * (1.f / 64);
#pragma unroll
        for (int u = 0; u < 4; u++) {
          const float d0 = blo(xr[u].x) - s0, d1 = bhi(xr[u].x) - s0, d2 = blo(xr[u].z) - s0, d3 = bhi(xr[u].z) - s0;
          const float d4 = blo(xr[u].y) - s1, d5 = bhi(xr[u].y) - s1, d6 = blo(xr[u].w) - s1, d7 = bhi(xr[u].w) - s1;
          v0 += (d0 * d0 + d1 * d1) + (d2 * d2 + d3 * d3); v1 += (d4 * d4 + d5 * d5) + (d6 * d6 + d7 * d7);
        }
        v0 = qsum(v0); v1 = qsum(v1);
        if (q == 0) stll(g_ST + ((t * 8 + warp) * 8 + c) * 8 + (ln_ >> 2), tg(__float_as_uint(s0), tag), __float_as_uint(v0), __float_as_uint(s1), __float_as_uint(v1));
      }
      release(); release();
      F1STAGE(1) MARK(13 + L * 19); F1STAGE(2) F1STAGE(3)
      uint4 sv[2];
      const uint4* ps = g_ST + ((t * 8 + warp) * 8 + 2 * (laneid() & 3)) * 8 + (laneid() >> 2);
      ll_issue<0, 2>(sv, ps, q < 3 ? 8 : 0);
      F1STAGE(4)
      ll_check<0, 2, false>(sv, ps, q < 3 ? 8 : 0, tag);
      const float wb = q < 3 ? 1.f : 0.f;
      const float ma = __uint_as_float(sv[0].x), mb = __uint_as_float(sv[1].x), mc = __uint_as_float(sv[0].z), md = __uint_as_float(sv[1].z);
      const float m0 = qsum(ma + wb * mb) * (1.f / 7), m1 = qsum(mc + wb * md) * (1.f / 7);
      const float v0 = qsum(__uint_as_float(sv[0].y) + 64.f * (ma - m0) * (ma - m0) + wb * (__uint_as_float(sv[1].y) + 64.f * (mb - m0) * (mb - m0)));
      const float v1 = qsum(__uint_as_float(sv[0].w) + 64.f * (mc - m1) * (mc - m1) + wb * (__uint_as_float(sv[1].w) + 64.f * (md - m1) * (md - m1)));
      const float e0 = v0 * (1.f / 448) + 1e-5f, e1 = v1 * (1.f / 448) + 1e-5f;
      rr0 = 1.f / e0; rr1 = 1.f / e1;
      auto fold = [&](float m, float sd) -> uint32_t {
        const float mh = blo(pack(-m, 0.f)), sh_ = blo(pack(sd, 0.f));
        return q == 0 ? pack(mh, -m - mh) : q == 1 ? pack(mh, sh_) : q == 2 ? pack(sd - sh_, 0.f) : 0u;
      };
      const uint32_t fa = fold(m0, sqrtf(e0)), fb = fold(m1, sqrtf(e1));
      if (L == 0) asm volatile("bar.sync 4, 288;" ::: "memory");
      wg_fence();
      wgmma_rs224(y, fa, fb, 0u, 0u, mkdesc(d16, OFF_CB, 512, 0, 2), 1);
      F1STAGE(5) F1STAGE(6)
      wg_wait<0>(); release(); regfence(y);
      MARK(14 + L * 19);
#pragma unroll
      for (int j = 0; j < 56; j++) {
        uint32_t r; asm("cvt.rn.relu.bf16x2.f32 %0, %1, %2;" : "=r"(r) : "f"(y[2 * j + 1]), "f"(y[2 * j]));
        asm("mul.bf16x2 %0, %1, %1;" : "=r"(hf[j]) : "r"(r));
      }
    }
    MARK(15 + L * 19);
    {
      PTRS
      float ya[32], yb[32];
      uint4* pp = g_P + ((t * 8 + warp) * 8 + c) * 28 * 32 + ln_;
#define F2STORE(j, Y) { regfence(Y); _Pragma("unroll") for (int u = 0; u < 4; u++) \
      stll(pp + (4 * (j) + u) * 32, tg(pack(Y[8 * u] * rr0, Y[8 * u + 1] * rr0), tag), pack(Y[8 * u + 2] * rr1, Y[8 * u + 3] * rr1), \
           pack(Y[8 * u + 4] * rr0, Y[8 * u + 5] * rr0), pack(Y[8 * u + 6] * rr1, Y[8 * u + 7] * rr1)); if ((j) >= 5) hint_post(hme, hs + (4 + (j)), lane); }
#define F2PASS(j, Y, Z) { const uint32_t st = acquire(); wg_fence(); \
      _Pragma("unroll") for (int ks = 0; ks < 14; ks++) wgmma_rs64(Y, hf[4 * ks], hf[4 * ks + 1], hf[4 * ks + 2], hf[4 * ks + 3], mkdesc(st, ks * 2048, 1024, 1024, 1), ks); \
      wg_commit(); if (j > 0) { wg_wait<1>(); release(); F2STORE(j - 1, Z) } }
      const uint4* pr = g_P + ((t * 8 + c) * 8 * 28 + warp) * 32 + ln_;
      uint4 p[8], p2[8]; uint2 xa, xb, xc, xd; uint32_t ba, bb, bc, bd;
      const uint32_t ptag = tag;
      const uint32_t* hred = g_H + (t * 8 + c) * 8 + (ln_ & 7);
      F2PASS(0, ya, yb) F2PASS(1, yb, ya) F2PASS(2, ya, yb) F2PASS(3, yb, ya)
      F2PASS(4, ya, yb)
      F2PASS(5, yb, ya)
      RISSUE(0, p2, xc, xd, bc, bd)
      F2PASS(6, ya, yb)
      RISSUE(1, p, xa, xb, ba, bb)
      wg_wait<0>(); release(); F2STORE(6, ya)
      MARK(16 + L * 19);
      if (L == 0) asm volatile("bar.sync 8, 288;" ::: "memory");
      REDU(0, p2, xc, xd, bc, bd)
      if (L == 0) { xw[0][0] = tg(xw[0][0], 0); RPUB(0) }
      if (wg) hint_wait(hred, hs + 9);
      RISSUE(2, p2, xc, xd, bc, bd)
      REDU(1, p, xa, xb, ba, bb)
      if (L == 0) { xw[1][0] = tg(xw[1][0], 0); RPUB(1) }
      MARK(17 + L * 19);
      REDU(2, p2, xc, xd, bc, bd)
      if (L == 0) { xw[2][0] = tg(xw[2][0], 0); RPUB(2) }
    }
    MARK(18 + L * 19);
  }
  {
    PTRS
    uint32_t* op = (uint32_t*)(out + XOFF(ln_));
#define OUT(u) { op[u * 64] = xw[u][0]; op[u * 64 + 1792] = xw[u][1]; op[u * 64 + 4] = xw[u][2]; op[u * 64 + 1796] = xw[u][3]; }
    OUT(0) OUT(1) OUT(2)
    if (wg == 0) { RLAST(0u, 20u) OUT(3) }
    else if (warp == 7) {
      if (t == 0 && lane == 0) g_WQF[c] = 0;
      if (lane < 8) stll(g_S2 + (t * 8 + c) * 8 + lane, 0, 0, 0, 0);
      if (lane < 4) { stll(g_CS + blockIdx.x * 4 + lane, 0, 0, 0, 0); if (blockIdx.x < 68) stll(g_CS + 512 + blockIdx.x * 4 + lane, 0, 0, 0, 0); }
    }
  }
  MARK(38); GT(39);
  }
}

typedef CUresult (*EncFn)(CUtensorMap*, CUtensorMapDataType, cuuint32_t, void*, const cuuint64_t*, const cuuint64_t*, const cuuint32_t*, const cuuint32_t*,
                          CUtensorMapInterleave, CUtensorMapSwizzle, CUtensorMapL2promotion, CUtensorMapFloatOOBfill);

extern "C" void kernel_launch(void* const* d_in, const int* in_sizes, int n_in, void* d_out, int out_size) {
  static EncFn enc = nullptr;
  if (!enc) {
    void* fn = nullptr; cudaDriverEntryPointQueryResult qr;
    cudaGetDriverEntryPoint("cuTensorMapEncodeTiled", &fn, cudaEnableDefault, &qr);
    enc = (EncFn)fn;
    cudaFuncSetAttribute(fused_kernel, cudaFuncAttributeMaxDynamicSharedMemorySize, SMEM_BYTES);
  }
  CUtensorMap mQKV, mWO, mW1, mW1b, mW2, mW2b, mX;
  const cuuint32_t es[3] = {1, 1, 1};
  auto enc2 = [&](CUtensorMap* m, void* p, cuuint64_t cols, cuuint64_t rows, cuuint32_t bc, cuuint32_t br) {
    const cuuint64_t dims[2] = {cols, rows}, str[1] = {cols * 2}; const cuuint32_t box[2] = {bc, br};
    enc(m, CU_TENSOR_MAP_DATA_TYPE_BFLOAT16, 2, p, dims, str, box, es, CU_TENSOR_MAP_INTERLEAVE_NONE,
        bc == 64 ? CU_TENSOR_MAP_SWIZZLE_128B : CU_TENSOR_MAP_SWIZZLE_64B, CU_TENSOR_MAP_L2_PROMOTION_L2_128B, CU_TENSOR_MAP_FLOAT_OOB_FILL_NONE);
  };
  enc2(&mQKV, d_in[1], 1344, 448, 64, 112); enc2(&mWO, d_in[3], 448, 448, 64, 112); enc2(&mW1b, d_in[5], 1792, 448, 32, 32);
  enc2(&mX, d_in[0], 448, 2048, 64, 128);
  enc2(&mW2, d_in[7], 448, 1792, 64, 96); enc2(&mW2b, d_in[7], 448, 1792, 64, 16);
  {
    const cuuint64_t dims[3] = {32, 448, 56}, str[2] = {3584, 64}; const cuuint32_t box[3] = {32, 32, 6};
    enc(&mW1, CU_TENSOR_MAP_DATA_TYPE_BFLOAT16, 3, d_in[5], dims, str, box, es, CU_TENSOR_MAP_INTERLEAVE_NONE, CU_TENSOR_MAP_SWIZZLE_64B,
        CU_TENSOR_MAP_L2_PROMOTION_L2_128B, CU_TENSOR_MAP_FLOAT_OOB_FILL_NONE);
  }
  typedef const __nv_bfloat16* BP;
  fused_kernel<<<128, 384, SMEM_BYTES>>>(mQKV, mWO, mW1, mW1b, mW2, mW2b, mX, (BP)d_in[1], (BP)d_in[2], (BP)d_in[3], (BP)d_in[5], (BP)d_in[6], (BP)d_in[7], (BP)d_in[8],
                                         (__nv_bfloat16*)d_out);
}
```

```cpp
#include <cuda_runtime.h>
#include <cuda_bf16.h>
#include <cuda.h>
#include <stdint.h>

constexpr int NST = 6, STAGE = 28672;
constexpr int OFF_PHIK = NST * STAGE;
constexpr int OFF_V = OFF_PHIK + 32768;
constexpr int OFF_WPHI = OFF_V + 16384;
constexpr int OFF_CB = OFF_WPHI + 7168;
constexpr int OFF_BAR = OFF_CB + 3584;
constexpr int SMEM_BYTES = OFF_BAR + 16 * NST + 8;
constexpr int FR = 16 * 8 * 28 * 32;
constexpr int SPIN = 1 << 18;
#define MC 0
#define MAPPING MC
#define MCS
#define MCA(n)
#define CLUSTER
#define LAG 2
#define PACE 2

__device__ uint4 g_F[3 * FR];
constexpr int XR = 0, OO = FR, X1 = 2 * FR;
__device__ uint4 g_P[8 * FR];
__device__ uint4 g_ST[16 * 8 * 8 * 8];
__device__ uint4 g_KVP[8 * 16 * 1024];
__device__ uint2 g_KVR[8 * 1024];
__device__ uint4 g_CS[784];
__device__ uint4 g_S2[16 * 8 * 8];
__device__ uint4 g_WQ[8 * 6 * (STAGE / 16)];
__device__ uint32_t g_WQF[8];
__device__ uint32_t g_H[16 * 8 * 8];
#define MARK(i)
#define GT(i)

__device__ __forceinline__ uint32_t s2u(const void* p) { return (uint32_t)__cvta_generic_to_shared(p); }
__device__ __forceinline__ void mbar_init(uint32_t b, uint32_t c) { asm volatile("mbarrier.init.shared::cta.b64 [%0], %1;" ::"r"(b), "r"(c)); }
__device__ __forceinline__ void mbar_expect(uint32_t b, uint32_t tx) { asm volatile("mbarrier.arrive.expect_tx.shared::cta.b64 _, [%0], %1;" ::"r"(b), "r"(tx) : "memory"); }
__device__ __forceinline__ void mbar_arrive_cl(uint32_t b, uint32_t rank) {
  asm volatile("{.reg .b32 r; mapa.shared::cluster.u32 r, %0, %1; mbarrier.arrive.shared::cluster.b64 _, [r];}" ::"r"(b), "r"(rank) : "memory");
}
__device__ __forceinline__ void mbar_wait(uint32_t b, uint32_t ph) {
  uint32_t ok = 0;
#pragma unroll 1
  for (int it = 0; it < SPIN && !ok; it++)
    asm volatile("{.reg .pred p; mbarrier.try_wait.parity.shared::cta.b64 p,[%1],%2; selp.u32 %0,1,0,p;}" : "=r"(ok) : "r"(b), "r"(ph) : "memory");
}
__device__ __forceinline__ void tma2d(uint32_t dst, const CUtensorMap* m, int c0, int c1, uint32_t bar) {
  asm volatile("cp.async.bulk.tensor.2d.shared::cluster.global.mbarrier::complete_tx::bytes" MCS " [%0], [%1, {%3, %4}], [%2]" MCA(5) ";"
               ::"r"(dst), "l"(m), "r"(bar), "r"(c0), "r"(c1), "h"((uint16_t)3) : "memory");
}
__device__ __forceinline__ void tma3d(uint32_t dst, const CUtensorMap* m, int c0, int c1, int c2, uint32_t bar) {
  asm volatile("cp.async.bulk.tensor.3d.shared::cluster.global.mbarrier::complete_tx::bytes" MCS " [%0], [%1, {%3, %4, %5}], [%2]" MCA(6) ";"
               ::"r"(dst), "l"(m), "r"(bar), "r"(c0), "r"(c1), "r"(c2), "h"((uint16_t)3) : "memory");
}
__device__ __forceinline__ void l2pf(const void* p, uint32_t bytes) { asm volatile("cp.async.bulk.prefetch.L2.global [%0], %1;" ::"l"(p), "r"(bytes) : "memory"); }
__device__ __forceinline__ void wg_fence() { asm volatile("wgmma.fence.sync.aligned;" ::: "memory"); }
__device__ __forceinline__ void wg_commit() { asm volatile("wgmma.commit_group.sync.aligned;" ::: "memory"); }
template <int N> __device__ __forceinline__ void wg_wait() { asm volatile("wgmma.wait_group.sync.aligned %0;" ::"n"(N) : "memory"); }
template <int N> __device__ __forceinline__ void regfence(float (&d)[N]) {
#pragma unroll
  for (int i = 0; i < N; i++) asm volatile("" : "+f"(d[i])::"memory");
}
__device__ __forceinline__ void bar_cons() { asm volatile("bar.sync 1, 256;" ::: "memory"); }
__device__ __forceinline__ void fence_async() { asm volatile("fence.proxy.async.shared::cta;" ::: "memory"); }
struct Desc { uint32_t lo, hi; };
__device__ __forceinline__ Desc mkdesc(uint32_t base16, uint32_t off, uint32_t lbo, uint32_t sbo, uint32_t swz) {
  return Desc{base16 + ((off >> 4) | ((lbo >> 4) << 16)), (sbo >> 4) | (swz << 30)};
}
__device__ __forceinline__ uint4 ldll(const uint4* p) {
  uint4 v; asm volatile("ld.relaxed.gpu.global.v4.u32 {%0,%1,%2,%3}, [%4];" : "=r"(v.x), "=r"(v.y), "=r"(v.z), "=r"(v.w) : "l"(p) : "memory"); return v;
}
__device__ __forceinline__ uint2 ldll2(const uint2* p) {
  uint2 v; asm volatile("ld.relaxed.gpu.global.v2.u32 {%0,%1}, [%2];" : "=r"(v.x), "=r"(v.y) : "l"(p) : "memory"); return v;
}
__device__ __forceinline__ void stll(uint4* p, uint32_t x, uint32_t y, uint32_t z, uint32_t w) {
  asm volatile("st.relaxed.gpu.global.v4.u32 [%0], {%1,%2,%3,%4};" ::"l"(p), "r"(x), "r"(y), "r"(z), "r"(w) : "memory");
}
__device__ __forceinline__ void stll2(void* p, uint32_t x, uint32_t y) {
  asm volatile("st.relaxed.gpu.global.v2.u32 [%0], {%1,%2};" ::"l"(p), "r"(x), "r"(y) : "memory");
}
__device__ __forceinline__ int laneid() { int l; asm volatile("mov.u32 %0, %%laneid;" : "=r"(l)); return l; }
__device__ __forceinline__ uint32_t tg(uint32_t w, uint32_t tag) { return (w & ~1u) | tag; }
__device__ __forceinline__ uint32_t pack(float lo, float hi) {
  uint32_t r; asm("cvt.rn.bf16x2.f32 %0, %1, %2;" : "=r"(r) : "f"(hi), "f"(lo)); return r;
}
__device__ __forceinline__ float blo(uint32_t w) { return __uint_as_float(w << 16); }
__device__ __forceinline__ float bhi(uint32_t w) { return __uint_as_float(w & 0xffff0000u); }
__device__ __forceinline__ float ex2(float x) { float r; asm("ex2.approx.ftz.f32 %0, %1;" : "=f"(r) : "f"(x)); return r; }
__device__ __forceinline__ float rcp(float x) { float r; asm("rcp.approx.ftz.f32 %0, %1;" : "=f"(r) : "f"(x)); return r; }
__device__ __forceinline__ float qsum(float v) { v += __shfl_xor_sync(~0u, v, 1); v += __shfl_xor_sync(~0u, v, 2); return v; }
__device__ __forceinline__ void sts32(uint32_t a, uint32_t v) { asm volatile("st.shared.u32 [%0], %1;" ::"r"(a), "r"(v) : "memory"); }
__device__ __forceinline__ void sts16(uint32_t a, uint32_t v) { asm volatile("st.shared.u16 [%0], %1;" ::"r"(a), "h"((uint16_t)v) : "memory"); }
__device__ __forceinline__ void sts128(uint32_t a, uint32_t x, uint32_t y, uint32_t z, uint32_t w) {
  asm volatile("st.shared.v4.u32 [%0], {%1,%2,%3,%4};" ::"r"(a), "r"(x), "r"(y), "r"(z), "r"(w) : "memory");
}
__device__ __forceinline__ uint32_t sw128(int row, int col) { return row * 128 + ((((col >> 3) ^ row) & 7) << 4) + (col & 7) * 2; }

__device__ __forceinline__ void wgmma_rs56(float (&d)[28], const uint32_t a0, const uint32_t a1, const uint32_t a2, const uint32_t a3, Desc db, int sd) {
  asm volatile("{.reg .pred p; .reg .b64 da, db; setp.ne.b32 p, %33, 0; mov.b64 db, {%32, %34};\n wgmma.mma_async.sync.aligned.m64n56k16.f32.bf16.bf16 {%0,%1,%2,%3,%4,%5,%6,%7,%8,%9,%10,%11,%12,%13,%14,%15,%16,%17,%18,%19,%20,%21,%22,%23,%24,%25,%26,%27}, {%28,%29,%30,%31}, db, p, 1, 1, 1;}"
   : "+f"(d[0]),"+f"(d[1]),"+f"(d[2]),"+f"(d[3]),"+f"(d[4]),"+f"(d[5]),"+f"(d[6]),"+f"(d[7]),"+f"(d[8]),"+f"(d[9]),"+f"(d[10]),"+f"(d[11]),"+f"(d[12]),"+f"(d[13]),"+f"(d[14]),"+f"(d[15]),"+f"(d[16]),"+f"(d[17]),"+f"(d[18]),"+f"(d[19]),"+f"(d[20]),"+f"(d[21]),"+f"(d[22]),"+f"(d[23]),"+f"(d[24]),"+f"(d[25]),"+f"(d[26]),"+f"(d[27])
   : "r"(a0),"r"(a1),"r"(a2),"r"(a3),"r"(db.lo),"r"(sd),"r"(db.hi));
}
__device__ __forceinline__ void wgmma_rs64(float (&d)[32], const uint32_t a0, const uint32_t a1, const uint32_t a2, const uint32_t a3, Desc db, int sd) {
  asm volatile("{.reg .pred p; .reg .b64 da, db; setp.ne.b32 p, %37, 0; mov.b64 db, {%36, %38};\n wgmma.mma_async.sync.aligned.m64n64k16.f32.bf16.bf16 {%0,%1,%2,%3,%4,%5,%6,%7,%8,%9,%10,%11,%12,%13,%14,%15,%16,%17,%18,%19,%20,%21,%22,%23,%24,%25,%26,%27,%28,%29,%30,%31}, {%32,%33,%34,%35}, db, p, 1, 1, 1;}"
   : "+f"(d[0]),"+f"(d[1]),"+f"(d[2]),"+f"(d[3]),"+f"(d[4]),"+f"(d[5]),"+f"(d[6]),"+f"(d[7]),"+f"(d[8]),"+f"(d[9]),"+f"(d[10]),"+f"(d[11]),"+f"(d[12]),"+f"(d[13]),"+f"(d[14]),"+f"(d[15]),"+f"(d[16]),"+f"(d[17]),"+f"(d[18]),"+f"(d[19]),"+f"(d[20]),"+f"(d[21]),"+f"(d[22]),"+f"(d[23]),"+f"(d[24]),"+f"(d[25]),"+f"(d[26]),"+f"(d[27]),"+f"(d[28]),"+f"(d[29]),"+f"(d[30]),"+f"(d[31])
   : "r"(a0),"r"(a1),"r"(a2),"r"(a3),"r"(db.lo),"r"(sd),"r"(db.hi));
}
__device__ __forceinline__ void wgmma_rs192(float (&d)[96], const uint32_t a0, const uint32_t a1, const uint32_t a2, const uint32_t a3, Desc db, int sd) {
  asm volatile("{.reg .pred p; .reg .b64 db; setp.ne.b32 p, %101, 0; mov.b64 db, {%100, %102};\n wgmma.mma_async.sync.aligned.m64n192k16.f32.bf16.bf16 {%0,%1,%2,%3,%4,%5,%6,%7,%8,%9,%10,%11,%12,%13,%14,%15,%16,%17,%18,%19,%20,%21,%22,%23,%24,%25,%26,%27,%28,%29,%30,%31,%32,%33,%34,%35,%36,%37,%38,%39,%40,%41,%42,%43,%44,%45,%46,%47,%48,%49,%50,%51,%52,%53,%54,%55,%56,%57,%58,%59,%60,%61,%62,%63,%64,%65,%66,%67,%68,%69,%70,%71,%72,%73,%74,%75,%76,%77,%78,%79,%80,%81,%82,%83,%84,%85,%86,%87,%88,%89,%90,%91,%92,%93,%94,%95}, {%96,%97,%98,%99}, db, p, 1, 1, 1;}"
   : "+f"(d[0]),"+f"(d[1]),"+f"(d[2]),"+f"(d[3]),"+f"(d[4]),"+f"(d[5]),"+f"(d[6]),"+f"(d[7]),"+f"(d[8]),"+f"(d[9]),"+f"(d[10]),"+f"(d[11]),"+f"(d[12]),"+f"(d[13]),"+f"(d[14]),"+f"(d[15]),"+f"(d[16]),"+f"(d[17]),"+f"(d[18]),"+f"(d[19]),"+f"(d[20]),"+f"(d[21]),"+f"(d[22]),"+f"(d[23]),"+f"(d[24]),"+f"(d[25]),"+f"(d[26]),"+f"(d[27]),"+f"(d[28]),"+f"(d[29]),"+f"(d[30]),"+f"(d[31]),"+f"(d[32]),"+f"(d[33]),"+f"(d[34]),"+f"(d[35]),"+f"(d[36]),"+f"(d[37]),"+f"(d[38]),"+f"(d[39]),"+f"(d[40]),"+f"(d[41]),"+f"(d[42]),"+f"(d[43]),"+f"(d[44]),"+f"(d[45]),"+f"(d[46]),"+f"(d[47]),"+f"(d[48]),"+f"(d[49]),"+f"(d[50]),"+f"(d[51]),"+f"(d[52]),"+f"(d[53]),"+f"(d[54]),"+f"(d[55]),"+f"(d[56]),"+f"(d[57]),"+f"(d[58]),"+f"(d[59]),"+f"(d[60]),"+f"(d[61]),"+f"(d[62]),"+f"(d[63]),"+f"(d[64]),"+f"(d[65]),"+f"(d[66]),"+f"(d[67]),"+f"(d[68]),"+f"(d[69]),"+f"(d[70]),"+f"(d[71]),"+f"(d[72]),"+f"(d[73]),"+f"(d[74]),"+f"(d[75]),"+f"(d[76]),"+f"(d[77]),"+f"(d[78]),"+f"(d[79]),"+f"(d[80]),"+f"(d[81]),"+f"(d[82]),"+f"(d[83]),"+f"(d[84]),"+f"(d[85]),"+f"(d[86]),"+f"(d[87]),"+f"(d[88]),"+f"(d[89]),"+f"(d[90]),"+f"(d[91]),"+f"(d[92]),"+f"(d[93]),"+f"(d[94]),"+f"(d[95])
   : "r"(a0),"r"(a1),"r"(a2),"r"(a3),"r"(db.lo),"r"(sd),"r"(db.hi));
}
__device__ __forceinline__ void wgmma_rs32(float (&d)[16], const uint32_t a0, const uint32_t a1, const uint32_t a2, const uint32_t a3, Desc db, int sd) {
  asm volatile("{.reg .pred p; .reg .b64 db; setp.ne.b32 p, %21, 0; mov.b64 db, {%20, %22};\n wgmma.mma_async.sync.aligned.m64n32k16.f32.bf16.bf16 {%0,%1,%2,%3,%4,%5,%6,%7,%8,%9,%10,%11,%12,%13,%14,%15}, {%16,%17,%18,%19}, db, p, 1, 1, 1;}"
   : "+f"(d[0]),"+f"(d[1]),"+f"(d[2]),"+f"(d[3]),"+f"(d[4]),"+f"(d[5]),"+f"(d[6]),"+f"(d[7]),"+f"(d[8]),"+f"(d[9]),"+f"(d[10]),"+f"(d[11]),"+f"(d[12]),"+f"(d[13]),"+f"(d[14]),"+f"(d[15])
   : "r"(a0),"r"(a1),"r"(a2),"r"(a3),"r"(db.lo),"r"(sd),"r"(db.hi));
}
__device__ __forceinline__ void wgmma_ss32(float (&d)[16], Desc da, Desc db, int sd) {
  asm volatile("{.reg .pred p; .reg .b64 da, db; setp.ne.b32 p, %18, 0; mov.b64 da, {%16, %19}; mov.b64 db, {%17, %19};\n wgmma.mma_async.sync.aligned.m64n32k16.f32.bf16.bf16 {%0,%1,%2,%3,%4,%5,%6,%7,%8,%9,%10,%11,%12,%13,%14,%15}, da, db, p, 1, 1, 1, 1;}"
   : "+f"(d[0]),"+f"(d[1]),"+f"(d[2]),"+f"(d[3]),"+f"(d[4]),"+f"(d[5]),"+f"(d[6]),"+f"(d[7]),"+f"(d[8]),"+f"(d[9]),"+f"(d[10]),"+f"(d[11]),"+f"(d[12]),"+f"(d[13]),"+f"(d[14]),"+f"(d[15])
   : "r"(da.lo),"r"(db.lo),"r"(sd),"r"(db.hi));
}

__device__ __forceinline__ uint4 ldsm4(uint32_t a) {
  uint4 v; asm volatile("ldmatrix.sync.aligned.m8n8.x4.shared.b16 {%0,%1,%2,%3}, [%4];" : "=r"(v.x), "=r"(v.y), "=r"(v.z), "=r"(v.w) : "r"(a) : "memory"); return v;
}
__device__ __forceinline__ void mma16816(float (&d)[4], const uint4& a, uint32_t b0, uint32_t b1) {
  asm("mma.sync.aligned.m16n8k16.row.col.f32.bf16.bf16.f32 {%0,%1,%2,%3}, {%4,%5,%6,%7}, {%8,%9}, {%0,%1,%2,%3};"
      : "+f"(d[0]), "+f"(d[1]), "+f"(d[2]), "+f"(d[3]) : "r"(a.x), "r"(a.y), "r"(a.z), "r"(a.w), "r"(b0), "r"(b1));
}
__device__ __forceinline__ uint32_t bsub(uint32_t a, uint32_t b) { uint32_t r; asm("sub.bf16x2 %0, %1, %2;" : "=r"(r) : "r"(a), "r"(b)); return r; }
__device__ __forceinline__ uint32_t hint_ld(const uint32_t* p) { uint32_t v; asm volatile("ld.relaxed.gpu.global.u32 %0, [%1];" : "=r"(v) : "l"(p) : "memory"); return v; }
template <int S, int N, bool SPL = false, int T> __device__ __forceinline__ void ll_issue(uint4 (&v)[T], const uint4* p, int stride, const uint2* p2 = nullptr) {
#pragma unroll
  for (int i = S; i < S + N; i++) {
    if (SPL && i % 7 == 3) { const uint2 lo = ldll2(p2 + i * 64), hi = ldll2(p2 + i * 64 + 32); v[i] = make_uint4(lo.x, lo.y, hi.x, hi.y); }
    else v[i] = ldll(p + i * stride);
  }
}
template <int S, int N, bool SPL, int T> __device__ __forceinline__ void ll_check(uint4 (&v)[T], const uint4* p, int stride, uint32_t tag, const uint2* p2 = nullptr) {
#pragma unroll 1
  for (int it = 0; it < SPIN; it++) {
    uint32_t bad = 0;
#pragma unroll
    for (int i = S; i < S + N; i++) bad |= (v[i].x ^ tag) | ((SPL && i % 7 == 3) ? (v[i].z ^ tag) : 0u);
    if (!__any_sync(~0u, bad & 1)) break;
    ll_issue<S, N, SPL>(v, p, stride, p2);
  }
}
__device__ __forceinline__ void hint_post(uint32_t* p, uint32_t v, int lane) {
  if (lane == 0) asm volatile("st.relaxed.gpu.global.u32 [%0], %1;" ::"l"(p), "r"(v) : "memory");
}
__device__ __forceinline__ void hint_wait(const uint32_t* p, uint32_t s, uint32_t v = 0xffffu) {
#pragma unroll 1
  for (int it = 0; it < SPIN; it++) {
    if (__all_sync(~0u, v - s < 10u)) break;
    v = hint_ld(p);
  }
}
__device__ __forceinline__ void slice_store(uint4* pf, uint2* ph, const uint32_t (&w)[14], bool odd) {
#pragma unroll
  for (int u = 0; u < 3; u++)
    stll(pf + u * 32, odd ? w[4 * u + 2] : w[4 * u], odd ? w[4 * u + 3] : w[4 * u + 1], odd ? w[4 * u + 4] : w[4 * u + 2], odd ? w[4 * u + 5] : w[4 * u + 3]);
  stll2(ph, odd ? w[0] : w[12], odd ? w[1] : w[13]);
}
template <class F, class M> __device__ __forceinline__ void hedgehog(const float (&d)[28], F sink, M mid) {
  const float L2E = 1.4426950408889634f;
#define HX(G, p) ((p) < 6 ? d[((G) & 1) * 16 + ((p) >> 1) * 4 + ((p) & 1) + ((G) & 2)] : d[12 + (G)])
  float mx[4], mn[4], sp[4], sn[4], ep[4][7], en[4][7];
#pragma unroll
  for (int G = 0; G < 4; G++) {
    mx[G] = mn[G] = HX(G, 0);
#pragma unroll
    for (int p = 1; p < 7; p++) { mx[G] = fmaxf(mx[G], HX(G, p)); mn[G] = fminf(mn[G], HX(G, p)); }
  }
#pragma unroll
  for (int o = 1; o < 4; o <<= 1)
#pragma unroll
    for (int G = 0; G < 4; G++) { mx[G] = fmaxf(mx[G], __shfl_xor_sync(~0u, mx[G], o)); mn[G] = fminf(mn[G], __shfl_xor_sync(~0u, mn[G], o)); }
#pragma unroll
  for (int G = 0; G < 4; G++) {
    const float a = -mx[G] * L2E, b = mn[G] * L2E;
#pragma unroll
    for (int p = 0; p < 7; p++) { ep[G][p] = ex2(fmaf(HX(G, p), L2E, a)); en[G][p] = ex2(fmaf(HX(G, p), -L2E, b)); }
    sp[G] = ((ep[G][0] + ep[G][1]) + (ep[G][2] + ep[G][3])) + ((ep[G][4] + ep[G][5]) + ep[G][6]);
    sn[G] = ((en[G][0] + en[G][1]) + (en[G][2] + en[G][3])) + ((en[G][4] + en[G][5]) + en[G][6]);
    if (G == 1) mid();
  }
#pragma unroll
  for (int o = 1; o < 4; o <<= 1)
#pragma unroll
    for (int G = 0; G < 4; G++) { sp[G] += __shfl_xor_sync(~0u, sp[G], o); sn[G] += __shfl_xor_sync(~0u, sn[G], o); }
#pragma unroll
  for (int G = 0; G < 4; G++) {
    const float a = rcp(sp[G]), b = rcp(sn[G]);
#pragma unroll
    for (int p = 0; p < 7; p++) sink(G >> 1, G & 1, p, pack(ep[G][p] * a, en[G][p] * b));
  }
}
__device__ __forceinline__ void phi_gemm(const float (&x)[28], float (&y)[28], uint32_t wphi, float r0, float r1) {
  uint32_t f[14];
#pragma unroll
  for (int j = 0; j < 14; j++) f[j] = pack(x[2 * j] * (j & 1 ? r1 : r0), x[2 * j + 1] * (j & 1 ? r1 : r0));
  wg_fence();
#pragma unroll
  for (int ks = 0; ks < 3; ks++) wgmma_rs56(y, f[4 * ks], f[4 * ks + 1], f[4 * ks + 2], f[4 * ks + 3], mkdesc(wphi, ks * 2048, 1024, 1024, 1), ks);
  wgmma_rs56(y, f[12], f[13], 0u, 0u, mkdesc(wphi, 3 * 2048, 1024, 1024, 1), 1);
  wg_commit();
}
__device__ __forceinline__ void ln_stats(uint32_t (&xw)[4][4], float* sLN, int warp, int lane, uint4* dst) {
  const int g = lane >> 2; const bool full = warp < 4;
  float s0 = 0.f, s1 = 0.f;
#pragma unroll
  for (int u = 0; u < 4; u++) {
    s0 += (blo(xw[u][0]) + bhi(xw[u][0])) + (blo(xw[u][2]) + bhi(xw[u][2]));
    s1 += (blo(xw[u][1]) + bhi(xw[u][1])) + (blo(xw[u][3]) + bhi(xw[u][3]));
  }
  const float rc = full ? 1.f / 64 : 1.f / 48;
  s0 = qsum(s0); s1 = qsum(s1);
  const float a0 = s0 * rc, a1 = s1 * rc;
  float v0 = 0.f, v1 = 0.f;
#pragma unroll
  for (int u = 0; u < 4; u++)
    if (u < 3 || full) {
#pragma unroll
      for (int k = 0; k < 4; k += 2) {
        float a = blo(xw[u][k]) - a0, b = bhi(xw[u][k]) - a0, c2 = blo(xw[u][k + 1]) - a1, d2 = bhi(xw[u][k + 1]) - a1;
        v0 += a * a + b * b; v1 += c2 * c2 + d2 * d2;
      }
    }
  v0 = qsum(v0); v1 = qsum(v1);
  if ((lane & 3) == 0) *(float4*)(sLN + (g * 8 + warp) * 4) = make_float4(s0, v0, s1, v1);
  if (warp) { asm volatile("bar.arrive 7, 256;" ::: "memory"); return; }
  asm volatile("bar.sync 7, 256;" ::: "memory");
  const float4 ea = *(const float4*)(sLN + (g * 8 + (lane & 3)) * 4), eb = *(const float4*)(sLN + (g * 8 + 4 + (lane & 3)) * 4);
  const float m0 = qsum(ea.x + eb.x) * (1.f / 448), m1 = qsum(ea.z + eb.z) * (1.f / 448);
  const float d0 = ea.x * (1.f / 64) - m0, d1 = eb.x * (1.f / 48) - m0, d2 = ea.z * (1.f / 64) - m1, d3 = eb.z * (1.f / 48) - m1;
  v0 = qsum(ea.y + eb.y + 64.f * d0 * d0 + 48.f * d1 * d1); v1 = qsum(ea.w + eb.w + 64.f * d2 * d2 + 48.f * d3 * d3);
  if ((lane & 3) == 0) stll(dst + g, tg(__float_as_uint(m0), 1), __float_as_uint(rsqrtf(v0 * (1.f / 448) + 1e-5f)), __float_as_uint(m1), __float_as_uint(rsqrtf(v1 * (1.f / 448) + 1e-5f)));
}

__global__ void CLUSTER __launch_bounds__(384, 1)
fused_kernel(const __grid_constant__ CUtensorMap mQKV, const __grid_constant__ CUtensorMap mWO, const __grid_constant__ CUtensorMap mW1,
             const __grid_constant__ CUtensorMap mW1b, const __grid_constant__ CUtensorMap mW2, const __grid_constant__ CUtensorMap mW2b,
             const __grid_constant__ CUtensorMap mX, const __nv_bfloat16* __restrict__ wqkv, const __nv_bfloat16* __restrict__ wphi,
             const __nv_bfloat16* __restrict__ wo, const __nv_bfloat16* __restrict__ w1, const __nv_bfloat16* __restrict__ b1,
             const __nv_bfloat16* __restrict__ w2, const __nv_bfloat16* __restrict__ b2, __nv_bfloat16* __restrict__ out) {
  extern __shared__ __align__(1024) uint8_t sm[];
  const uint32_t sb = s2u(sm);
  const int tid = threadIdx.x, warp = __shfl_sync(~0u, tid >> 5, 0), lane = tid & 31,
            t = MAPPING ? (blockIdx.x >> 4) * 2 + (blockIdx.x & 1) : blockIdx.x >> 3, c = MAPPING ? (blockIdx.x >> 1) & 7 : blockIdx.x & 7;
  const uint32_t bfull = sb + OFF_BAR, bempty = bfull + 8 * NST;

#define XOFF(l) ((t * 128 + c * 16 + ((l) >> 2)) * 448 + warp * 16 + 2 * ((l) & 3))
  if (warp < 8) { MARK(0); GT(19); }
  if (tid == 256) {
    for (int s = 0; s < NST; s++) { mbar_init(bfull + 8 * s, 1); mbar_init(bempty + 8 * s, MC ? 16 : 8); }
    mbar_init(bempty + 8 * NST, 1);
    asm volatile("fence.mbarrier_init.release.cluster;" ::: "memory");
    fence_async();
    mbar_expect(bempty + 8 * NST, 114688);
    for (int i = 0; i < 7; i++)
      asm volatile("cp.async.bulk.tensor.2d.shared::cluster.global.mbarrier::complete_tx::bytes [%0], [%1, {%3, %4}], [%2];"
                   ::"r"(sb + 2 * STAGE + i * 16384), "l"(&mX), "r"(bempty + 8 * NST), "r"(64 * i), "r"(128 * t) : "memory");
  }
  asm volatile("barrier.cluster.arrive.release.aligned; barrier.cluster.wait.acquire.aligned;" ::: "memory");
  if (warp >= 8) {
    asm volatile("setmaxnreg.dec.sync.aligned.u32 24;");
    auto issue = [&](int i, int s) {
      const uint32_t dst = sb + s * STAGE, bar = bfull + 8 * s;
      mbar_expect(bar, STAGE);
#pragma unroll 1
      for (int rk = MC ? (blockIdx.x & 1) : 0; rk < (MC ? (blockIdx.x & 1) + 1 : 2); rk++)
      if (i < 4) tma2d(dst + rk * 14336, &mQKV, 448 + 448 * rk + 56 * c, 112 * i, bar);
      else if (i < 8) tma2d(dst + rk * 14336, i < 6 ? &mQKV : &mWO, (i < 6 ? 56 : 64) * c, 224 * (i & 1) + 112 * rk, bar);
      else if (i < 15) { const int k0 = 64 * ((i - 8 + c) % 7) + 32 * rk;
        tma3d(dst + rk * 12288, &mW1, 0, k0, 3 * c, bar); tma2d(dst + 24576 + rk * 2048, &mW1b, 1536 + 32 * c, k0, bar); }
      else { tma2d(dst + rk * 12288, &mW2, 64 * (i - 15), 192 * c + 96 * rk, bar); tma2d(dst + 24576 + rk * 2048, &mW2b, 64 * (i - 15), 1536 + 32 * c + 16 * rk, bar); }
    };
    auto colsum = [&](int job) {
        const int ld4 = job < 112 ? 448 : 336;
        const uint2* wp = (job < 112 ? (const uint2*)w1 + job * 4 : (const uint2*)wqkv + (job - 112) * 4) + (lane >> 2) * ld4 + (lane & 3);
        float s0 = 0.f, s1 = 0.f, s2 = 0.f, s3 = 0.f;
#pragma unroll 8
        for (int i = 0; i < 56; i++) { const uint2 v = __ldg(wp + i * 8 * ld4); s0 += blo(v.x); s1 += bhi(v.x); s2 += blo(v.y); s3 += bhi(v.y); }
#pragma unroll 1
        for (int o = 4; o < 32; o <<= 1) { s0 += __shfl_xor_sync(~0u, s0, o); s1 += __shfl_xor_sync(~0u, s1, o); s2 += __shfl_xor_sync(~0u, s2, o); s3 += __shfl_xor_sync(~0u, s3, o); }
        if (lane < 4) stll(g_CS + job * 4 + lane, tg(__float_as_uint(s0), 1), __float_as_uint(s1), __float_as_uint(s2), __float_as_uint(s3));
      };
    if (warp == 8) {
      int s = 0; uint32_t ph = 1;
      for (int n = 0; n < 44; n++) {
        if (n == PACE) asm volatile("bar.sync 2, 288;" ::: "memory");
        mbar_wait(bempty + 8 * s, ph);
        if (n == 22) {
          uint32_t v = 0;
#pragma unroll 1
          for (int it = 0; it < SPIN && v < 32; it++) asm volatile("ld.acquire.gpu.global.u32 %0, [%1];" : "=r"(v) : "l"(g_WQF + c) : "memory");
          asm volatile("fence.proxy.async.global;" ::: "memory");
        }
        if (lane == 0) {
          if (n >= 22 && n < 28) {
            mbar_expect(bfull + 8 * s, STAGE);
            asm volatile("cp.async.bulk.shared::cluster.global.mbarrier::complete_tx::bytes [%0], [%1], %2, [%3];"
                         ::"r"(sb + s * STAGE), "l"(g_WQ + c * 10752 + (n - 22) * (STAGE / 16)), "r"(STAGE), "r"(bfull + 8 * s) : "memory");
          } else issue(n >= 22 ? n - 22 : n, s);
        }
        __syncwarp();
        if (++s == NST) { s = 0; ph ^= 1; }
      }
    } else if (warp == 9) {
      mbar_wait(bfull + 8 * 3, 0);
      if (lane == 0) {
        l2pf((const uint8_t*)wo + blockIdx.x * 3136, 3136);
        l2pf((const uint8_t*)w1 + blockIdx.x * 12544, 12544);
        l2pf((const uint8_t*)w2 + blockIdx.x * 12544, 12544);
      }
      if (blockIdx.x < 112) colsum(blockIdx.x);
      asm volatile("bar.sync 6, 96;" ::: "memory");
#pragma unroll 1
      for (int i = 0; i < 4; i++) {
        const int e = lane < 28 ? lane + 28 * (i & 1) : 0;
        const bool ok = i < 2 || (e < 48 && (e & 15) < 14);
        const int e4 = i < 2 ? (e < 48 ? 48 * c + e : 336 + 8 * c + e) : ok ? 448 + 112 * (e >> 4) + 14 * c + (e & 15) : 448;
        uint4 cv[1];
        ll_issue<0, 1>(cv, g_CS + e4, 0); ll_check<0, 1, false>(cv, g_CS + e4, 0, 1u);
        const uint2 bb = __ldg((const uint2*)b1 + (i < 2 ? e4 : 0));
        const uint32_t h0 = pack(__uint_as_float(cv[0].x), __uint_as_float(cv[0].y)), h1 = pack(__uint_as_float(cv[0].z), __uint_as_float(cv[0].w));
        const uint32_t l0 = pack(__uint_as_float(cv[0].x) - blo(h0), __uint_as_float(cv[0].y) - bhi(h0)), l1 = pack(__uint_as_float(cv[0].z) - blo(h1), __uint_as_float(cv[0].w) - bhi(h1));
#pragma unroll 1
        for (int j = 0; j < (i < 2 ? 5 : 3); j++) {
          const int r = i < 2 ? j : j + 5;
          const uint32_t ad = sb + OFF_CB + (e >> 3) * 512 + r * 64 + ((((e >> 1) ^ (r >> 1)) & 3) << 4) + (e & 1) * 8;
          sts32(ad, j < 2 ? h0 : j == 2 ? l0 : bb.x); sts32(ad + 4, j < 2 ? h1 : j == 2 ? l1 : bb.y);
        }
        if (i & 1) { fence_async(); if (i == 1) asm volatile("bar.arrive 4, 288;" ::: "memory"); else asm volatile("bar.arrive 8, 288;" ::: "memory"); }
      }
    } else if (warp >= 10) {
      const int h = warp - 10;
      uint32_t wv[13];
#pragma unroll
      for (int i = 0; i < 13; i++) { const int e = lane + 32 * i; wv[i] = e < 392 ? __ldg((const uint32_t*)wphi + (2 * c + h) * 392 + e) : 0u; }
#pragma unroll 1
      for (int e = h * 32 + lane; e < 672; e += 64) sts128(sb + OFF_WPHI + e * 16, 0, 0, 0, 0);
      asm volatile("bar.arrive 6, 96;" ::: "memory");
#pragma unroll 1
      for (int i = 0; i < 4; i++) sts128(sb + OFF_PHIK + sw128(h * 128 + i * 32 + lane, 56), 0, 0, 0, 0);
      asm volatile("bar.sync 5, 64;" ::: "memory");
#pragma unroll
      for (int i = 0; i < 13; i++) {
        const int e = lane + 32 * i, d = e / 14, f2 = 2 * (e - 14 * d), k = 28 * h + d;
        if (e < 392) {
          if (f2 < 24) sts32(sb + OFF_WPHI + sw128(k, 32 * h + f2), wv[i]);
          else { sts16(sb + OFF_WPHI + sw128(k, 2 * f2 - 24 + h), wv[i]); sts16(sb + OFF_WPHI + sw128(k, 2 * f2 - 22 + h), wv[i] >> 16); }
        }
      }
      fence_async();
      asm volatile("bar.arrive 3, 320;" ::: "memory");
      mbar_wait(bfull + 8 * 5, 0);
#pragma unroll 2
      for (int e = t * 672 + h * 32 + lane; e < t * 672 + 672; e += 64) {
        const int r = e >> 3, st = r / 224, rr = r - st * 224, ch = (e & 7) ^ (rr & 7);
        const int k = st < 4 ? 112 * st + (rr >= 112 ? rr - 112 : rr) : 224 * (st - 4) + rr, col = (st < 4 ? (rr >= 112 ? 896 : 448) : 0) + 56 * c + 8 * ch;
        g_WQ[c * 10752 + e] = ch < 7 ? __ldg((const uint4*)(wqkv + k * 1344 + col)) : make_uint4(0, 0, 0, 0);
      }
      __syncwarp();
      if (lane == 0) asm volatile("red.release.gpu.global.add.u32 [%0], 1;" ::"l"(g_WQF + c) : "memory");
      if (h == 0 && blockIdx.x < 84) colsum(112 + blockIdx.x);
    }
  } else {
  asm volatile("setmaxnreg.inc.sync.aligned.u32 240;");

  const int wg = warp >> 2, g = lane >> 2, q = lane & 3;
  const int row0 = warp * 16 + g;
#define PTRS const int ln_ = laneid(); \
  uint4* const fm = g_F + ((t * 8 + warp) * 28) * 32 + ln_;            \
  uint4* const fr = g_F + ((t * 8 + c) * 28 + warp) * 32 + ln_;        \
  uint4* const sf = fm + (7 * (c >> 1) + 4 * (c & 1)) * 32;             \
  uint2* const f2 = (uint2*)(fm - ln_) + ln_;                           \
  uint2* const sh = f2 + (7 * (c >> 1) + 3) * 64 + 32 * (c & 1);        \
  uint32_t* const hme = g_H + (t * 8 + warp) * 8 + c; \
  const uint32_t* const hrow = g_H + (t * 8 + warp) * 8 + (ln_ & 7); \
  (void)fm; (void)fr; (void)sf; (void)f2; (void)sh; (void)hme; (void)hrow;
  float* sLN = (float*)(sm + OFF_V);
  const uint32_t sPK = sb + OFF_PHIK, sV = sb + OFF_V, d16 = (sb & 0x3FFFF) >> 4;
    uint32_t xw[4][4];
#pragma unroll
  for (int i = 0; i < 16; i++) xw[i >> 2][i & 3] = 0;
  int cs = 0, rs = 0; uint32_t cph = 0;
  auto acquire = [&]() -> uint32_t { mbar_wait(bfull + 8 * cs, cph); const uint32_t a = d16 + cs * (STAGE >> 4); if (++cs == NST) { cs = 0; cph ^= 1; } return a; };
  int nrel = 44 - NST;
  auto release = [&]() { if (lane < 1 + MC && nrel > 0) mbar_arrive_cl(bempty + 8 * rs, lane); nrel--; if (++rs == NST) rs = 0; };

#define RISSUE(m, P, XA, XB, BA, BB) { ll_issue<0, 8>(P, pr + (m) * 256, 896); \
      { const uint4 v_ = ldll(fr + X1 + (m) * 256); XA = make_uint2(v_.x, v_.y); XB = make_uint2(v_.z, v_.w); } \
      const uint32_t* bp = (const uint32_t*)(b2 + 128 * (m) + 16 * warp) + (ln_ & 3); BA = __ldg(bp); BB = __ldg(bp + 4); }
#define REDU(m, P, XA, XB, BA, BB) { ll_check<0, 8, false>(P, pr + (m) * 256, 896, ptag); \
      float e[8] = {blo(XA.x) + blo(BA), bhi(XA.x) + bhi(BA), blo(XA.y) + blo(BA), bhi(XA.y) + bhi(BA), blo(XB.x) + blo(BB), bhi(XB.x) + bhi(BB), blo(XB.y) + blo(BB), bhi(XB.y) + bhi(BB)}; \
      _Pragma("unroll") for (int i = 0; i < 8; i++) { e[0] += blo(P[i].x); e[1] += bhi(P[i].x); e[2] += blo(P[i].y); e[3] += bhi(P[i].y); \
        e[4] += blo(P[i].z); e[5] += bhi(P[i].z); e[6] += blo(P[i].w); e[7] += bhi(P[i].w); } \
      xw[m][0] = pack(e[0], e[1]); xw[m][1] = pack(e[2], e[3]); xw[m][2] = pack(e[4], e[5]); xw[m][3] = pack(e[6], e[7]); }
#define RPUB(m) stll(fr + XR + (m) * 256, tg(xw[m][0], 0), xw[m][1], xw[m][2], xw[m][3]);
#define RLAST(ptag_, hv) { const uint32_t ptag = ptag_; const uint4* pr = g_P + ((t * 8 + c) * 8 * 28 + warp) * 32 + ln_; uint4 p[8]; uint2 xa, xb; uint32_t ba, bb; \
      hint_wait(g_H + (t * 8 + c) * 8 + (ln_ & 7), hv); RISSUE(3, p, xa, xb, ba, bb) REDU(3, p, xa, xb, ba, bb) }
#pragma unroll 1
  for (int L = 0; L < 2; L++) {
    const uint32_t tag = 1 - L;
    uint32_t phq[2][2][7];
    const uint32_t hs = 10 * L;
    {
      PTRS
      uint4 a[28];
      const uint4* pa = fm + XR;
      uint32_t fa = 0, fb = 0;
      float r0 = 1.f, r1 = 1.f;
      if (L == 0) {
        hint_post(hme, 1, lane);
        mbar_wait(bempty + 8 * NST, 0);
        MARK(1);
        const int row = warp * 16 + (ln_ & 15);
        const uint32_t xb = sb + 2 * STAGE + row * 128;
        float cs_[4][4] = {};
#pragma unroll
        for (int ks = 0; ks < 28; ks++) { a[ks] = ldsm4(xb + (ks >> 2) * 16384 + (((2 * (ks & 3) + (ln_ >> 4)) ^ (row & 7)) << 4)); mma16816(cs_[ks & 3], a[ks], 0x3F803F80u, 0x3F803F80u); }
        if (c < 7) {
#pragma unroll
          for (int u = 0; u < 4; u++) { const uint4 v = ldsm4(xb + c * 16384 + (((2 * u + (ln_ >> 4)) ^ (row & 7)) << 4)); stll(fm + XR + 128 * c + u * 32, tg(v.x, tag), v.y, v.z, v.w); }
        }
        const float m0 = ((cs_[0][0] + cs_[1][0]) + (cs_[2][0] + cs_[3][0])) * (1.f / 448), m1 = ((cs_[0][2] + cs_[1][2]) + (cs_[2][2] + cs_[3][2])) * (1.f / 448);
        const uint32_t mb0 = pack(m0, m0), mb1 = pack(m1, m1);
        asm volatile("bar.arrive 2, 288;" ::"r"(mb0) : "memory");
#pragma unroll
        for (int ks = 0; ks < 28; ks++) {
          a[ks].x = bsub(a[ks].x, mb0); a[ks].y = bsub(a[ks].y, mb1); a[ks].z = bsub(a[ks].z, mb0); a[ks].w = bsub(a[ks].w, mb1);
        }
        r0 = m0 - blo(mb0); r1 = m1 - blo(mb1);
      } else {
        ll_issue<0, 14>(a, pa, 32);
        if (wg == 0) { RLAST(1u, 10u) xw[3][0] = tg(xw[3][0], 0); RPUB(3) } else { xw[3][0] = xw[3][1] = xw[3][2] = xw[3][3] = 0; }
        MARK(20);
        ll_issue<14, 7>(a, pa, 32);
        ln_stats(xw, sLN, warp, lane, g_S2 + (t * 8 + c) * 8);
      }
      MARK(2 + L * 19);
      float ak[28], av[28], aq[28], pp[28];
#define KVSTAGE(i) { if (L) ll_check<7 * i, 7, false>(a, pa, 32, tag); const uint32_t st = acquire(); wg_fence(); \
      _Pragma("unroll") for (int ks = 0; ks < 7; ks++) { const uint4 f = a[7 * i + ks]; \
        wgmma_rs56(ak, f.x, f.y, f.z, f.w, mkdesc(st, ks * 2048, 1024, 1024, 1), i | ks); \
        wgmma_rs56(av, f.x, f.y, f.z, f.w, mkdesc(st, 14336 + ks * 2048, 1024, 1024, 1), i | ks); } \
      wg_commit(); if (i > 0) { wg_wait<1>(); release(); } }
      KVSTAGE(0) KVSTAGE(1)
      uint4 sv[1];
      const uint4* ps = g_S2 + (t * 8 + warp) * 8 + (ln_ >> 2);
      if (L) { ll_issue<21, 7>(a, pa, 32); ll_issue<0, 1>(sv, ps, 0); }
      KVSTAGE(2) KVSTAGE(3)
      if (L) {
        ll_check<0, 1, false>(sv, ps, 0, 1u);
        const float m0 = -__uint_as_float(sv[0].x), m1 = -__uint_as_float(sv[0].z), h0 = blo(pack(m0, 0.f)), h1 = blo(pack(m1, 0.f));
        r0 = __uint_as_float(sv[0].y); r1 = __uint_as_float(sv[0].w);
        fa = q == 2 ? pack(0.f, h0) : q == 3 ? pack(m0 - h0, h0) : 0u; fb = q == 2 ? pack(0.f, h1) : q == 3 ? pack(m1 - h1, h1) : 0u;
      } else {
        float c0[2][4] = {}, c1[2][4] = {};
#pragma unroll
        for (int ks = 0; ks < 28; ks++) { mma16816(c0[ks & 1], a[ks], a[ks].x, a[ks].z); mma16816(c1[ks & 1], a[ks], a[ks].y, a[ks].w); }
        const int src = (ln_ & 28) | (g >> 1);
        const float q0 = __shfl_sync(~0u, (g & 1) ? c0[0][1] + c0[1][1] : c0[0][0] + c0[1][0], src), q1 = __shfl_sync(~0u, (g & 1) ? c1[0][3] + c1[1][3] : c1[0][2] + c1[1][2], src);
        r0 = rsqrtf(fmaxf(q0 * (1.f / 448) - r0 * r0, 0.f) + 1e-5f); r1 = rsqrtf(fmaxf(q1 * (1.f / 448) - r1 * r1, 0.f) + 1e-5f);
        asm volatile("bar.sync 3, 320;" ::: "memory");
      }
      wg_fence();
      wgmma_rs56(ak, fa, fb, 0u, 0u, mkdesc(d16, OFF_CB + 1024, 512, 0, 2), 1);
      wgmma_rs56(av, fa, fb, 0u, 0u, mkdesc(d16, OFF_CB + 2048, 512, 0, 2), 1);
      wg_commit();
      wg_wait<0>(); release(); regfence(ak); regfence(av);
      MARK(3 + L * 19);
      phi_gemm(ak, pp, d16 + (OFF_WPHI >> 4), r0, r1);
#pragma unroll
      for (int j = 0; j < 7; j++) {
        const int n = 8 * j + 2 * q, n2 = n < 28 ? n : n + 4;
        sts32(sV + sw128(row0, n2), pack(av[4 * j] * r0, av[4 * j + 1] * r0)); sts32(sV + sw128(row0 + 8, n2), pack(av[4 * j + 2] * r1, av[4 * j + 3] * r1));
      }
      { const int n2 = 28 + 2 * (q & 1) + 32 * (q >> 1); const uint32_t v = (q & 1) ? 0u : 0x3F80u; sts32(sV + sw128(row0, n2), v); sts32(sV + sw128(row0 + 8, n2), v); }
      wg_wait<0>(); regfence(pp);
      hedgehog(pp, [&](int r, int h, int p, uint32_t v) { sts32(sPK + h * 16384 + sw128(row0 + 8 * r, 8 * p + 2 * q), v); }, [] {});
      fence_async();
      bar_cons();
      MARK(4 + L * 19);
      float kv[16];
      wg_fence();
#pragma unroll
      for (int ks = 0; ks < 8; ks++) wgmma_ss32(kv, mkdesc(d16 + wg * 1024, OFF_PHIK + ks * 2048, 1024, 1024, 1), mkdesc(d16 + wg * 4, OFF_V + ks * 2048, 1024, 1024, 1), ks);
      wg_commit(); wg_wait<0>(); regfence(kv);
      const int ln2 = laneid();
#pragma unroll
      for (int u = 0; u < 4; u++) {
        float e[4];
#pragma unroll
        for (int i = 0; i < 4; i++) e[i] = kv[4 * u + i];
        stll(g_KVP + (c * 16 + t) * 1024 + wg * 512 + u * 128 + (warp & 3) * 32 + ln2, tg(__float_as_uint(e[0]), tag), __float_as_uint(e[1]), __float_as_uint(e[2]), __float_as_uint(e[3]));
      }
      MARK(5 + L * 19);
      uint4 k4[4];
      const uint4* pk = g_KVP + (c * 16 + 4 * (ln2 & 3)) * 1024 + 64 * t + warp * 8 + (ln2 >> 2);
#pragma unroll
      for (int i = 0; i < 2; i++) {
        const uint32_t st = acquire(); wg_fence();
#pragma unroll
        for (int ks = 0; ks < 14; ks++) { const uint4 f = a[14 * i + ks]; wgmma_rs56(aq, f.x, f.y, f.z, f.w, mkdesc(st, ks * 2048, 1024, 1024, 1), i | ks); }
        if (i == 1) wgmma_rs56(aq, fa, fb, 0u, 0u, mkdesc(d16, OFF_CB, 512, 0, 2), 1);
        wg_commit();
        if (i == 1) ll_issue<0, 4>(k4, pk, 1024);
      }
      ll_check<0, 4, false>(k4, pk, 1024, tag);
      float s0 = 0, s1 = 0, s2 = 0, s3 = 0;
#pragma unroll
      for (int i = 0; i < 4; i++) { s0 += __uint_as_float(k4[i].x); s1 += __uint_as_float(k4[i].y); s2 += __uint_as_float(k4[i].z); s3 += __uint_as_float(k4[i].w); }
      s0 = qsum(s0); s1 = qsum(s1); s2 = qsum(s2); s3 = qsum(s3);
      if (q == 0) stll2(g_KVR + c * 1024 + 64 * t + warp * 8 + (ln2 >> 2), tg(pack(s0, s1), tag), pack(s2, s3));
      MARK(6 + L * 19);
      wg_wait<0>(); release(); release(); regfence(aq);
      phi_gemm(aq, pp, d16 + (OFF_WPHI >> 4), r0, r1);
      bar_cons();
#pragma unroll
      for (int i = 0; i < 4; i++) sts128(sV + warp * 2048 + (lane + i * 32) * 16, 0, 0, 0, 0);
      wg_wait<0>(); regfence(pp);
      uint2 r[4];
      const uint2* pr = g_KVR + c * 1024 + wg * 512 + (warp & 3) * 32 + ln2;
      hedgehog(pp, [&](int r, int h, int p, uint32_t v) { phq[r][h][p] = v; }, [&] {
#pragma unroll
        for (int u = 0; u < 4; u++) r[u] = ldll2(pr + u * 128); });
      MARK(7 + L * 19);
#pragma unroll 1
      for (int it = 0; it < SPIN; it++) {
        if (!__any_sync(~0u, ((r[0].x ^ tag) | (r[1].x ^ tag) | (r[2].x ^ tag) | (r[3].x ^ tag)) & 1)) break;
#pragma unroll
        for (int u = 0; u < 4; u++) r[u] = ldll2(pr + u * 128);
      }
#pragma unroll
      for (int u = 0; u < 4; u++) {
        const int d = 8 * u + 2 * q;
        if (d < 28) { sts32(sV + sw128(row0, 28 * wg + d), r[u].x); sts32(sV + sw128(row0 + 8, 28 * wg + d), r[u].y); }
        else if (d == 28) {
#pragma unroll
          for (int j = 0; j < 4; j++) { sts16(sV + sw128(row0, 56 + 2 * j + wg), r[u].x); sts16(sV + sw128(row0 + 8, 56 + 2 * j + wg), r[u].y); }
        }
      }
      fence_async();
      bar_cons();
      MARK(8 + L * 19);
      float o[32];
      wg_fence();
#pragma unroll
      for (int ks = 0; ks < 8; ks++) {
        const int h = ks >> 2, p = 2 * (ks & 3);
        wgmma_rs64(o, phq[0][h][p], phq[1][h][p], p < 6 ? phq[0][h][p < 6 ? p + 1 : 0] : 0u, p < 6 ? phq[1][h][p < 6 ? p + 1 : 0] : 0u, mkdesc(d16, OFF_V + ks * 2048, 1024, 1024, 1), ks);
      }
      wg_commit(); wg_wait<0>(); regfence(o);
      const float iA0 = rcp(o[28] + 1e-6f), iB0 = rcp(o[29] + 1e-6f), iA1 = rcp(o[30] + 1e-6f), iB1 = rcp(o[31] + 1e-6f);
      uint32_t w[14];
      { PTRS
#pragma unroll
      for (int j = 0; j < 7; j++) {
        const bool hb = 8 * j + 2 * q >= 28; const float i0 = hb ? iB0 : iA0, i1 = hb ? iB1 : iA1;
        w[2 * j] = pack(o[4 * j] * i0, o[4 * j + 1] * i0); w[2 * j + 1] = pack(o[4 * j + 2] * i1, o[4 * j + 3] * i1);
        if (j == 0 || ((j ^ c) & 1) == 0) w[2 * j] = tg(w[2 * j], tag);
      }
      slice_store(sf + OO, sh + 2 * OO, w, c & 1);
      hint_post(hme, hs + 2, lane); }
    }
    MARK(9 + L * 19);
    uint4 xr[4];
    if (c < 7) {
      PTRS
      ll_issue<0, 4>(xr, fm + XR + 128 * c, 32);
      uint4 a[28];
      const uint4* pa = fm + OO;
      hint_wait(hrow, hs + 2);
      MARK(10 + L * 19);
      ll_issue<0, 28, true>(a, pa, 32, f2 + 2 * OO);
      float y[32];
      uint32_t st;
#define WOSTEP(i) { ll_check<7 * i, 7, true>(a, pa, 32, tag, f2 + 2 * OO); if (!(i & 1)) st = acquire(); wg_fence(); \
      _Pragma("unroll") for (int ks = 0; ks < 7; ks++) { const uint4 f = a[7 * i + ks]; \
        wgmma_rs64(y, f.x, f.y, f.z, f.w, mkdesc(st, ((i & 1) * 7 + ks) * 2048, 1024, 1024, 1), i | ks); } wg_commit(); }
      WOSTEP(0) WOSTEP(1) WOSTEP(2) WOSTEP(3)
      ll_check<0, 4, false>(xr, fm + XR + 128 * c, 32, tag);
      wg_wait<0>(); regfence(y);
      MARK(11 + L * 19);
#pragma unroll
      for (int u = 0; u < 4; u++) {
        xr[u].x = tg(pack(blo(xr[u].x) + y[8 * u], bhi(xr[u].x) + y[8 * u + 1]), tag); xr[u].y = pack(blo(xr[u].y) + y[8 * u + 2], bhi(xr[u].y) + y[8 * u + 3]);
        xr[u].z = pack(blo(xr[u].z) + y[8 * u + 4], bhi(xr[u].z) + y[8 * u + 5]); xr[u].w = pack(blo(xr[u].w) + y[8 * u + 6], bhi(xr[u].w) + y[8 * u + 7]);
        stll(fm + X1 + 128 * c + u * 32, xr[u].x, xr[u].y, xr[u].z, xr[u].w);
      }
      hint_post(hme, hs + 3, lane);
    } else {
      PTRS
      hint_post(hme, hs + 3, lane);
      acquire(); acquire();
      hint_wait(g_H + (t * 8 + warp) * 8, hs + 3);
      ll_issue<0, 4>(xr, fm + X1, 32); ll_check<0, 4, false>(xr, fm + X1, 32, tag);
      MARK(10 + L * 19); MARK(11 + L * 19);
    }
    uint32_t hf[56];
    float rr0, rr1;
    {
      PTRS
      uint4 a[28];
      const uint4* pa = fm + X1;
      auto grp = [&](int i) -> const uint4* { const int k = i + c; return pa + ((k >= 7 ? k - 7 : k) - i) * 128; };
#pragma unroll
      for (int u = 0; u < 4; u++) a[u] = xr[u];
      float y[96], z[16];
#define F1STAGE(i) { if (i > 0) ll_check<4 * i, 4, false>(a, grp(i), 32, tag); const uint32_t st = acquire(); wg_fence(); \
      _Pragma("unroll") for (int ks = 0; ks < 4; ks++) { const uint4 f = a[4 * i + ks]; \
        wgmma_rs192(y, f.x, f.y, f.z, f.w, mkdesc(st, (ks >> 1) * 12288 + (ks & 1) * 2048, 4096, 1024, 1), i | ks); \
        wgmma_rs32(z, f.x, f.y, f.z, f.w, mkdesc(st, 24576 + ks * 1024, 512, 512, 2), i | ks); } \
      wg_commit(); if (i > 0) { wg_wait<1>(); release(); if (i < 4) ll_issue<(i < 4 ? 4 * i + 12 : 0), 4>(a, grp(i + 3), 32); } }
      F1STAGE(0)
      hint_wait(hrow, hs + 3);
      MARK(12 + L * 19);
      ll_issue<4, 4>(a, grp(1), 32); ll_issue<8, 4>(a, grp(2), 32); ll_issue<12, 4>(a, grp(3), 32);
      if (c < 7) {
        float s0 = 0.f, s1 = 0.f, v0 = 0.f, v1 = 0.f;
#pragma unroll
        for (int u = 0; u < 4; u++) { s0 += (blo(xr[u].x) + bhi(xr[u].x)) + (blo(xr[u].z) + bhi(xr[u].z)); s1 += (blo(xr[u].y) + bhi(xr[u].y)) + (blo(xr[u].w) + bhi(xr[u].w)); }
        s0 = qsum(s0) * (1.f / 64); s1 = qsum(s1) * (1.f / 64);
#pragma unroll
        for (int u = 0; u < 4; u++) {
          const float d0 = blo(xr[u].x) - s0, d1 = bhi(xr[u].x) - s0, d2 = blo(xr[u].z) - s0, d3 = bhi(xr[u].z) - s0;
          const float d4 = blo(xr[u].y) - s1, d5 = bhi(xr[u].y) - s1, d6 = blo(xr[u].w) - s1, d7 = bhi(xr[u].w) - s1;
          v0 += (d0 * d0 + d1 * d1) + (d2 * d2 + d3 * d3); v1 += (d4 * d4 + d5 * d5) + (d6 * d6 + d7 * d7);
        }
        v0 = qsum(v0); v1 = qsum(v1);
        if (q == 0) stll(g_ST + ((t * 8 + warp) * 8 + c) * 8 + (ln_ >> 2), tg(__float_as_uint(s0), tag), __float_as_uint(v0), __float_as_uint(s1), __float_as_uint(v1));
      }
      if (LAG < 2) release();
      if (LAG < 1) release();
#define LAGREL if (LAG > 0) release(); if (LAG > 1) release();
      F1STAGE(1) MARK(13 + L * 19); F1STAGE(2) F1STAGE(3)
      uint4 sv[2];
      const uint4* ps = g_ST + ((t * 8 + warp) * 8 + 2 * (laneid() & 3)) * 8 + (laneid() >> 2);
      ll_issue<0, 2>(sv, ps, q < 3 ? 8 : 0);
      F1STAGE(4)
      ll_check<0, 2, false>(sv, ps, q < 3 ? 8 : 0, tag);
      const float wb = q < 3 ? 1.f : 0.f;
      const float ma = __uint_as_float(sv[0].x), mb = __uint_as_float(sv[1].x), mc = __uint_as_float(sv[0].z), md = __uint_as_float(sv[1].z);
      const float m0 = qsum(ma + wb * mb) * (1.f / 7), m1 = qsum(mc + wb * md) * (1.f / 7);
      const float v0 = qsum(__uint_as_float(sv[0].y) + 64.f * (ma - m0) * (ma - m0) + wb * (__uint_as_float(sv[1].y) + 64.f * (mb - m0) * (mb - m0)));
      const float v1 = qsum(__uint_as_float(sv[0].w) + 64.f * (mc - m1) * (mc - m1) + wb * (__uint_as_float(sv[1].w) + 64.f * (md - m1) * (md - m1)));
      const float e0 = v0 * (1.f / 448) + 1e-5f, e1 = v1 * (1.f / 448) + 1e-5f;
      rr0 = 1.f / e0; rr1 = 1.f / e1;
      auto fold = [&](float m, float sd) -> uint32_t {
        const float mh = blo(pack(-m, 0.f)), sh_ = blo(pack(sd, 0.f));
        return q == 0 ? pack(mh, -m - mh) : q == 1 ? pack(mh, sh_) : q == 2 ? pack(sd - sh_, 0.f) : 0u;
      };
      const uint32_t fa = fold(m0, sqrtf(e0)), fb = fold(m1, sqrtf(e1));
      if (L == 0) asm volatile("bar.sync 4, 288;" ::: "memory");
      wg_fence();
      wgmma_rs192(y, fa, fb, 0u, 0u, mkdesc(d16, OFF_CB, 512, 0, 2), 1);
      wgmma_rs32(z, fa, fb, 0u, 0u, mkdesc(d16, OFF_CB + 3072, 512, 0, 2), 1);
      F1STAGE(5) F1STAGE(6)
      wg_wait<0>(); release(); LAGREL regfence(y); regfence(z);
      MARK(14 + L * 19);
#pragma unroll
      for (int j = 0; j < 56; j++) {
        uint32_t r; asm("cvt.rn.relu.bf16x2.f32 %0, %1, %2;" : "=r"(r) : "f"(j < 48 ? y[j < 48 ? 2 * j + 1 : 0] : z[j < 48 ? 0 : 2 * j - 95]), "f"(j < 48 ? y[j < 48 ? 2 * j : 0] : z[j < 48 ? 0 : 2 * j - 96]));
        asm("mul.bf16x2 %0, %1, %1;" : "=r"(hf[j]) : "r"(r));
      }
    }
    MARK(15 + L * 19);
    {
      PTRS
      float ya[32], yb[32];
      uint4* pp = g_P + ((t * 8 + warp) * 8 + c) * 28 * 32 + ln_;
#define F2STORE(j, Y) { regfence(Y); _Pragma("unroll") for (int u = 0; u < 4; u++) \
      stll(pp + (4 * (j) + u) * 32, tg(pack(Y[8 * u] * rr0, Y[8 * u + 1] * rr0), tag), pack(Y[8 * u + 2] * rr1, Y[8 * u + 3] * rr1), \
           pack(Y[8 * u + 4] * rr0, Y[8 * u + 5] * rr0), pack(Y[8 * u + 6] * rr1, Y[8 * u + 7] * rr1)); if ((j) >= 5) hint_post(hme, hs + (4 + (j)), lane); }
#define F2PASS(j, Y, Z) { const uint32_t st = acquire(); wg_fence(); \
      _Pragma("unroll") for (int ks = 0; ks < 14; ks++) wgmma_rs64(Y, hf[4 * ks], hf[4 * ks + 1], hf[4 * ks + 2], hf[4 * ks + 3], mkdesc(st, ks * 2048, 1024, 1024, 1), ks); \
      wg_commit(); if (j > 0) { wg_wait<1>(); release(); F2STORE(j - 1, Z) } }
      const uint4* pr = g_P + ((t * 8 + c) * 8 * 28 + warp) * 32 + ln_;
      uint4 p[8], p2[8]; uint2 xa, xb, xc, xd; uint32_t ba, bb, bc, bd;
      const uint32_t ptag = tag;
      const uint32_t* hred = g_H + (t * 8 + c) * 8 + (ln_ & 7);
      F2PASS(0, ya, yb) F2PASS(1, yb, ya) F2PASS(2, ya, yb) F2PASS(3, yb, ya)
      F2PASS(4, ya, yb)
      RISSUE(0, p, xa, xb, ba, bb)
      F2PASS(5, yb, ya)
      REDU(0, p, xa, xb, ba, bb)
      if (L == 0) { xw[0][0] = tg(xw[0][0], 0); RPUB(0) }
      F2PASS(6, ya, yb)
      RISSUE(1, p, xa, xb, ba, bb)
      wg_wait<0>(); release(); F2STORE(6, ya)
      MARK(16 + L * 19);
      if (L == 0) asm volatile("bar.sync 8, 288;" ::: "memory");
      if (wg) hint_wait(hred, hs + 9);
      RISSUE(2, p2, xc, xd, bc, bd)
      REDU(1, p, xa, xb, ba, bb)
      if (L == 0) { xw[1][0] = tg(xw[1][0], 0); RPUB(1) }
      MARK(17 + L * 19);
      REDU(2, p2, xc, xd, bc, bd)
      if (L == 0) { xw[2][0] = tg(xw[2][0], 0); RPUB(2) }
    }
    MARK(18 + L * 19);
  }
  {
    PTRS
    uint32_t* op = (uint32_t*)(out + XOFF(ln_));
#define OUT(u) { op[u * 64] = xw[u][0]; op[u * 64 + 1792] = xw[u][1]; op[u * 64 + 4] = xw[u][2]; op[u * 64 + 1796] = xw[u][3]; }
    OUT(0) OUT(1) OUT(2)
    if (wg == 0) { RLAST(0u, 20u) OUT(3) }
    else if (warp == 7) {
      if (t == 0 && lane == 0) g_WQF[c] = 0;
      if (lane < 8) stll(g_S2 + (t * 8 + c) * 8 + lane, 0, 0, 0, 0);
      if (lane < 4) { stll(g_CS + blockIdx.x * 4 + lane, 0, 0, 0, 0); if (blockIdx.x < 68) stll(g_CS + 512 + blockIdx.x * 4 + lane, 0, 0, 0, 0); }
    }
  }
  MARK(38); GT(39);
  }
}

typedef CUresult (*EncFn)(CUtensorMap*, CUtensorMapDataType, cuuint32_t, void*, const cuuint64_t*, const cuuint64_t*, const cuuint32_t*, const cuuint32_t*,
                          CUtensorMapInterleave, CUtensorMapSwizzle, CUtensorMapL2promotion, CUtensorMapFloatOOBfill);

extern "C" void kernel_launch(void* const* d_in, const int* in_sizes, int n_in, void* d_out, int out_size) {
  static EncFn enc = nullptr;
  if (!enc) {
    void* fn = nullptr; cudaDriverEntryPointQueryResult qr;
    cudaGetDriverEntryPoint("cuTensorMapEncodeTiled", &fn, cudaEnableDefault, &qr);
    enc = (EncFn)fn;
    cudaFuncSetAttribute(fused_kernel, cudaFuncAttributeMaxDynamicSharedMemorySize, SMEM_BYTES);
  }
  CUtensorMap mQKV, mWO, mW1, mW1b, mW2, mW2b, mX;
  const cuuint32_t es[3] = {1, 1, 1};
  auto enc2 = [&](CUtensorMap* m, void* p, cuuint64_t cols, cuuint64_t rows, cuuint32_t bc, cuuint32_t br) {
    const cuuint64_t dims[2] = {cols, rows}, str[1] = {cols * 2}; const cuuint32_t box[2] = {bc, br};
    enc(m, CU_TENSOR_MAP_DATA_TYPE_BFLOAT16, 2, p, dims, str, box, es, CU_TENSOR_MAP_INTERLEAVE_NONE,
        bc == 64 ? CU_TENSOR_MAP_SWIZZLE_128B : CU_TENSOR_MAP_SWIZZLE_64B, CU_TENSOR_MAP_L2_PROMOTION_L2_128B, CU_TENSOR_MAP_FLOAT_OOB_FILL_NONE);
  };
  enc2(&mQKV, d_in[1], 1344, 448, 64, 112); enc2(&mWO, d_in[3], 448, 448, 64, 112); enc2(&mW1b, d_in[5], 1792, 448, 32, 32);
  enc2(&mX, d_in[0], 448, 2048, 64, 128);
  enc2(&mW2, d_in[7], 448, 1792, 64, 96); enc2(&mW2b, d_in[7], 448, 1792, 64, 16);
  {
    const cuuint64_t dims[3] = {64, 448, 28}, str[2] = {3584, 128}; const cuuint32_t box[3] = {64, 32, 3};
    enc(&mW1, CU_TENSOR_MAP_DATA_TYPE_BFLOAT16, 3, d_in[5], dims, str, box, es, CU_TENSOR_MAP_INTERLEAVE_NONE, CU_TENSOR_MAP_SWIZZLE_128B,
        CU_TENSOR_MAP_L2_PROMOTION_L2_128B, CU_TENSOR_MAP_FLOAT_OOB_FILL_NONE);
  }
  typedef const __nv_bfloat16* BP;
  fused_kernel<<<128, 384, SMEM_BYTES>>>(mQKV, mWO, mW1, mW1b, mW2, mW2b, mX, (BP)d_in[1], (BP)d_in[2], (BP)d_in[3], (BP)d_in[5], (BP)d_in[6], (BP)d_in[7], (BP)d_in[8],
                                         (__nv_bfloat16*)d_out);
}
```

```cpp
#include <cuda_runtime.h>
#include <cuda_bf16.h>
#include <cuda.h>
#include <stdint.h>

constexpr int NST = 6, STAGE = 28672;
constexpr int OFF_PHIK = NST * STAGE;
constexpr int OFF_V = OFF_PHIK + 32768;
constexpr int OFF_WPHI = OFF_V + 16384;
constexpr int OFF_CB = OFF_WPHI + 7168;
constexpr int OFF_BAR = OFF_CB + 3584;
constexpr int SMEM_BYTES = OFF_BAR + 16 * NST + 8;
constexpr int FR = 16 * 8 * 28 * 32;
constexpr int SPIN = 1 << 18;
#define MC 0
#define MAPPING MC
#define MCS
#define MCA(n)
#define CLUSTER
#define LAG 1
#define PFQ 1
#define PFS 3
#define PACE 2

__device__ uint4 g_F[3 * FR];
constexpr int XR = 0, OO = FR, X1 = 2 * FR;
__device__ uint4 g_P[8 * FR];
__device__ uint4 g_ST[16 * 8 * 8 * 8];
__device__ uint4 g_KVP[8 * 16 * 1024];
__device__ uint2 g_KVR[8 * 1024];
__device__ uint4 g_CS[784];
__device__ uint4 g_S2[16 * 8 * 8];
__device__ uint4 g_WQ[8 * 6 * (STAGE / 16)];
__device__ uint32_t g_WQF[8];
__device__ uint32_t g_H[16 * 8 * 8];
#define MARK(i)
#define GT(i)

__device__ __forceinline__ uint32_t s2u(const void* p) { return (uint32_t)__cvta_generic_to_shared(p); }
__device__ __forceinline__ void mbar_init(uint32_t b, uint32_t c) { asm volatile("mbarrier.init.shared::cta.b64 [%0], %1;" ::"r"(b), "r"(c)); }
__device__ __forceinline__ void mbar_expect(uint32_t b, uint32_t tx) { asm volatile("mbarrier.arrive.expect_tx.shared::cta.b64 _, [%0], %1;" ::"r"(b), "r"(tx) : "memory"); }
__device__ __forceinline__ void mbar_arrive_cl(uint32_t b, uint32_t rank) {
  asm volatile("{.reg .b32 r; mapa.shared::cluster.u32 r, %0, %1; mbarrier.arrive.shared::cluster.b64 _, [r];}" ::"r"(b), "r"(rank) : "memory");
}
__device__ __forceinline__ void mbar_wait(uint32_t b, uint32_t ph) {
  uint32_t ok = 0;
#pragma unroll 1
  for (int it = 0; it < SPIN && !ok; it++)
    asm volatile("{.reg .pred p; mbarrier.try_wait.parity.shared::cta.b64 p,[%1],%2; selp.u32 %0,1,0,p;}" : "=r"(ok) : "r"(b), "r"(ph) : "memory");
}
__device__ __forceinline__ void tma2d(uint32_t dst, const CUtensorMap* m, int c0, int c1, uint32_t bar) {
  asm volatile("cp.async.bulk.tensor.2d.shared::cluster.global.mbarrier::complete_tx::bytes" MCS " [%0], [%1, {%3, %4}], [%2]" MCA(5) ";"
               ::"r"(dst), "l"(m), "r"(bar), "r"(c0), "r"(c1), "h"((uint16_t)3) : "memory");
}
__device__ __forceinline__ void tma3d(uint32_t dst, const CUtensorMap* m, int c0, int c1, int c2, uint32_t bar) {
  asm volatile("cp.async.bulk.tensor.3d.shared::cluster.global.mbarrier::complete_tx::bytes" MCS " [%0], [%1, {%3, %4, %5}], [%2]" MCA(6) ";"
               ::"r"(dst), "l"(m), "r"(bar), "r"(c0), "r"(c1), "r"(c2), "h"((uint16_t)3) : "memory");
}
__device__ __forceinline__ void l2pf(const void* p, uint32_t bytes) { asm volatile("cp.async.bulk.prefetch.L2.global [%0], %1;" ::"l"(p), "r"(bytes) : "memory"); }
__device__ __forceinline__ void wg_fence() { asm volatile("wgmma.fence.sync.aligned;" ::: "memory"); }
__device__ __forceinline__ void wg_commit() { asm volatile("wgmma.commit_group.sync.aligned;" ::: "memory"); }
template <int N> __device__ __forceinline__ void wg_wait() { asm volatile("wgmma.wait_group.sync.aligned %0;" ::"n"(N) : "memory"); }
template <int N> __device__ __forceinline__ void regfence(float (&d)[N]) {
#pragma unroll
  for (int i = 0; i < N; i++) asm volatile("" : "+f"(d[i])::"memory");
}
__device__ __forceinline__ void bar_cons() { asm volatile("bar.sync 1, 256;" ::: "memory"); }
__device__ __forceinline__ void fence_async() { asm volatile("fence.proxy.async.shared::cta;" ::: "memory"); }
struct Desc { uint32_t lo, hi; };
__device__ __forceinline__ Desc mkdesc(uint32_t base16, uint32_t off, uint32_t lbo, uint32_t sbo, uint32_t swz) {
  return Desc{base16 + ((off >> 4) | ((lbo >> 4) << 16)), (sbo >> 4) | (swz << 30)};
}
__device__ __forceinline__ uint4 ldll(const uint4* p) {
  uint4 v; asm volatile("ld.relaxed.gpu.global.v4.u32 {%0,%1,%2,%3}, [%4];" : "=r"(v.x), "=r"(v.y), "=r"(v.z), "=r"(v.w) : "l"(p) : "memory"); return v;
}
__device__ __forceinline__ uint2 ldll2(const uint2* p) {
  uint2 v; asm volatile("ld.relaxed.gpu.global.v2.u32 {%0,%1}, [%2];" : "=r"(v.x), "=r"(v.y) : "l"(p) : "memory"); return v;
}
__device__ __forceinline__ void stll(uint4* p, uint32_t x, uint32_t y, uint32_t z, uint32_t w) {
  asm volatile("st.relaxed.gpu.global.v4.u32 [%0], {%1,%2,%3,%4};" ::"l"(p), "r"(x), "r"(y), "r"(z), "r"(w) : "memory");
}
__device__ __forceinline__ void stll2(void* p, uint32_t x, uint32_t y) {
  asm volatile("st.relaxed.gpu.global.v2.u32 [%0], {%1,%2};" ::"l"(p), "r"(x), "r"(y) : "memory");
}
__device__ __forceinline__ int laneid() { int l; asm volatile("mov.u32 %0, %%laneid;" : "=r"(l)); return l; }
__device__ __forceinline__ uint32_t tg(uint32_t w, uint32_t tag) { return (w & ~1u) | tag; }
__device__ __forceinline__ uint32_t pack(float lo, float hi) {
  uint32_t r; asm("cvt.rn.bf16x2.f32 %0, %1, %2;" : "=r"(r) : "f"(hi), "f"(lo)); return r;
}
__device__ __forceinline__ float blo(uint32_t w) { return __uint_as_float(w << 16); }
__device__ __forceinline__ float bhi(uint32_t w) { return __uint_as_float(w & 0xffff0000u); }
__device__ __forceinline__ float ex2(float x) { float r; asm("ex2.approx.ftz.f32 %0, %1;" : "=f"(r) : "f"(x)); return r; }
__device__ __forceinline__ float rcp(float x) { float r; asm("rcp.approx.ftz.f32 %0, %1;" : "=f"(r) : "f"(x)); return r; }
__device__ __forceinline__ float qsum(float v) { v += __shfl_xor_sync(~0u, v, 1); v += __shfl_xor_sync(~0u, v, 2); return v; }
__device__ __forceinline__ void sts32(uint32_t a, uint32_t v) { asm volatile("st.shared.u32 [%0], %1;" ::"r"(a), "r"(v) : "memory"); }
__device__ __forceinline__ void sts16(uint32_t a, uint32_t v) { asm volatile("st.shared.u16 [%0], %1;" ::"r"(a), "h"((uint16_t)v) : "memory"); }
__device__ __forceinline__ void sts128(uint32_t a, uint32_t x, uint32_t y, uint32_t z, uint32_t w) {
  asm volatile("st.shared.v4.u32 [%0], {%1,%2,%3,%4};" ::"r"(a), "r"(x), "r"(y), "r"(z), "r"(w) : "memory");
}
__device__ __forceinline__ uint32_t sw128(int row, int col) { return row * 128 + ((((col >> 3) ^ row) & 7) << 4) + (col & 7) * 2; }

__device__ __forceinline__ void wgmma_rs56(float (&d)[28], const uint32_t a0, const uint32_t a1, const uint32_t a2, const uint32_t a3, Desc db, int sd) {
  asm volatile("{.reg .pred p; .reg .b64 da, db; setp.ne.b32 p, %33, 0; mov.b64 db, {%32, %34};\n wgmma.mma_async.sync.aligned.m64n56k16.f32.bf16.bf16 {%0,%1,%2,%3,%4,%5,%6,%7,%8,%9,%10,%11,%12,%13,%14,%15,%16,%17,%18,%19,%20,%21,%22,%23,%24,%25,%26,%27}, {%28,%29,%30,%31}, db, p, 1, 1, 1;}"
   : "+f"(d[0]),"+f"(d[1]),"+f"(d[2]),"+f"(d[3]),"+f"(d[4]),"+f"(d[5]),"+f"(d[6]),"+f"(d[7]),"+f"(d[8]),"+f"(d[9]),"+f"(d[10]),"+f"(d[11]),"+f"(d[12]),"+f"(d[13]),"+f"(d[14]),"+f"(d[15]),"+f"(d[16]),"+f"(d[17]),"+f"(d[18]),"+f"(d[19]),"+f"(d[20]),"+f"(d[21]),"+f"(d[22]),"+f"(d[23]),"+f"(d[24]),"+f"(d[25]),"+f"(d[26]),"+f"(d[27])
   : "r"(a0),"r"(a1),"r"(a2),"r"(a3),"r"(db.lo),"r"(sd),"r"(db.hi));
}
__device__ __forceinline__ void wgmma_rs64(float (&d)[32], const uint32_t a0, const uint32_t a1, const uint32_t a2, const uint32_t a3, Desc db, int sd) {
  asm volatile("{.reg .pred p; .reg .b64 da, db; setp.ne.b32 p, %37, 0; mov.b64 db, {%36, %38};\n wgmma.mma_async.sync.aligned.m64n64k16.f32.bf16.bf16 {%0,%1,%2,%3,%4,%5,%6,%7,%8,%9,%10,%11,%12,%13,%14,%15,%16,%17,%18,%19,%20,%21,%22,%23,%24,%25,%26,%27,%28,%29,%30,%31}, {%32,%33,%34,%35}, db, p, 1, 1, 1;}"
   : "+f"(d[0]),"+f"(d[1]),"+f"(d[2]),"+f"(d[3]),"+f"(d[4]),"+f"(d[5]),"+f"(d[6]),"+f"(d[7]),"+f"(d[8]),"+f"(d[9]),"+f"(d[10]),"+f"(d[11]),"+f"(d[12]),"+f"(d[13]),"+f"(d[14]),"+f"(d[15]),"+f"(d[16]),"+f"(d[17]),"+f"(d[18]),"+f"(d[19]),"+f"(d[20]),"+f"(d[21]),"+f"(d[22]),"+f"(d[23]),"+f"(d[24]),"+f"(d[25]),"+f"(d[26]),"+f"(d[27]),"+f"(d[28]),"+f"(d[29]),"+f"(d[30]),"+f"(d[31])
   : "r"(a0),"r"(a1),"r"(a2),"r"(a3),"r"(db.lo),"r"(sd),"r"(db.hi));
}
__device__ __forceinline__ void wgmma_rs192(float (&d)[96], const uint32_t a0, const uint32_t a1, const uint32_t a2, const uint32_t a3, Desc db, int sd) {
  asm volatile("{.reg .pred p; .reg .b64 db; setp.ne.b32 p, %101, 0; mov.b64 db, {%100, %102};\n wgmma.mma_async.sync.aligned.m64n192k16.f32.bf16.bf16 {%0,%1,%2,%3,%4,%5,%6,%7,%8,%9,%10,%11,%12,%13,%14,%15,%16,%17,%18,%19,%20,%21,%22,%23,%24,%25,%26,%27,%28,%29,%30,%31,%32,%33,%34,%35,%36,%37,%38,%39,%40,%41,%42,%43,%44,%45,%46,%47,%48,%49,%50,%51,%52,%53,%54,%55,%56,%57,%58,%59,%60,%61,%62,%63,%64,%65,%66,%67,%68,%69,%70,%71,%72,%73,%74,%75,%76,%77,%78,%79,%80,%81,%82,%83,%84,%85,%86,%87,%88,%89,%90,%91,%92,%93,%94,%95}, {%96,%97,%98,%99}, db, p, 1, 1, 1;}"
   : "+f"(d[0]),"+f"(d[1]),"+f"(d[2]),"+f"(d[3]),"+f"(d[4]),"+f"(d[5]),"+f"(d[6]),"+f"(d[7]),"+f"(d[8]),"+f"(d[9]),"+f"(d[10]),"+f"(d[11]),"+f"(d[12]),"+f"(d[13]),"+f"(d[14]),"+f"(d[15]),"+f"(d[16]),"+f"(d[17]),"+f"(d[18]),"+f"(d[19]),"+f"(d[20]),"+f"(d[21]),"+f"(d[22]),"+f"(d[23]),"+f"(d[24]),"+f"(d[25]),"+f"(d[26]),"+f"(d[27]),"+f"(d[28]),"+f"(d[29]),"+f"(d[30]),"+f"(d[31]),"+f"(d[32]),"+f"(d[33]),"+f"(d[34]),"+f"(d[35]),"+f"(d[36]),"+f"(d[37]),"+f"(d[38]),"+f"(d[39]),"+f"(d[40]),"+f"(d[41]),"+f"(d[42]),"+f"(d[43]),"+f"(d[44]),"+f"(d[45]),"+f"(d[46]),"+f"(d[47]),"+f"(d[48]),"+f"(d[49]),"+f"(d[50]),"+f"(d[51]),"+f"(d[52]),"+f"(d[53]),"+f"(d[54]),"+f"(d[55]),"+f"(d[56]),"+f"(d[57]),"+f"(d[58]),"+f"(d[59]),"+f"(d[60]),"+f"(d[61]),"+f"(d[62]),"+f"(d[63]),"+f"(d[64]),"+f"(d[65]),"+f"(d[66]),"+f"(d[67]),"+f"(d[68]),"+f"(d[69]),"+f"(d[70]),"+f"(d[71]),"+f"(d[72]),"+f"(d[73]),"+f"(d[74]),"+f"(d[75]),"+f"(d[76]),"+f"(d[77]),"+f"(d[78]),"+f"(d[79]),"+f"(d[80]),"+f"(d[81]),"+f"(d[82]),"+f"(d[83]),"+f"(d[84]),"+f"(d[85]),"+f"(d[86]),"+f"(d[87]),"+f"(d[88]),"+f"(d[89]),"+f"(d[90]),"+f"(d[91]),"+f"(d[92]),"+f"(d[93]),"+f"(d[94]),"+f"(d[95])
   : "r"(a0),"r"(a1),"r"(a2),"r"(a3),"r"(db.lo),"r"(sd),"r"(db.hi));
}
__device__ __forceinline__ void wgmma_rs32(float (&d)[16], const uint32_t a0, const uint32_t a1, const uint32_t a2, const uint32_t a3, Desc db, int sd) {
  asm volatile("{.reg .pred p; .reg .b64 db; setp.ne.b32 p, %21, 0; mov.b64 db, {%20, %22};\n wgmma.mma_async.sync.aligned.m64n32k16.f32.bf16.bf16 {%0,%1,%2,%3,%4,%5,%6,%7,%8,%9,%10,%11,%12,%13,%14,%15}, {%16,%17,%18,%19}, db, p, 1, 1, 1;}"
   : "+f"(d[0]),"+f"(d[1]),"+f"(d[2]),"+f"(d[3]),"+f"(d[4]),"+f"(d[5]),"+f"(d[6]),"+f"(d[7]),"+f"(d[8]),"+f"(d[9]),"+f"(d[10]),"+f"(d[11]),"+f"(d[12]),"+f"(d[13]),"+f"(d[14]),"+f"(d[15])
   : "r"(a0),"r"(a1),"r"(a2),"r"(a3),"r"(db.lo),"r"(sd),"r"(db.hi));
}
__device__ __forceinline__ void wgmma_ss32(float (&d)[16], Desc da, Desc db, int sd) {
  asm volatile("{.reg .pred p; .reg .b64 da, db; setp.ne.b32 p, %18, 0; mov.b64 da, {%16, %19}; mov.b64 db, {%17, %19};\n wgmma.mma_async.sync.aligned.m64n32k16.f32.bf16.bf16 {%0,%1,%2,%3,%4,%5,%6,%7,%8,%9,%10,%11,%12,%13,%14,%15}, da, db, p, 1, 1, 1, 1;}"
   : "+f"(d[0]),"+f"(d[1]),"+f"(d[2]),"+f"(d[3]),"+f"(d[4]),"+f"(d[5]),"+f"(d[6]),"+f"(d[7]),"+f"(d[8]),"+f"(d[9]),"+f"(d[10]),"+f"(d[11]),"+f"(d[12]),"+f"(d[13]),"+f"(d[14]),"+f"(d[15])
   : "r"(da.lo),"r"(db.lo),"r"(sd),"r"(db.hi));
}

__device__ __forceinline__ uint4 ldsm4(uint32_t a) {
  uint4 v; asm volatile("ldmatrix.sync.aligned.m8n8.x4.shared.b16 {%0,%1,%2,%3}, [%4];" : "=r"(v.x), "=r"(v.y), "=r"(v.z), "=r"(v.w) : "r"(a) : "memory"); return v;
}
__device__ __forceinline__ void mma16816(float (&d)[4], const uint4& a, uint32_t b0, uint32_t b1) {
  asm("mma.sync.aligned.m16n8k16.row.col.f32.bf16.bf16.f32 {%0,%1,%2,%3}, {%4,%5,%6,%7}, {%8,%9}, {%0,%1,%2,%3};"
      : "+f"(d[0]), "+f"(d[1]), "+f"(d[2]), "+f"(d[3]) : "r"(a.x), "r"(a.y), "r"(a.z), "r"(a.w), "r"(b0), "r"(b1));
}
__device__ __forceinline__ uint32_t bsub(uint32_t a, uint32_t b) { uint32_t r; asm("sub.bf16x2 %0, %1, %2;" : "=r"(r) : "r"(a), "r"(b)); return r; }
__device__ __forceinline__ uint32_t hint_ld(const uint32_t* p) { uint32_t v; asm volatile("ld.relaxed.gpu.global.u32 %0, [%1];" : "=r"(v) : "l"(p) : "memory"); return v; }
template <int S, int N, bool SPL = false, int T> __device__ __forceinline__ void ll_issue(uint4 (&v)[T], const uint4* p, int stride, const uint2* p2 = nullptr) {
#pragma unroll
  for (int i = S; i < S + N; i++) {
    if (SPL && i % 7 == 3) { const uint2 lo = ldll2(p2 + i * 64), hi = ldll2(p2 + i * 64 + 32); v[i] = make_uint4(lo.x, lo.y, hi.x, hi.y); }
    else v[i] = ldll(p + i * stride);
  }
}
template <int S, int N, bool SPL, int T> __device__ __forceinline__ void ll_check(uint4 (&v)[T], const uint4* p, int stride, uint32_t tag, const uint2* p2 = nullptr) {
#pragma unroll 1
  for (int it = 0; it < SPIN; it++) {
    uint32_t bad = 0;
#pragma unroll
    for (int i = S; i < S + N; i++) bad |= (v[i].x ^ tag) | ((SPL && i % 7 == 3) ? (v[i].z ^ tag) : 0u);
    if (!__any_sync(~0u, bad & 1)) break;
    ll_issue<S, N, SPL>(v, p, stride, p2);
  }
}
__device__ __forceinline__ void hint_post(uint32_t* p, uint32_t v, int lane) {
  if (lane == 0) asm volatile("st.relaxed.gpu.global.u32 [%0], %1;" ::"l"(p), "r"(v) : "memory");
}
__device__ __forceinline__ void hint_wait(const uint32_t* p, uint32_t s, uint32_t v = 0xffffu) {
#pragma unroll 1
  for (int it = 0; it < SPIN; it++) {
    if (__all_sync(~0u, v - s < 10u)) break;
    v = hint_ld(p);
  }
}
__device__ __forceinline__ void slice_store(uint4* pf, uint2* ph, const uint32_t (&w)[14], bool odd) {
#pragma unroll
  for (int u = 0; u < 3; u++)
    stll(pf + u * 32, odd ? w[4 * u + 2] : w[4 * u], odd ? w[4 * u + 3] : w[4 * u + 1], odd ? w[4 * u + 4] : w[4 * u + 2], odd ? w[4 * u + 5] : w[4 * u + 3]);
  stll2(ph, odd ? w[0] : w[12], odd ? w[1] : w[13]);
}
template <class F, class M> __device__ __forceinline__ void hedgehog(const float (&d)[28], F sink, M mid) {
  const float L2E = 1.4426950408889634f;
#define HX(G, p) ((p) < 6 ? d[((G) & 1) * 16 + ((p) >> 1) * 4 + ((p) & 1) + ((G) & 2)] : d[12 + (G)])
  float mx[4], mn[4], sp[4], sn[4], ep[4][7], en[4][7];
#pragma unroll
  for (int G = 0; G < 4; G++) {
    mx[G] = mn[G] = HX(G, 0);
#pragma unroll
    for (int p = 1; p < 7; p++) { mx[G] = fmaxf(mx[G], HX(G, p)); mn[G] = fminf(mn[G], HX(G, p)); }
  }
#pragma unroll
  for (int o = 1; o < 4; o <<= 1)
#pragma unroll
    for (int G = 0; G < 4; G++) { mx[G] = fmaxf(mx[G], __shfl_xor_sync(~0u, mx[G], o)); mn[G] = fminf(mn[G], __shfl_xor_sync(~0u, mn[G], o)); }
#pragma unroll
  for (int G = 0; G < 4; G++) {
    const float a = -mx[G] * L2E, b = mn[G] * L2E;
#pragma unroll
    for (int p = 0; p < 7; p++) { ep[G][p] = ex2(fmaf(HX(G, p), L2E, a)); en[G][p] = ex2(fmaf(HX(G, p), -L2E, b)); }
    sp[G] = ((ep[G][0] + ep[G][1]) + (ep[G][2] + ep[G][3])) + ((ep[G][4] + ep[G][5]) + ep[G][6]);
    sn[G] = ((en[G][0] + en[G][1]) + (en[G][2] + en[G][3])) + ((en[G][4] + en[G][5]) + en[G][6]);
    if (G == 1) mid();
  }
#pragma unroll
  for (int o = 1; o < 4; o <<= 1)
#pragma unroll
    for (int G = 0; G < 4; G++) { sp[G] += __shfl_xor_sync(~0u, sp[G], o); sn[G] += __shfl_xor_sync(~0u, sn[G], o); }
#pragma unroll
  for (int G = 0; G < 4; G++) {
    const float a = rcp(sp[G]), b = rcp(sn[G]);
#pragma unroll
    for (int p = 0; p < 7; p++) sink(G >> 1, G & 1, p, pack(ep[G][p] * a, en[G][p] * b));
  }
}
__device__ __forceinline__ void phi_gemm(const float (&x)[28], float (&y)[28], uint32_t wphi, float r0, float r1) {
  uint32_t f[14];
#pragma unroll
  for (int j = 0; j < 14; j++) f[j] = pack(x[2 * j] * (j & 1 ? r1 : r0), x[2 * j + 1] * (j & 1 ? r1 : r0));
  wg_fence();
#pragma unroll
  for (int ks = 0; ks < 3; ks++) wgmma_rs56(y, f[4 * ks], f[4 * ks + 1], f[4 * ks + 2], f[4 * ks + 3], mkdesc(wphi, ks * 2048, 1024, 1024, 1), ks);
  wgmma_rs56(y, f[12], f[13], 0u, 0u, mkdesc(wphi, 3 * 2048, 1024, 1024, 1), 1);
  wg_commit();
}
__device__ __forceinline__ void ln_stats(uint32_t (&xw)[4][4], float* sLN, int warp, int lane, uint4* dst) {
  const int g = lane >> 2; const bool full = warp < 4;
  float s0 = 0.f, s1 = 0.f;
#pragma unroll
  for (int u = 0; u < 4; u++) {
    s0 += (blo(xw[u][0]) + bhi(xw[u][0])) + (blo(xw[u][2]) + bhi(xw[u][2]));
    s1 += (blo(xw[u][1]) + bhi(xw[u][1])) + (blo(xw[u][3]) + bhi(xw[u][3]));
  }
  const float rc = full ? 1.f / 64 : 1.f / 48;
  s0 = qsum(s0); s1 = qsum(s1);
  const float a0 = s0 * rc, a1 = s1 * rc;
  float v0 = 0.f, v1 = 0.f;
#pragma unroll
  for (int u = 0; u < 4; u++)
    if (u < 3 || full) {
#pragma unroll
      for (int k = 0; k < 4; k += 2) {
        float a = blo(xw[u][k]) - a0, b = bhi(xw[u][k]) - a0, c2 = blo(xw[u][k + 1]) - a1, d2 = bhi(xw[u][k + 1]) - a1;
        v0 += a * a + b * b; v1 += c2 * c2 + d2 * d2;
      }
    }
  v0 = qsum(v0); v1 = qsum(v1);
  if ((lane & 3) == 0) *(float4*)(sLN + (g * 8 + warp) * 4) = make_float4(s0, v0, s1, v1);
  if (warp) { asm volatile("bar.arrive 7, 256;" ::: "memory"); return; }
  asm volatile("bar.sync 7, 256;" ::: "memory");
  const float4 ea = *(const float4*)(sLN + (g * 8 + (lane & 3)) * 4), eb = *(const float4*)(sLN + (g * 8 + 4 + (lane & 3)) * 4);
  const float m0 = qsum(ea.x + eb.x) * (1.f / 448), m1 = qsum(ea.z + eb.z) * (1.f / 448);
  const float d0 = ea.x * (1.f / 64) - m0, d1 = eb.x * (1.f / 48) - m0, d2 = ea.z * (1.f / 64) - m1, d3 = eb.z * (1.f / 48) - m1;
  v0 = qsum(ea.y + eb.y + 64.f * d0 * d0 + 48.f * d1 * d1); v1 = qsum(ea.w + eb.w + 64.f * d2 * d2 + 48.f * d3 * d3);
  if ((lane & 3) == 0) stll(dst + g, tg(__float_as_uint(m0), 1), __float_as_uint(rsqrtf(v0 * (1.f / 448) + 1e-5f)), __float_as_uint(m1), __float_as_uint(rsqrtf(v1 * (1.f / 448) + 1e-5f)));
}

__global__ void CLUSTER __launch_bounds__(384, 1)
fused_kernel(const __grid_constant__ CUtensorMap mQKV, const __grid_constant__ CUtensorMap mWO, const __grid_constant__ CUtensorMap mW1,
             const __grid_constant__ CUtensorMap mW1b, const __grid_constant__ CUtensorMap mW2, const __grid_constant__ CUtensorMap mW2b,
             const __grid_constant__ CUtensorMap mX, const __nv_bfloat16* __restrict__ wqkv, const __nv_bfloat16* __restrict__ wphi,
             const __nv_bfloat16* __restrict__ wo, const __nv_bfloat16* __restrict__ w1, const __nv_bfloat16* __restrict__ b1,
             const __nv_bfloat16* __restrict__ w2, const __nv_bfloat16* __restrict__ b2, __nv_bfloat16* __restrict__ out) {
  extern __shared__ __align__(1024) uint8_t sm[];
  const uint32_t sb = s2u(sm);
  const int tid = threadIdx.x, warp = __shfl_sync(~0u, tid >> 5, 0), lane = tid & 31,
            t = MAPPING ? (blockIdx.x >> 4) * 2 + (blockIdx.x & 1) : blockIdx.x >> 3, c = MAPPING ? (blockIdx.x >> 1) & 7 : blockIdx.x & 7;
  const uint32_t bfull = sb + OFF_BAR, bempty = bfull + 8 * NST;

#define XOFF(l) ((t * 128 + c * 16 + ((l) >> 2)) * 448 + warp * 16 + 2 * ((l) & 3))
  if (warp < 8) { MARK(0); GT(19); }
  if (tid == 256) {
    for (int s = 0; s < NST; s++) { mbar_init(bfull + 8 * s, 1); mbar_init(bempty + 8 * s, MC ? 16 : 8); }
    mbar_init(bempty + 8 * NST, 1);
    asm volatile("fence.mbarrier_init.release.cluster;" ::: "memory");
    fence_async();
    mbar_expect(bempty + 8 * NST, 114688);
    for (int i = 0; i < 7; i++)
      asm volatile("cp.async.bulk.tensor.2d.shared::cluster.global.mbarrier::complete_tx::bytes [%0], [%1, {%3, %4}], [%2];"
                   ::"r"(sb + 2 * STAGE + i * 16384), "l"(&mX), "r"(bempty + 8 * NST), "r"(64 * i), "r"(128 * t) : "memory");
  }
  asm volatile("barrier.cluster.arrive.release.aligned; barrier.cluster.wait.acquire.aligned;" ::: "memory");
  if (warp >= 8) {
    asm volatile("setmaxnreg.dec.sync.aligned.u32 24;");
    auto issue = [&](int i, int s) {
      const uint32_t dst = sb + s * STAGE, bar = bfull + 8 * s;
      mbar_expect(bar, STAGE);
#pragma unroll 1
      for (int rk = MC ? (blockIdx.x & 1) : 0; rk < (MC ? (blockIdx.x & 1) + 1 : 2); rk++)
      if (i < 4) tma2d(dst + rk * 14336, &mQKV, 448 + 448 * rk + 56 * c, 112 * i, bar);
      else if (i < 8) tma2d(dst + rk * 14336, i < 6 ? &mQKV : &mWO, (i < 6 ? 56 : 64) * c, 224 * (i & 1) + 112 * rk, bar);
      else if (i < 15) { const int k0 = 64 * ((i - 8 + c) % 7) + 32 * rk;
        tma3d(dst + rk * 12288, &mW1, 0, k0, 3 * c, bar); tma2d(dst + 24576 + rk * 2048, &mW1b, 1536 + 32 * c, k0, bar); }
      else { tma2d(dst + rk * 12288, &mW2, 64 * (i - 15), 192 * c + 96 * rk, bar); tma2d(dst + 24576 + rk * 2048, &mW2b, 64 * (i - 15), 1536 + 32 * c + 16 * rk, bar); }
    };
    auto colsum = [&](int job) {
        const int ld4 = job < 112 ? 448 : 336;
        const uint2* wp = (job < 112 ? (const uint2*)w1 + job * 4 : (const uint2*)wqkv + (job - 112) * 4) + (lane >> 2) * ld4 + (lane & 3);
        float s0 = 0.f, s1 = 0.f, s2 = 0.f, s3 = 0.f;
#pragma unroll 8
        for (int i = 0; i < 56; i++) { const uint2 v = __ldg(wp + i * 8 * ld4); s0 += blo(v.x); s1 += bhi(v.x); s2 += blo(v.y); s3 += bhi(v.y); }
#pragma unroll 1
        for (int o = 4; o < 32; o <<= 1) { s0 += __shfl_xor_sync(~0u, s0, o); s1 += __shfl_xor_sync(~0u, s1, o); s2 += __shfl_xor_sync(~0u, s2, o); s3 += __shfl_xor_sync(~0u, s3, o); }
        if (lane < 4) stll(g_CS + job * 4 + lane, tg(__float_as_uint(s0), 1), __float_as_uint(s1), __float_as_uint(s2), __float_as_uint(s3));
      };
    if (warp == 8) {
      int s = 0; uint32_t ph = 1;
      for (int n = 0; n < 44; n++) {
        if (n == PACE) asm volatile("bar.sync 2, 288;" ::: "memory");
        mbar_wait(bempty + 8 * s, ph);
        if (n == 22) {
          uint32_t v = 0;
#pragma unroll 1
          for (int it = 0; it < SPIN && v < 32; it++) asm volatile("ld.acquire.gpu.global.u32 %0, [%1];" : "=r"(v) : "l"(g_WQF + c) : "memory");
          asm volatile("fence.proxy.async.global;" ::: "memory");
        }
        if (lane == 0) {
          if (n >= 22 && n < 28) {
            mbar_expect(bfull + 8 * s, STAGE);
            asm volatile("cp.async.bulk.shared::cluster.global.mbarrier::complete_tx::bytes [%0], [%1], %2, [%3];"
                         ::"r"(sb + s * STAGE), "l"(g_WQ + c * 10752 + (n - 22) * (STAGE / 16)), "r"(STAGE), "r"(bfull + 8 * s) : "memory");
          } else issue(n >= 22 ? n - 22 : n, s);
        }
        __syncwarp();
        if (++s == NST) { s = 0; ph ^= 1; }
      }
    } else if (warp == 9) {
      mbar_wait(bempty + 8 * NST, 0);
      if (lane == 0) l2pf((const uint8_t*)wqkv + blockIdx.x * 9408, 9408);
      mbar_wait(bfull + 8 * PFS, 0);
      if (lane == 0) {
        l2pf((const uint8_t*)wo + blockIdx.x * 3136, 3136);
        l2pf((const uint8_t*)w1 + blockIdx.x * 12544, 12544);
        l2pf((const uint8_t*)w2 + blockIdx.x * 12544, 12544);
      }
      if (blockIdx.x < 112) colsum(blockIdx.x);
      asm volatile("bar.sync 6, 96;" ::: "memory");
#pragma unroll 1
      for (int i = 0; i < 4; i++) {
        const int e = lane < 28 ? lane + 28 * (i & 1) : 0;
        const bool ok = i < 2 || (e < 48 && (e & 15) < 14);
        const int e4 = i < 2 ? (e < 48 ? 48 * c + e : 336 + 8 * c + e) : ok ? 448 + 112 * (e >> 4) + 14 * c + (e & 15) : 448;
        uint4 cv[1];
        ll_issue<0, 1>(cv, g_CS + e4, 0); ll_check<0, 1, false>(cv, g_CS + e4, 0, 1u);
        const uint2 bb = __ldg((const uint2*)b1 + (i < 2 ? e4 : 0));
        const uint32_t h0 = pack(__uint_as_float(cv[0].x), __uint_as_float(cv[0].y)), h1 = pack(__uint_as_float(cv[0].z), __uint_as_float(cv[0].w));
        const uint32_t l0 = pack(__uint_as_float(cv[0].x) - blo(h0), __uint_as_float(cv[0].y) - bhi(h0)), l1 = pack(__uint_as_float(cv[0].z) - blo(h1), __uint_as_float(cv[0].w) - bhi(h1));
#pragma unroll 1
        for (int j = 0; j < (i < 2 ? 5 : 3); j++) {
          const int r = i < 2 ? j : j + 5;
          const uint32_t ad = sb + OFF_CB + (e >> 3) * 512 + r * 64 + ((((e >> 1) ^ (r >> 1)) & 3) << 4) + (e & 1) * 8;
          sts32(ad, j < 2 ? h0 : j == 2 ? l0 : bb.x); sts32(ad + 4, j < 2 ? h1 : j == 2 ? l1 : bb.y);
        }
        if (i & 1) { fence_async(); if (i == 1) asm volatile("bar.arrive 4, 288;" ::: "memory"); else asm volatile("bar.arrive 8, 288;" ::: "memory"); }
      }
    } else if (warp >= 10) {
      const int h = warp - 10;
      uint32_t wv[13];
#pragma unroll
      for (int i = 0; i < 13; i++) { const int e = lane + 32 * i; wv[i] = e < 392 ? __ldg((const uint32_t*)wphi + (2 * c + h) * 392 + e) : 0u; }
#pragma unroll 1
      for (int e = h * 32 + lane; e < 672; e += 64) sts128(sb + OFF_WPHI + e * 16, 0, 0, 0, 0);
      asm volatile("bar.arrive 6, 96;" ::: "memory");
#pragma unroll 1
      for (int i = 0; i < 4; i++) sts128(sb + OFF_PHIK + sw128(h * 128 + i * 32 + lane, 56), 0, 0, 0, 0);
      asm volatile("bar.sync 5, 64;" ::: "memory");
#pragma unroll
      for (int i = 0; i < 13; i++) {
        const int e = lane + 32 * i, d = e / 14, f2 = 2 * (e - 14 * d), k = 28 * h + d;
        if (e < 392) {
          if (f2 < 24) sts32(sb + OFF_WPHI + sw128(k, 32 * h + f2), wv[i]);
          else { sts16(sb + OFF_WPHI + sw128(k, 2 * f2 - 24 + h), wv[i]); sts16(sb + OFF_WPHI + sw128(k, 2 * f2 - 22 + h), wv[i] >> 16); }
        }
      }
      fence_async();
      asm volatile("bar.arrive 3, 320;" ::: "memory");
      mbar_wait(bfull + 8 * 5, 0);
#pragma unroll 2
      for (int e = t * 672 + h * 32 + lane; e < t * 672 + 672; e += 64) {
        const int r = e >> 3, st = r / 224, rr = r - st * 224, ch = (e & 7) ^ (rr & 7);
        const int k = st < 4 ? 112 * st + (rr >= 112 ? rr - 112 : rr) : 224 * (st - 4) + rr, col = (st < 4 ? (rr >= 112 ? 896 : 448) : 0) + 56 * c + 8 * ch;
        g_WQ[c * 10752 + e] = ch < 7 ? __ldg((const uint4*)(wqkv + k * 1344 + col)) : make_uint4(0, 0, 0, 0);
      }
      __syncwarp();
      if (lane == 0) asm volatile("red.release.gpu.global.add.u32 [%0], 1;" ::"l"(g_WQF + c) : "memory");
      if (h == 0 && blockIdx.x < 84) colsum(112 + blockIdx.x);
    }
  } else {
  asm volatile("setmaxnreg.inc.sync.aligned.u32 240;");

  const int wg = warp >> 2, g = lane >> 2, q = lane & 3;
  const int row0 = warp * 16 + g;
#define PTRS const int ln_ = laneid(); \
  uint4* const fm = g_F + ((t * 8 + warp) * 28) * 32 + ln_;            \
  uint4* const fr = g_F + ((t * 8 + c) * 28 + warp) * 32 + ln_;        \
  uint4* const sf = fm + (7 * (c >> 1) + 4 * (c & 1)) * 32;             \
  uint2* const f2 = (uint2*)(fm - ln_) + ln_;                           \
  uint2* const sh = f2 + (7 * (c >> 1) + 3) * 64 + 32 * (c & 1);        \
  uint32_t* const hme = g_H + (t * 8 + warp) * 8 + c; \
  const uint32_t* const hrow = g_H + (t * 8 + warp) * 8 + (ln_ & 7); \
  (void)fm; (void)fr; (void)sf; (void)f2; (void)sh; (void)hme; (void)hrow;
  float* sLN = (float*)(sm + OFF_V);
  const uint32_t sPK = sb + OFF_PHIK, sV = sb + OFF_V, d16 = (sb & 0x3FFFF) >> 4;
    uint32_t xw[4][4];
#pragma unroll
  for (int i = 0; i < 16; i++) xw[i >> 2][i & 3] = 0;
  int cs = 0, rs = 0; uint32_t cph = 0;
  auto acquire = [&]() -> uint32_t { mbar_wait(bfull + 8 * cs, cph); const uint32_t a = d16 + cs * (STAGE >> 4); if (++cs == NST) { cs = 0; cph ^= 1; } return a; };
  int nrel = 44 - NST;
  auto release = [&]() { if (lane < 1 + MC && nrel > 0) mbar_arrive_cl(bempty + 8 * rs, lane); nrel--; if (++rs == NST) rs = 0; };

#define RISSUE(m, P, XA, XB, BA, BB) { ll_issue<0, 8>(P, pr + (m) * 256, 896); \
      { const uint4 v_ = ldll(fr + X1 + (m) * 256); XA = make_uint2(v_.x, v_.y); XB = make_uint2(v_.z, v_.w); } \
      const uint32_t* bp = (const uint32_t*)(b2 + 128 * (m) + 16 * warp) + (ln_ & 3); BA = __ldg(bp); BB = __ldg(bp + 4); }
#define REDU(m, P, XA, XB, BA, BB) { ll_check<0, 8, false>(P, pr + (m) * 256, 896, ptag); \
      float e[8] = {blo(XA.x) + blo(BA), bhi(XA.x) + bhi(BA), blo(XA.y) + blo(BA), bhi(XA.y) + bhi(BA), blo(XB.x) + blo(BB), bhi(XB.x) + bhi(BB), blo(XB.y) + blo(BB), bhi(XB.y) + bhi(BB)}; \
      _Pragma("unroll") for (int i = 0; i < 8; i++) { e[0] += blo(P[i].x); e[1] += bhi(P[i].x); e[2] += blo(P[i].y); e[3] += bhi(P[i].y); \
        e[4] += blo(P[i].z); e[5] += bhi(P[i].z); e[6] += blo(P[i].w); e[7] += bhi(P[i].w); } \
      xw[m][0] = pack(e[0], e[1]); xw[m][1] = pack(e[2], e[3]); xw[m][2] = pack(e[4], e[5]); xw[m][3] = pack(e[6], e[7]); }
#define RPUB(m) stll(fr + XR + (m) * 256, tg(xw[m][0], 0), xw[m][1], xw[m][2], xw[m][3]);
#define RLAST(ptag_, hv) { const uint32_t ptag = ptag_; const uint4* pr = g_P + ((t * 8 + c) * 8 * 28 + warp) * 32 + ln_; uint4 p[8]; uint2 xa, xb; uint32_t ba, bb; \
      hint_wait(g_H + (t * 8 + c) * 8 + (ln_ & 7), hv); RISSUE(3, p, xa, xb, ba, bb) REDU(3, p, xa, xb, ba, bb) }
#pragma unroll 1
  for (int L = 0; L < 2; L++) {
    const uint32_t tag = 1 - L;
    uint32_t phq[2][2][7];
    const uint32_t hs = 10 * L;
    {
      PTRS
      uint4 a[28];
      const uint4* pa = fm + XR;
      uint32_t fa = 0, fb = 0;
      float r0 = 1.f, r1 = 1.f;
      if (L == 0) {
        hint_post(hme, 1, lane);
        mbar_wait(bempty + 8 * NST, 0);
        MARK(1);
        const int row = warp * 16 + (ln_ & 15);
        const uint32_t xb = sb + 2 * STAGE + row * 128;
        float cs_[4][4] = {};
#pragma unroll
        for (int ks = 0; ks < 28; ks++) { a[ks] = ldsm4(xb + (ks >> 2) * 16384 + (((2 * (ks & 3) + (ln_ >> 4)) ^ (row & 7)) << 4)); mma16816(cs_[ks & 3], a[ks], 0x3F803F80u, 0x3F803F80u); }
        if (c < 7) {
#pragma unroll
          for (int u = 0; u < 4; u++) { const uint4 v = ldsm4(xb + c * 16384 + (((2 * u + (ln_ >> 4)) ^ (row & 7)) << 4)); stll(fm + XR + 128 * c + u * 32, tg(v.x, tag), v.y, v.z, v.w); }
        }
        const float m0 = ((cs_[0][0] + cs_[1][0]) + (cs_[2][0] + cs_[3][0])) * (1.f / 448), m1 = ((cs_[0][2] + cs_[1][2]) + (cs_[2][2] + cs_[3][2])) * (1.f / 448);
        const uint32_t mb0 = pack(m0, m0), mb1 = pack(m1, m1);
        asm volatile("bar.arrive 2, 288;" ::"r"(mb0) : "memory");
#pragma unroll
        for (int ks = 0; ks < 28; ks++) {
          a[ks].x = bsub(a[ks].x, mb0); a[ks].y = bsub(a[ks].y, mb1); a[ks].z = bsub(a[ks].z, mb0); a[ks].w = bsub(a[ks].w, mb1);
        }
        r0 = m0 - blo(mb0); r1 = m1 - blo(mb1);
      } else {
        ll_issue<0, 14>(a, pa, 32);
        if (wg == 0) { RLAST(1u, 10u) xw[3][0] = tg(xw[3][0], 0); RPUB(3) } else { xw[3][0] = xw[3][1] = xw[3][2] = xw[3][3] = 0; }
        MARK(20);
        ll_issue<14, 7>(a, pa, 32);
        ln_stats(xw, sLN, warp, lane, g_S2 + (t * 8 + c) * 8);
      }
      MARK(2 + L * 19);
      float ak[28], av[28], aq[28], pp[28];
#define KVSTAGE(i) { if (L) ll_check<7 * i, 7, false>(a, pa, 32, tag); const uint32_t st = acquire(); wg_fence(); \
      _Pragma("unroll") for (int ks = 0; ks < 7; ks++) { const uint4 f = a[7 * i + ks]; \
        wgmma_rs56(ak, f.x, f.y, f.z, f.w, mkdesc(st, ks * 2048, 1024, 1024, 1), i | ks); \
        wgmma_rs56(av, f.x, f.y, f.z, f.w, mkdesc(st, 14336 + ks * 2048, 1024, 1024, 1), i | ks); } \
      wg_commit(); if (i > 0) { wg_wait<1>(); release(); } }
      KVSTAGE(0) KVSTAGE(1)
      uint4 sv[1];
      const uint4* ps = g_S2 + (t * 8 + warp) * 8 + (ln_ >> 2);
      if (L) { ll_issue<21, 7>(a, pa, 32); ll_issue<0, 1>(sv, ps, 0); }
      else {
        float c0[2][4] = {}, c1[2][4] = {};
#pragma unroll
        for (int ks = 0; ks < 28; ks++) { mma16816(c0[ks & 1], a[ks], a[ks].x, a[ks].z); mma16816(c1[ks & 1], a[ks], a[ks].y, a[ks].w); }
        const int src = (ln_ & 28) | (g >> 1);
        const float q0 = __shfl_sync(~0u, (g & 1) ? c0[0][1] + c0[1][1] : c0[0][0] + c0[1][0], src), q1 = __shfl_sync(~0u, (g & 1) ? c1[0][3] + c1[1][3] : c1[0][2] + c1[1][2], src);
        r0 = rsqrtf(fmaxf(q0 * (1.f / 448) - r0 * r0, 0.f) + 1e-5f); r1 = rsqrtf(fmaxf(q1 * (1.f / 448) - r1 * r1, 0.f) + 1e-5f);
      }
      KVSTAGE(2) KVSTAGE(3)
      if (L) {
        ll_check<0, 1, false>(sv, ps, 0, 1u);
        const float m0 = -__uint_as_float(sv[0].x), m1 = -__uint_as_float(sv[0].z), h0 = blo(pack(m0, 0.f)), h1 = blo(pack(m1, 0.f));
        r0 = __uint_as_float(sv[0].y); r1 = __uint_as_float(sv[0].w);
        fa = q == 2 ? pack(0.f, h0) : q == 3 ? pack(m0 - h0, h0) : 0u; fb = q == 2 ? pack(0.f, h1) : q == 3 ? pack(m1 - h1, h1) : 0u;
      } else {
        asm volatile("bar.sync 3, 320;" ::: "memory");
      }
      wg_fence();
      wgmma_rs56(ak, fa, fb, 0u, 0u, mkdesc(d16, OFF_CB + 1024, 512, 0, 2), 1);
      wgmma_rs56(av, fa, fb, 0u, 0u, mkdesc(d16, OFF_CB + 2048, 512, 0, 2), 1);
      wg_commit();
      wg_wait<0>(); release(); regfence(ak); regfence(av);
      MARK(3 + L * 19);
      phi_gemm(ak, pp, d16 + (OFF_WPHI >> 4), r0, r1);
#pragma unroll
      for (int j = 0; j < 7; j++) {
        const int n = 8 * j + 2 * q, n2 = n < 28 ? n : n + 4;
        sts32(sV + sw128(row0, n2), pack(av[4 * j] * r0, av[4 * j + 1] * r0)); sts32(sV + sw128(row0 + 8, n2), pack(av[4 * j + 2] * r1, av[4 * j + 3] * r1));
      }
      { const int n2 = 28 + 2 * (q & 1) + 32 * (q >> 1); const uint32_t v = (q & 1) ? 0u : 0x3F80u; sts32(sV + sw128(row0, n2), v); sts32(sV + sw128(row0 + 8, n2), v); }
      wg_wait<0>(); regfence(pp);
      hedgehog(pp, [&](int r, int h, int p, uint32_t v) { sts32(sPK + h * 16384 + sw128(row0 + 8 * r, 8 * p + 2 * q), v); }, [] {});
      fence_async();
      bar_cons();
      MARK(4 + L * 19);
      float kv[16];
      wg_fence();
#pragma unroll
      for (int ks = 0; ks < 8; ks++) wgmma_ss32(kv, mkdesc(d16 + wg * 1024, OFF_PHIK + ks * 2048, 1024, 1024, 1), mkdesc(d16 + wg * 4, OFF_V + ks * 2048, 1024, 1024, 1), ks);
      wg_commit(); wg_wait<0>(); regfence(kv);
      const int ln2 = laneid();
#pragma unroll
      for (int u = 0; u < 4; u++) {
        float e[4];
#pragma unroll
        for (int i = 0; i < 4; i++) e[i] = kv[4 * u + i];
        stll(g_KVP + (c * 16 + t) * 1024 + wg * 512 + u * 128 + (warp & 3) * 32 + ln2, tg(__float_as_uint(e[0]), tag), __float_as_uint(e[1]), __float_as_uint(e[2]), __float_as_uint(e[3]));
      }
      MARK(5 + L * 19);
      uint4 k4[4];
      const uint4* pk = g_KVP + (c * 16 + 4 * (ln2 & 3)) * 1024 + 64 * t + warp * 8 + (ln2 >> 2);
#pragma unroll
      for (int i = 0; i < 2; i++) {
        const uint32_t st = acquire(); wg_fence();
#pragma unroll
        for (int ks = 0; ks < 14; ks++) { const uint4 f = a[14 * i + ks]; wgmma_rs56(aq, f.x, f.y, f.z, f.w, mkdesc(st, ks * 2048, 1024, 1024, 1), i | ks); }
        if (i == 1) wgmma_rs56(aq, fa, fb, 0u, 0u, mkdesc(d16, OFF_CB, 512, 0, 2), 1);
        wg_commit();
        if (i == 1) ll_issue<0, 4>(k4, pk, 1024);
      }
      ll_check<0, 4, false>(k4, pk, 1024, tag);
      float s0 = 0, s1 = 0, s2 = 0, s3 = 0;
#pragma unroll
      for (int i = 0; i < 4; i++) { s0 += __uint_as_float(k4[i].x); s1 += __uint_as_float(k4[i].y); s2 += __uint_as_float(k4[i].z); s3 += __uint_as_float(k4[i].w); }
      s0 = qsum(s0); s1 = qsum(s1); s2 = qsum(s2); s3 = qsum(s3);
      if (q == 0) stll2(g_KVR + c * 1024 + 64 * t + warp * 8 + (ln2 >> 2), tg(pack(s0, s1), tag), pack(s2, s3));
      MARK(6 + L * 19);
      wg_wait<0>(); release(); release(); regfence(aq);
      phi_gemm(aq, pp, d16 + (OFF_WPHI >> 4), r0, r1);
      bar_cons();
#pragma unroll
      for (int i = 0; i < 4; i++) sts128(sV + warp * 2048 + (lane + i * 32) * 16, 0, 0, 0, 0);
      wg_wait<0>(); regfence(pp);
      uint2 r[4];
      const uint2* pr = g_KVR + c * 1024 + wg * 512 + (warp & 3) * 32 + ln2;
      hedgehog(pp, [&](int r, int h, int p, uint32_t v) { phq[r][h][p] = v; }, [&] {
#pragma unroll
        for (int u = 0; u < 4; u++) r[u] = ldll2(pr + u * 128); });
      MARK(7 + L * 19);
#pragma unroll 1
      for (int it = 0; it < SPIN; it++) {
        if (!__any_sync(~0u, ((r[0].x ^ tag) | (r[1].x ^ tag) | (r[2].x ^ tag) | (r[3].x ^ tag)) & 1)) break;
#pragma unroll
        for (int u = 0; u < 4; u++) r[u] = ldll2(pr + u * 128);
      }
#pragma unroll
      for (int u = 0; u < 4; u++) {
        const int d = 8 * u + 2 * q;
        if (d < 28) { sts32(sV + sw128(row0, 28 * wg + d), r[u].x); sts32(sV + sw128(row0 + 8, 28 * wg + d), r[u].y); }
        else if (d == 28) {
#pragma unroll
          for (int j = 0; j < 4; j++) { sts16(sV + sw128(row0, 56 + 2 * j + wg), r[u].x); sts16(sV + sw128(row0 + 8, 56 + 2 * j + wg), r[u].y); }
        }
      }
      fence_async();
      bar_cons();
      MARK(8 + L * 19);
      float o[32];
      wg_fence();
#pragma unroll
      for (int ks = 0; ks < 8; ks++) {
        const int h = ks >> 2, p = 2 * (ks & 3);
        wgmma_rs64(o, phq[0][h][p], phq[1][h][p], p < 6 ? phq[0][h][p < 6 ? p + 1 : 0] : 0u, p < 6 ? phq[1][h][p < 6 ? p + 1 : 0] : 0u, mkdesc(d16, OFF_V + ks * 2048, 1024, 1024, 1), ks);
      }
      wg_commit(); wg_wait<0>(); regfence(o);
      const float iA0 = rcp(o[28] + 1e-6f), iB0 = rcp(o[29] + 1e-6f), iA1 = rcp(o[30] + 1e-6f), iB1 = rcp(o[31] + 1e-6f);
      uint32_t w[14];
      { PTRS
#pragma unroll
      for (int j = 0; j < 7; j++) {
        const bool hb = 8 * j + 2 * q >= 28; const float i0 = hb ? iB0 : iA0, i1 = hb ? iB1 : iA1;
        w[2 * j] = pack(o[4 * j] * i0, o[4 * j + 1] * i0); w[2 * j + 1] = pack(o[4 * j + 2] * i1, o[4 * j + 3] * i1);
        if (j == 0 || ((j ^ c) & 1) == 0) w[2 * j] = tg(w[2 * j], tag);
      }
      slice_store(sf + OO, sh + 2 * OO, w, c & 1);
      hint_post(hme, hs + 2, lane); }
    }
    MARK(9 + L * 19);
    uint4 xr[4];
    if (c < 7) {
      PTRS
      ll_issue<0, 4>(xr, fm + XR + 128 * c, 32);
      uint4 a[28];
      const uint4* pa = fm + OO;
      hint_wait(hrow, hs + 2);
      MARK(10 + L * 19);
      ll_issue<0, 28, true>(a, pa, 32, f2 + 2 * OO);
      float y[32];
      uint32_t st;
#define WOSTEP(i) { ll_check<7 * i, 7, true>(a, pa, 32, tag, f2 + 2 * OO); if (!(i & 1)) st = acquire(); wg_fence(); \
      _Pragma("unroll") for (int ks = 0; ks < 7; ks++) { const uint4 f = a[7 * i + ks]; \
        wgmma_rs64(y, f.x, f.y, f.z, f.w, mkdesc(st, ((i & 1) * 7 + ks) * 2048, 1024, 1024, 1), i | ks); } wg_commit(); }
      WOSTEP(0) WOSTEP(1) WOSTEP(2) WOSTEP(3)
      ll_check<0, 4, false>(xr, fm + XR + 128 * c, 32, tag);
      wg_wait<0>(); regfence(y);
      MARK(11 + L * 19);
#pragma unroll
      for (int u = 0; u < 4; u++) {
        xr[u].x = tg(pack(blo(xr[u].x) + y[8 * u], bhi(xr[u].x) + y[8 * u + 1]), tag); xr[u].y = pack(blo(xr[u].y) + y[8 * u + 2], bhi(xr[u].y) + y[8 * u + 3]);
        xr[u].z = pack(blo(xr[u].z) + y[8 * u + 4], bhi(xr[u].z) + y[8 * u + 5]); xr[u].w = pack(blo(xr[u].w) + y[8 * u + 6], bhi(xr[u].w) + y[8 * u + 7]);
        stll(fm + X1 + 128 * c + u * 32, xr[u].x, xr[u].y, xr[u].z, xr[u].w);
      }
      hint_post(hme, hs + 3, lane);
    } else {
      PTRS
      hint_post(hme, hs + 3, lane);
      acquire(); acquire();
      hint_wait(g_H + (t * 8 + warp) * 8, hs + 3);
      ll_issue<0, 4>(xr, fm + X1, 32); ll_check<0, 4, false>(xr, fm + X1, 32, tag);
      MARK(10 + L * 19); MARK(11 + L * 19);
    }
    uint32_t hf[56];
    float rr0, rr1;
    {
      PTRS
      uint4 a[28];
      const uint4* pa = fm + X1;
      auto grp = [&](int i) -> const uint4* { const int k = i + c; return pa + ((k >= 7 ? k - 7 : k) - i) * 128; };
#pragma unroll
      for (int u = 0; u < 4; u++) a[u] = xr[u];
      float y[96], z[16];
#define F1STAGE(i) { if (i > 0) ll_check<4 * i, 4, false>(a, grp(i), 32, tag); const uint32_t st = acquire(); wg_fence(); \
      _Pragma("unroll") for (int ks = 0; ks < 4; ks++) { const uint4 f = a[4 * i + ks]; \
        wgmma_rs192(y, f.x, f.y, f.z, f.w, mkdesc(st, (ks >> 1) * 12288 + (ks & 1) * 2048, 4096, 1024, 1), i | ks); \
        wgmma_rs32(z, f.x, f.y, f.z, f.w, mkdesc(st, 24576 + ks * 1024, 512, 512, 2), i | ks); } \
      wg_commit(); if (i > 0) { wg_wait<1>(); release(); if (i < 4) ll_issue<(i < 4 ? 4 * i + 12 : 0), 4>(a, grp(i + 3), 32); } }
      F1STAGE(0)
      hint_wait(hrow, hs + 3);
      MARK(12 + L * 19);
      ll_issue<4, 4>(a, grp(1), 32); ll_issue<8, 4>(a, grp(2), 32); ll_issue<12, 4>(a, grp(3), 32);
      if (c < 7) {
        float s0 = 0.f, s1 = 0.f, v0 = 0.f, v1 = 0.f;
#pragma unroll
        for (int u = 0; u < 4; u++) { s0 += (blo(xr[u].x) + bhi(xr[u].x)) + (blo(xr[u].z) + bhi(xr[u].z)); s1 += (blo(xr[u].y) + bhi(xr[u].y)) + (blo(xr[u].w) + bhi(xr[u].w)); }
        s0 = qsum(s0) * (1.f / 64); s1 = qsum(s1) * (1.f / 64);
#pragma unroll
        for (int u = 0; u < 4; u++) {
          const float d0 = blo(xr[u].x) - s0, d1 = bhi(xr[u].x) - s0, d2 = blo(xr[u].z) - s0, d3 = bhi(xr[u].z) - s0;
          const float d4 = blo(xr[u].y) - s1, d5 = bhi(xr[u].y) - s1, d6 = blo(xr[u].w) - s1, d7 = bhi(xr[u].w) - s1;
          v0 += (d0 * d0 + d1 * d1) + (d2 * d2 + d3 * d3); v1 += (d4 * d4 + d5 * d5) + (d6 * d6 + d7 * d7);
        }
        v0 = qsum(v0); v1 = qsum(v1);
        if (q == 0) stll(g_ST + ((t * 8 + warp) * 8 + c) * 8 + (ln_ >> 2), tg(__float_as_uint(s0), tag), __float_as_uint(v0), __float_as_uint(s1), __float_as_uint(v1));
      }
      if (LAG < 2) release();
      if (LAG < 1) release();
#define LAGREL if (LAG > 0) release(); if (LAG > 1) release();
      F1STAGE(1) MARK(13 + L * 19); F1STAGE(2) F1STAGE(3)
      uint4 sv[2];
      const uint4* ps = g_ST + ((t * 8 + warp) * 8 + 2 * (laneid() & 3)) * 8 + (laneid() >> 2);
      ll_issue<0, 2>(sv, ps, q < 3 ? 8 : 0);
      F1STAGE(4)
      ll_check<0, 2, false>(sv, ps, q < 3 ? 8 : 0, tag);
      const float wb = q < 3 ? 1.f : 0.f;
      const float ma = __uint_as_float(sv[0].x), mb = __uint_as_float(sv[1].x), mc = __uint_as_float(sv[0].z), md = __uint_as_float(sv[1].z);
      const float m0 = qsum(ma + wb * mb) * (1.f / 7), m1 = qsum(mc + wb * md) * (1.f / 7);
      const float v0 = qsum(__uint_as_float(sv[0].y) + 64.f * (ma - m0) * (ma - m0) + wb * (__uint_as_float(sv[1].y) + 64.f * (mb - m0) * (mb - m0)));
      const float v1 = qsum(__uint_as_float(sv[0].w) + 64.f * (mc - m1) * (mc - m1) + wb * (__uint_as_float(sv[1].w) + 64.f * (md - m1) * (md - m1)));
      const float e0 = v0 * (1.f / 448) + 1e-5f, e1 = v1 * (1.f / 448) + 1e-5f;
      rr0 = 1.f / e0; rr1 = 1.f / e1;
      auto fold = [&](float m, float sd) -> uint32_t {
        const float mh = blo(pack(-m, 0.f)), sh_ = blo(pack(sd, 0.f));
        return q == 0 ? pack(mh, -m - mh) : q == 1 ? pack(mh, sh_) : q == 2 ? pack(sd - sh_, 0.f) : 0u;
      };
      const uint32_t fa = fold(m0, sqrtf(e0)), fb = fold(m1, sqrtf(e1));
      if (L == 0) asm volatile("bar.sync 4, 288;" ::: "memory");
      wg_fence();
      wgmma_rs192(y, fa, fb, 0u, 0u, mkdesc(d16, OFF_CB, 512, 0, 2), 1);
      wgmma_rs32(z, fa, fb, 0u, 0u, mkdesc(d16, OFF_CB + 3072, 512, 0, 2), 1);
      F1STAGE(5) F1STAGE(6)
      wg_wait<0>(); release(); LAGREL regfence(y); regfence(z);
      MARK(14 + L * 19);
#pragma unroll
      for (int j = 0; j < 56; j++) {
        uint32_t r; asm("cvt.rn.relu.bf16x2.f32 %0, %1, %2;" : "=r"(r) : "f"(j < 48 ? y[j < 48 ? 2 * j + 1 : 0] : z[j < 48 ? 0 : 2 * j - 95]), "f"(j < 48 ? y[j < 48 ? 2 * j : 0] : z[j < 48 ? 0 : 2 * j - 96]));
        asm("mul.bf16x2 %0, %1, %1;" : "=r"(hf[j]) : "r"(r));
      }
    }
    MARK(15 + L * 19);
    {
      PTRS
      float ya[32], yb[32];
      uint4* pp = g_P + ((t * 8 + warp) * 8 + c) * 28 * 32 + ln_;
#define F2STORE(j, Y) { regfence(Y); _Pragma("unroll") for (int u = 0; u < 4; u++) \
      stll(pp + (4 * (j) + u) * 32, tg(pack(Y[8 * u] * rr0, Y[8 * u + 1] * rr0), tag), pack(Y[8 * u + 2] * rr1, Y[8 * u + 3] * rr1), \
           pack(Y[8 * u + 4] * rr0, Y[8 * u + 5] * rr0), pack(Y[8 * u + 6] * rr1, Y[8 * u + 7] * rr1)); if ((j) >= 5) hint_post(hme, hs + (4 + (j)), lane); }
#define F2PASS(j, Y, Z) { const uint32_t st = acquire(); wg_fence(); \
      _Pragma("unroll") for (int ks = 0; ks < 14; ks++) wgmma_rs64(Y, hf[4 * ks], hf[4 * ks + 1], hf[4 * ks + 2], hf[4 * ks + 3], mkdesc(st, ks * 2048, 1024, 1024, 1), ks); \
      wg_commit(); if (j > 0) { wg_wait<1>(); release(); F2STORE(j - 1, Z) } }
      const uint4* pr = g_P + ((t * 8 + c) * 8 * 28 + warp) * 32 + ln_;
      uint4 p[8], p2[8]; uint2 xa, xb, xc, xd; uint32_t ba, bb, bc, bd;
      const uint32_t ptag = tag;
      const uint32_t* hred = g_H + (t * 8 + c) * 8 + (ln_ & 7);
      F2PASS(0, ya, yb) F2PASS(1, yb, ya) F2PASS(2, ya, yb) F2PASS(3, yb, ya)
      F2PASS(4, ya, yb)
      RISSUE(0, p, xa, xb, ba, bb)
      F2PASS(5, yb, ya)
      REDU(0, p, xa, xb, ba, bb)
      if (L == 0) { xw[0][0] = tg(xw[0][0], 0); RPUB(0) }
      F2PASS(6, ya, yb)
      RISSUE(1, p, xa, xb, ba, bb)
      wg_wait<0>(); release(); F2STORE(6, ya)
      MARK(16 + L * 19);
      if (L == 0) asm volatile("bar.sync 8, 288;" ::: "memory");
      if (wg) hint_wait(hred, hs + 9);
      RISSUE(2, p2, xc, xd, bc, bd)
      REDU(1, p, xa, xb, ba, bb)
      if (L == 0) { xw[1][0] = tg(xw[1][0], 0); RPUB(1) }
      MARK(17 + L * 19);
      REDU(2, p2, xc, xd, bc, bd)
      if (L == 0) { xw[2][0] = tg(xw[2][0], 0); RPUB(2) }
    }
    MARK(18 + L * 19);
  }
  {
    PTRS
    uint32_t* op = (uint32_t*)(out + XOFF(ln_));
#define OUT(u) { op[u * 64] = xw[u][0]; op[u * 64 + 1792] = xw[u][1]; op[u * 64 + 4] = xw[u][2]; op[u * 64 + 1796] = xw[u][3]; }
    OUT(0) OUT(1) OUT(2)
    if (wg == 0) { RLAST(0u, 20u) OUT(3) }
    else if (warp == 7) {
      if (t == 0 && lane == 0) g_WQF[c] = 0;
      if (lane < 8) stll(g_S2 + (t * 8 + c) * 8 + lane, 0, 0, 0, 0);
      if (lane < 4) { stll(g_CS + blockIdx.x * 4 + lane, 0, 0, 0, 0); if (blockIdx.x < 68) stll(g_CS + 512 + blockIdx.x * 4 + lane, 0, 0, 0, 0); }
    }
  }
  MARK(38); GT(39);
  }
}

typedef CUresult (*EncFn)(CUtensorMap*, CUtensorMapDataType, cuuint32_t, void*, const cuuint64_t*, const cuuint64_t*, const cuuint32_t*, const cuuint32_t*,
                          CUtensorMapInterleave, CUtensorMapSwizzle, CUtensorMapL2promotion, CUtensorMapFloatOOBfill);

extern "C" void kernel_launch(void* const* d_in, const int* in_sizes, int n_in, void* d_out, int out_size) {
  static EncFn enc = nullptr;
  if (!enc) {
    void* fn = nullptr; cudaDriverEntryPointQueryResult qr;
    cudaGetDriverEntryPoint("cuTensorMapEncodeTiled", &fn, cudaEnableDefault, &qr);
    enc = (EncFn)fn;
    cudaFuncSetAttribute(fused_kernel, cudaFuncAttributeMaxDynamicSharedMemorySize, SMEM_BYTES);
  }
  CUtensorMap mQKV, mWO, mW1, mW1b, mW2, mW2b, mX;
  const cuuint32_t es[3] = {1, 1, 1};
  auto enc2 = [&](CUtensorMap* m, void* p, cuuint64_t cols, cuuint64_t rows, cuuint32_t bc, cuuint32_t br) {
    const cuuint64_t dims[2] = {cols, rows}, str[1] = {cols * 2}; const cuuint32_t box[2] = {bc, br};
    enc(m, CU_TENSOR_MAP_DATA_TYPE_BFLOAT16, 2, p, dims, str, box, es, CU_TENSOR_MAP_INTERLEAVE_NONE,
        bc == 64 ? CU_TENSOR_MAP_SWIZZLE_128B : CU_TENSOR_MAP_SWIZZLE_64B, CU_TENSOR_MAP_L2_PROMOTION_L2_128B, CU_TENSOR_MAP_FLOAT_OOB_FILL_NONE);
  };
  enc2(&mQKV, d_in[1], 1344, 448, 64, 112); enc2(&mWO, d_in[3], 448, 448, 64, 112); enc2(&mW1b, d_in[5], 1792, 448, 32, 32);
  enc2(&mX, d_in[0], 448, 2048, 64, 128);
  enc2(&mW2, d_in[7], 448, 1792, 64, 96); enc2(&mW2b, d_in[7], 448, 1792, 64, 16);
  {
    const cuuint64_t dims[3] = {64, 448, 28}, str[2] = {3584, 128}; const cuuint32_t box[3] = {64, 32, 3};
    enc(&mW1, CU_TENSOR_MAP_DATA_TYPE_BFLOAT16, 3, d_in[5], dims, str, box, es, CU_TENSOR_MAP_INTERLEAVE_NONE, CU_TENSOR_MAP_SWIZZLE_128B,
        CU_TENSOR_MAP_L2_PROMOTION_L2_128B, CU_TENSOR_MAP_FLOAT_OOB_FILL_NONE);
  }
  typedef const __nv_bfloat16* BP;
  fused_kernel<<<128, 384, SMEM_BYTES>>>(mQKV, mWO, mW1, mW1b, mW2, mW2b, mX, (BP)d_in[1], (BP)d_in[2], (BP)d_in[3], (BP)d_in[5], (BP)d_in[6], (BP)d_in[7], (BP)d_in[8],
                                         (__nv_bfloat16*)d_out);
}
```

```cpp
#include <cuda_runtime.h>
#include <cuda_bf16.h>
#include <cuda.h>
#include <stdint.h>

constexpr int NST = 6, STAGE = 28672;
constexpr int OFF_PHIK = NST * STAGE;
constexpr int OFF_V = OFF_PHIK + 32768;
constexpr int OFF_WPHI = OFF_V + 16384;
constexpr int OFF_CB = OFF_WPHI + 7168;
constexpr int OFF_BAR = OFF_CB + 3584;
constexpr int SMEM_BYTES = OFF_BAR + 16 * NST + 8;
constexpr int FR = 16 * 8 * 28 * 32;
constexpr int SPIN = 1 << 18;
#define MC 0
#define MAPPING MC
#define MCS
#define MCA(n)
#define CLUSTER
#define LAG 1
#define PFQ 0
#define PFS 3
#define PACE 2

__device__ uint4 g_F[3 * FR];
constexpr int XR = 0, OO = FR, X1 = 2 * FR;
__device__ uint4 g_P[8 * FR];
__device__ uint4 g_ST[16 * 8 * 8 * 8];
__device__ uint4 g_KVP[8 * 16 * 1024];
__device__ uint2 g_KVR[8 * 1024];
__device__ uint4 g_CS[784];
__device__ uint4 g_S2[16 * 8 * 8];
__device__ uint4 g_WQ[8 * 6 * (STAGE / 16)];
__device__ uint32_t g_WQF[8];
__device__ uint32_t g_H[16 * 8 * 8];
#define MARK(i)
#define GT(i)

__device__ __forceinline__ uint32_t s2u(const void* p) { return (uint32_t)__cvta_generic_to_shared(p); }
__device__ __forceinline__ void mbar_init(uint32_t b, uint32_t c) { asm volatile("mbarrier.init.shared::cta.b64 [%0], %1;" ::"r"(b), "r"(c)); }
__device__ __forceinline__ void mbar_expect(uint32_t b, uint32_t tx) { asm volatile("mbarrier.arrive.expect_tx.shared::cta.b64 _, [%0], %1;" ::"r"(b), "r"(tx) : "memory"); }
__device__ __forceinline__ void mbar_arrive_cl(uint32_t b, uint32_t rank) {
  asm volatile("{.reg .b32 r; mapa.shared::cluster.u32 r, %0, %1; mbarrier.arrive.shared::cluster.b64 _, [r];}" ::"r"(b), "r"(rank) : "memory");
}
__device__ __forceinline__ void mbar_wait(uint32_t b, uint32_t ph) {
  uint32_t ok = 0;
#pragma unroll 1
  for (int it = 0; it < SPIN && !ok; it++)
    asm volatile("{.reg .pred p; mbarrier.try_wait.parity.shared::cta.b64 p,[%1],%2; selp.u32 %0,1,0,p;}" : "=r"(ok) : "r"(b), "r"(ph) : "memory");
}
__device__ __forceinline__ void tma2d(uint32_t dst, const CUtensorMap* m, int c0, int c1, uint32_t bar) {
  asm volatile("cp.async.bulk.tensor.2d.shared::cluster.global.mbarrier::complete_tx::bytes" MCS " [%0], [%1, {%3, %4}], [%2]" MCA(5) ";"
               ::"r"(dst), "l"(m), "r"(bar), "r"(c0), "r"(c1), "h"((uint16_t)3) : "memory");
}
__device__ __forceinline__ void tma3d(uint32_t dst, const CUtensorMap* m, int c0, int c1, int c2, uint32_t bar) {
  asm volatile("cp.async.bulk.tensor.3d.shared::cluster.global.mbarrier::complete_tx::bytes" MCS " [%0], [%1, {%3, %4, %5}], [%2]" MCA(6) ";"
               ::"r"(dst), "l"(m), "r"(bar), "r"(c0), "r"(c1), "r"(c2), "h"((uint16_t)3) : "memory");
}
__device__ __forceinline__ void l2pf(const void* p, uint32_t bytes) { asm volatile("cp.async.bulk.prefetch.L2.global [%0], %1;" ::"l"(p), "r"(bytes) : "memory"); }
__device__ __forceinline__ void wg_fence() { asm volatile("wgmma.fence.sync.aligned;" ::: "memory"); }
__device__ __forceinline__ void wg_commit() { asm volatile("wgmma.commit_group.sync.aligned;" ::: "memory"); }
template <int N> __device__ __forceinline__ void wg_wait() { asm volatile("wgmma.wait_group.sync.aligned %0;" ::"n"(N) : "memory"); }
template <int N> __device__ __forceinline__ void regfence(float (&d)[N]) {
#pragma unroll
  for (int i = 0; i < N; i++) asm volatile("" : "+f"(d[i])::"memory");
}
__device__ __forceinline__ void bar_cons() { asm volatile("bar.sync 1, 256;" ::: "memory"); }
__device__ __forceinline__ void fence_async() { asm volatile("fence.proxy.async.shared::cta;" ::: "memory"); }
struct Desc { uint32_t lo, hi; };
__device__ __forceinline__ Desc mkdesc(uint32_t base16, uint32_t off, uint32_t lbo, uint32_t sbo, uint32_t swz) {
  return Desc{base16 + ((off >> 4) | ((lbo >> 4) << 16)), (sbo >> 4) | (swz << 30)};
}
__device__ __forceinline__ uint4 ldll(const uint4* p) {
  uint4 v; asm volatile("ld.relaxed.gpu.global.v4.u32 {%0,%1,%2,%3}, [%4];" : "=r"(v.x), "=r"(v.y), "=r"(v.z), "=r"(v.w) : "l"(p) : "memory"); return v;
}
__device__ __forceinline__ uint2 ldll2(const uint2* p) {
  uint2 v; asm volatile("ld.relaxed.gpu.global.v2.u32 {%0,%1}, [%2];" : "=r"(v.x), "=r"(v.y) : "l"(p) : "memory"); return v;
}
__device__ __forceinline__ void stll(uint4* p, uint32_t x, uint32_t y, uint32_t z, uint32_t w) {
  asm volatile("st.relaxed.gpu.global.v4.u32 [%0], {%1,%2,%3,%4};" ::"l"(p), "r"(x), "r"(y), "r"(z), "r"(w) : "memory");
}
__device__ __forceinline__ void stll2(void* p, uint32_t x, uint32_t y) {
  asm volatile("st.relaxed.gpu.global.v2.u32 [%0], {%1,%2};" ::"l"(p), "r"(x), "r"(y) : "memory");
}
__device__ __forceinline__ int laneid() { int l; asm volatile("mov.u32 %0, %%laneid;" : "=r"(l)); return l; }
__device__ __forceinline__ uint32_t tg(uint32_t w, uint32_t tag) { return (w & ~1u) | tag; }
__device__ __forceinline__ uint32_t pack(float lo, float hi) {
  uint32_t r; asm("cvt.rn.bf16x2.f32 %0, %1, %2;" : "=r"(r) : "f"(hi), "f"(lo)); return r;
}
__device__ __forceinline__ float blo(uint32_t w) { return __uint_as_float(w << 16); }
__device__ __forceinline__ float bhi(uint32_t w) { return __uint_as_float(w & 0xffff0000u); }
__device__ __forceinline__ float ex2(float x) { float r; asm("ex2.approx.ftz.f32 %0, %1;" : "=f"(r) : "f"(x)); return r; }
__device__ __forceinline__ float rcp(float x) { float r; asm("rcp.approx.ftz.f32 %0, %1;" : "=f"(r) : "f"(x)); return r; }
__device__ __forceinline__ float qsum(float v) { v += __shfl_xor_sync(~0u, v, 1); v += __shfl_xor_sync(~0u, v, 2); return v; }
__device__ __forceinline__ void sts32(uint32_t a, uint32_t v) { asm volatile("st.shared.u32 [%0], %1;" ::"r"(a), "r"(v) : "memory"); }
__device__ __forceinline__ void sts16(uint32_t a, uint32_t v) { asm volatile("st.shared.u16 [%0], %1;" ::"r"(a), "h"((uint16_t)v) : "memory"); }
__device__ __forceinline__ void sts128(uint32_t a, uint32_t x, uint32_t y, uint32_t z, uint32_t w) {
  asm volatile("st.shared.v4.u32 [%0], {%1,%2,%3,%4};" ::"r"(a), "r"(x), "r"(y), "r"(z), "r"(w) : "memory");
}
__device__ __forceinline__ uint32_t sw128(int row, int col) { return row * 128 + ((((col >> 3) ^ row) & 7) << 4) + (col & 7) * 2; }

__device__ __forceinline__ void wgmma_rs56(float (&d)[28], const uint32_t a0, const uint32_t a1, const uint32_t a2, const uint32_t a3, Desc db, int sd) {
  asm volatile("{.reg .pred p; .reg .b64 da, db; setp.ne.b32 p, %33, 0; mov.b64 db, {%32, %34};\n wgmma.mma_async.sync.aligned.m64n56k16.f32.bf16.bf16 {%0,%1,%2,%3,%4,%5,%6,%7,%8,%9,%10,%11,%12,%13,%14,%15,%16,%17,%18,%19,%20,%21,%22,%23,%24,%25,%26,%27}, {%28,%29,%30,%31}, db, p, 1, 1, 1;}"
   : "+f"(d[0]),"+f"(d[1]),"+f"(d[2]),"+f"(d[3]),"+f"(d[4]),"+f"(d[5]),"+f"(d[6]),"+f"(d[7]),"+f"(d[8]),"+f"(d[9]),"+f"(d[10]),"+f"(d[11]),"+f"(d[12]),"+f"(d[13]),"+f"(d[14]),"+f"(d[15]),"+f"(d[16]),"+f"(d[17]),"+f"(d[18]),"+f"(d[19]),"+f"(d[20]),"+f"(d[21]),"+f"(d[22]),"+f"(d[23]),"+f"(d[24]),"+f"(d[25]),"+f"(d[26]),"+f"(d[27])
   : "r"(a0),"r"(a1),"r"(a2),"r"(a3),"r"(db.lo),"r"(sd),"r"(db.hi));
}
__device__ __forceinline__ void wgmma_rs64(float (&d)[32], const uint32_t a0, const uint32_t a1, const uint32_t a2, const uint32_t a3, Desc db, int sd) {
  asm volatile("{.reg .pred p; .reg .b64 da, db; setp.ne.b32 p, %37, 0; mov.b64 db, {%36, %38};\n wgmma.mma_async.sync.aligned.m64n64k16.f32.bf16.bf16 {%0,%1,%2,%3,%4,%5,%6,%7,%8,%9,%10,%11,%12,%13,%14,%15,%16,%17,%18,%19,%20,%21,%22,%23,%24,%25,%26,%27,%28,%29,%30,%31}, {%32,%33,%34,%35}, db, p, 1, 1, 1;}"
   : "+f"(d[0]),"+f"(d[1]),"+f"(d[2]),"+f"(d[3]),"+f"(d[4]),"+f"(d[5]),"+f"(d[6]),"+f"(d[7]),"+f"(d[8]),"+f"(d[9]),"+f"(d[10]),"+f"(d[11]),"+f"(d[12]),"+f"(d[13]),"+f"(d[14]),"+f"(d[15]),"+f"(d[16]),"+f"(d[17]),"+f"(d[18]),"+f"(d[19]),"+f"(d[20]),"+f"(d[21]),"+f"(d[22]),"+f"(d[23]),"+f"(d[24]),"+f"(d[25]),"+f"(d[26]),"+f"(d[27]),"+f"(d[28]),"+f"(d[29]),"+f"(d[30]),"+f"(d[31])
   : "r"(a0),"r"(a1),"r"(a2),"r"(a3),"r"(db.lo),"r"(sd),"r"(db.hi));
}
__device__ __forceinline__ void wgmma_rs192(float (&d)[96], const uint32_t a0, const uint32_t a1, const uint32_t a2, const uint32_t a3, Desc db, int sd) {
  asm volatile("{.reg .pred p; .reg .b64 db; setp.ne.b32 p, %101, 0; mov.b64 db, {%100, %102};\n wgmma.mma_async.sync.aligned.m64n192k16.f32.bf16.bf16 {%0,%1,%2,%3,%4,%5,%6,%7,%8,%9,%10,%11,%12,%13,%14,%15,%16,%17,%18,%19,%20,%21,%22,%23,%24,%25,%26,%27,%28,%29,%30,%31,%32,%33,%34,%35,%36,%37,%38,%39,%40,%41,%42,%43,%44,%45,%46,%47,%48,%49,%50,%51,%52,%53,%54,%55,%56,%57,%58,%59,%60,%61,%62,%63,%64,%65,%66,%67,%68,%69,%70,%71,%72,%73,%74,%75,%76,%77,%78,%79,%80,%81,%82,%83,%84,%85,%86,%87,%88,%89,%90,%91,%92,%93,%94,%95}, {%96,%97,%98,%99}, db, p, 1, 1, 1;}"
   : "+f"(d[0]),"+f"(d[1]),"+f"(d[2]),"+f"(d[3]),"+f"(d[4]),"+f"(d[5]),"+f"(d[6]),"+f"(d[7]),"+f"(d[8]),"+f"(d[9]),"+f"(d[10]),"+f"(d[11]),"+f"(d[12]),"+f"(d[13]),"+f"(d[14]),"+f"(d[15]),"+f"(d[16]),"+f"(d[17]),"+f"(d[18]),"+f"(d[19]),"+f"(d[20]),"+f"(d[21]),"+f"(d[22]),"+f"(d[23]),"+f"(d[24]),"+f"(d[25]),"+f"(d[26]),"+f"(d[27]),"+f"(d[28]),"+f"(d[29]),"+f"(d[30]),"+f"(d[31]),"+f"(d[32]),"+f"(d[33]),"+f"(d[34]),"+f"(d[35]),"+f"(d[36]),"+f"(d[37]),"+f"(d[38]),"+f"(d[39]),"+f"(d[40]),"+f"(d[41]),"+f"(d[42]),"+f"(d[43]),"+f"(d[44]),"+f"(d[45]),"+f"(d[46]),"+f"(d[47]),"+f"(d[48]),"+f"(d[49]),"+f"(d[50]),"+f"(d[51]),"+f"(d[52]),"+f"(d[53]),"+f"(d[54]),"+f"(d[55]),"+f"(d[56]),"+f"(d[57]),"+f"(d[58]),"+f"(d[59]),"+f"(d[60]),"+f"(d[61]),"+f"(d[62]),"+f"(d[63]),"+f"(d[64]),"+f"(d[65]),"+f"(d[66]),"+f"(d[67]),"+f"(d[68]),"+f"(d[69]),"+f"(d[70]),"+f"(d[71]),"+f"(d[72]),"+f"(d[73]),"+f"(d[74]),"+f"(d[75]),"+f"(d[76]),"+f"(d[77]),"+f"(d[78]),"+f"(d[79]),"+f"(d[80]),"+f"(d[81]),"+f"(d[82]),"+f"(d[83]),"+f"(d[84]),"+f"(d[85]),"+f"(d[86]),"+f"(d[87]),"+f"(d[88]),"+f"(d[89]),"+f"(d[90]),"+f"(d[91]),"+f"(d[92]),"+f"(d[93]),"+f"(d[94]),"+f"(d[95])
   : "r"(a0),"r"(a1),"r"(a2),"r"(a3),"r"(db.lo),"r"(sd),"r"(db.hi));
}
__device__ __forceinline__ void wgmma_rs32(float (&d)[16], const uint32_t a0, const uint32_t a1, const uint32_t a2, const uint32_t a3, Desc db, int sd) {
  asm volatile("{.reg .pred p; .reg .b64 db; setp.ne.b32 p, %21, 0; mov.b64 db, {%20, %22};\n wgmma.mma_async.sync.aligned.m64n32k16.f32.bf16.bf16 {%0,%1,%2,%3,%4,%5,%6,%7,%8,%9,%10,%11,%12,%13,%14,%15}, {%16,%17,%18,%19}, db, p, 1, 1, 1;}"
   : "+f"(d[0]),"+f"(d[1]),"+f"(d[2]),"+f"(d[3]),"+f"(d[4]),"+f"(d[5]),"+f"(d[6]),"+f"(d[7]),"+f"(d[8]),"+f"(d[9]),"+f"(d[10]),"+f"(d[11]),"+f"(d[12]),"+f"(d[13]),"+f"(d[14]),"+f"(d[15])
   : "r"(a0),"r"(a1),"r"(a2),"r"(a3),"r"(db.lo),"r"(sd),"r"(db.hi));
}
__device__ __forceinline__ void wgmma_ss32(float (&d)[16], Desc da, Desc db, int sd) {
  asm volatile("{.reg .pred p; .reg .b64 da, db; setp.ne.b32 p, %18, 0; mov.b64 da, {%16, %19}; mov.b64 db, {%17, %19};\n wgmma.mma_async.sync.aligned.m64n32k16.f32.bf16.bf16 {%0,%1,%2,%3,%4,%5,%6,%7,%8,%9,%10,%11,%12,%13,%14,%15}, da, db, p, 1, 1, 1, 1;}"
   : "+f"(d[0]),"+f"(d[1]),"+f"(d[2]),"+f"(d[3]),"+f"(d[4]),"+f"(d[5]),"+f"(d[6]),"+f"(d[7]),"+f"(d[8]),"+f"(d[9]),"+f"(d[10]),"+f"(d[11]),"+f"(d[12]),"+f"(d[13]),"+f"(d[14]),"+f"(d[15])
   : "r"(da.lo),"r"(db.lo),"r"(sd),"r"(db.hi));
}

__device__ __forceinline__ uint4 ldsm4(uint32_t a) {
  uint4 v; asm volatile("ldmatrix.sync.aligned.m8n8.x4.shared.b16 {%0,%1,%2,%3}, [%4];" : "=r"(v.x), "=r"(v.y), "=r"(v.z), "=r"(v.w) : "r"(a) : "memory"); return v;
}
__device__ __forceinline__ void mma16816(float (&d)[4], const uint4& a, uint32_t b0, uint32_t b1) {
  asm("mma.sync.aligned.m16n8k16.row.col.f32.bf16.bf16.f32 {%0,%1,%2,%3}, {%4,%5,%6,%7}, {%8,%9}, {%0,%1,%2,%3};"
      : "+f"(d[0]), "+f"(d[1]), "+f"(d[2]), "+f"(d[3]) : "r"(a.x), "r"(a.y), "r"(a.z), "r"(a.w), "r"(b0), "r"(b1));
}
__device__ __forceinline__ uint32_t bsub(uint32_t a, uint32_t b) { uint32_t r; asm("sub.bf16x2 %0, %1, %2;" : "=r"(r) : "r"(a), "r"(b)); return r; }
__device__ __forceinline__ uint32_t hint_ld(const uint32_t* p) { uint32_t v; asm volatile("ld.relaxed.gpu.global.u32 %0, [%1];" : "=r"(v) : "l"(p) : "memory"); return v; }
template <int S, int N, bool SPL = false, int T> __device__ __forceinline__ void ll_issue(uint4 (&v)[T], const uint4* p, int stride, const uint2* p2 = nullptr) {
#pragma unroll
  for (int i = S; i < S + N; i++) {
    if (SPL && i % 7 == 3) { const uint2 lo = ldll2(p2 + i * 64), hi = ldll2(p2 + i * 64 + 32); v[i] = make_uint4(lo.x, lo.y, hi.x, hi.y); }
    else v[i] = ldll(p + i * stride);
  }
}
template <int S, int N, bool SPL, int T> __device__ __forceinline__ void ll_check(uint4 (&v)[T], const uint4* p, int stride, uint32_t tag, const uint2* p2 = nullptr) {
#pragma unroll 1
  for (int it = 0; it < SPIN; it++) {
    uint32_t bad = 0;
#pragma unroll
    for (int i = S; i < S + N; i++) bad |= (v[i].x ^ tag) | ((SPL && i % 7 == 3) ? (v[i].z ^ tag) : 0u);
    if (!__any_sync(~0u, bad & 1)) break;
    ll_issue<S, N, SPL>(v, p, stride, p2);
  }
}
__device__ __forceinline__ void hint_post(uint32_t* p, uint32_t v, int lane) {
  if (lane == 0) asm volatile("st.relaxed.gpu.global.u32 [%0], %1;" ::"l"(p), "r"(v) : "memory");
}
__device__ __forceinline__ void hint_wait(const uint32_t* p, uint32_t s, uint32_t v = 0xffffu) {
#pragma unroll 1
  for (int it = 0; it < SPIN; it++) {
    if (__all_sync(~0u, v - s < 10u)) break;
    v = hint_ld(p);
  }
}
__device__ __forceinline__ void slice_store(uint4* pf, uint2* ph, const uint32_t (&w)[14], bool odd) {
#pragma unroll
  for (int u = 0; u < 3; u++)
    stll(pf + u * 32, odd ? w[4 * u + 2] : w[4 * u], odd ? w[4 * u + 3] : w[4 * u + 1], odd ? w[4 * u + 4] : w[4 * u + 2], odd ? w[4 * u + 5] : w[4 * u + 3]);
  stll2(ph, odd ? w[0] : w[12], odd ? w[1] : w[13]);
}
template <class F, class M> __device__ __forceinline__ void hedgehog(const float (&d)[28], F sink, M mid) {
  const float L2E = 1.4426950408889634f;
#define HX(G, p) ((p) < 6 ? d[((G) & 1) * 16 + ((p) >> 1) * 4 + ((p) & 1) + ((G) & 2)] : d[12 + (G)])
  float mx[4], mn[4], sp[4], sn[4], ep[4][7], en[4][7];
#pragma unroll
  for (int G = 0; G < 4; G++) {
    mx[G] = mn[G] = HX(G, 0);
#pragma unroll
    for (int p = 1; p < 7; p++) { mx[G] = fmaxf(mx[G], HX(G, p)); mn[G] = fminf(mn[G], HX(G, p)); }
  }
#pragma unroll
  for (int o = 1; o < 4; o <<= 1)
#pragma unroll
    for (int G = 0; G < 4; G++) { mx[G] = fmaxf(mx[G], __shfl_xor_sync(~0u, mx[G], o)); mn[G] = fminf(mn[G], __shfl_xor_sync(~0u, mn[G], o)); }
#pragma unroll
  for (int G = 0; G < 4; G++) {
    const float a = -mx[G] * L2E, b = mn[G] * L2E;
#pragma unroll
    for (int p = 0; p < 7; p++) { ep[G][p] = ex2(fmaf(HX(G, p), L2E, a)); en[G][p] = ex2(fmaf(HX(G, p), -L2E, b)); }
    sp[G] = ((ep[G][0] + ep[G][1]) + (ep[G][2] + ep[G][3])) + ((ep[G][4] + ep[G][5]) + ep[G][6]);
    sn[G] = ((en[G][0] + en[G][1]) + (en[G][2] + en[G][3])) + ((en[G][4] + en[G][5]) + en[G][6]);
    if (G == 1) mid();
  }
#pragma unroll
  for (int o = 1; o < 4; o <<= 1)
#pragma unroll
    for (int G = 0; G < 4; G++) { sp[G] += __shfl_xor_sync(~0u, sp[G], o); sn[G] += __shfl_xor_sync(~0u, sn[G], o); }
#pragma unroll
  for (int G = 0; G < 4; G++) {
    const float a = rcp(sp[G]), b = rcp(sn[G]);
#pragma unroll
    for (int p = 0; p < 7; p++) sink(G >> 1, G & 1, p, pack(ep[G][p] * a, en[G][p] * b));
  }
}
__device__ __forceinline__ void phi_gemm(const float (&x)[28], float (&y)[28], uint32_t wphi, float r0, float r1) {
  uint32_t f[14];
#pragma unroll
  for (int j = 0; j < 14; j++) f[j] = pack(x[2 * j] * (j & 1 ? r1 : r0), x[2 * j + 1] * (j & 1 ? r1 : r0));
  wg_fence();
#pragma unroll
  for (int ks = 0; ks < 3; ks++) wgmma_rs56(y, f[4 * ks], f[4 * ks + 1], f[4 * ks + 2], f[4 * ks + 3], mkdesc(wphi, ks * 2048, 1024, 1024, 1), ks);
  wgmma_rs56(y, f[12], f[13], 0u, 0u, mkdesc(wphi, 3 * 2048, 1024, 1024, 1), 1);
  wg_commit();
}
__device__ __forceinline__ void ln_stats(uint32_t (&xw)[4][4], float* sLN, int warp, int lane, uint4* dst) {
  const int g = lane >> 2; const bool full = warp < 4;
  float s0 = 0.f, s1 = 0.f;
#pragma unroll
  for (int u = 0; u < 4; u++) {
    s0 += (blo(xw[u][0]) + bhi(xw[u][0])) + (blo(xw[u][2]) + bhi(xw[u][2]));
    s1 += (blo(xw[u][1]) + bhi(xw[u][1])) + (blo(xw[u][3]) + bhi(xw[u][3]));
  }
  const float rc = full ? 1.f / 64 : 1.f / 48;
  s0 = qsum(s0); s1 = qsum(s1);
  const float a0 = s0 * rc, a1 = s1 * rc;
  float v0 = 0.f, v1 = 0.f;
#pragma unroll
  for (int u = 0; u < 4; u++)
    if (u < 3 || full) {
#pragma unroll
      for (int k = 0; k < 4; k += 2) {
        float a = blo(xw[u][k]) - a0, b = bhi(xw[u][k]) - a0, c2 = blo(xw[u][k + 1]) - a1, d2 = bhi(xw[u][k + 1]) - a1;
        v0 += a * a + b * b; v1 += c2 * c2 + d2 * d2;
      }
    }
  v0 = qsum(v0); v1 = qsum(v1);
  if ((lane & 3) == 0) *(float4*)(sLN + (g * 8 + warp) * 4) = make_float4(s0, v0, s1, v1);
  if (warp) { asm volatile("bar.arrive 7, 256;" ::: "memory"); return; }
  asm volatile("bar.sync 7, 256;" ::: "memory");
  const float4 ea = *(const float4*)(sLN + (g * 8 + (lane & 3)) * 4), eb = *(const float4*)(sLN + (g * 8 + 4 + (lane & 3)) * 4);
  const float m0 = qsum(ea.x + eb.x) * (1.f / 448), m1 = qsum(ea.z + eb.z) * (1.f / 448);
  const float d0 = ea.x * (1.f / 64) - m0, d1 = eb.x * (1.f / 48) - m0, d2 = ea.z * (1.f / 64) - m1, d3 = eb.z * (1.f / 48) - m1;
  v0 = qsum(ea.y + eb.y + 64.f * d0 * d0 + 48.f * d1 * d1); v1 = qsum(ea.w + eb.w + 64.f * d2 * d2 + 48.f * d3 * d3);
  if ((lane & 3) == 0) stll(dst + g, tg(__float_as_uint(m0), 1), __float_as_uint(rsqrtf(v0 * (1.f / 448) + 1e-5f)), __float_as_uint(m1), __float_as_uint(rsqrtf(v1 * (1.f / 448) + 1e-5f)));
}

__global__ void CLUSTER __launch_bounds__(384, 1)
fused_kernel(const __grid_constant__ CUtensorMap mQKV, const __grid_constant__ CUtensorMap mWO, const __grid_constant__ CUtensorMap mW1,
             const __grid_constant__ CUtensorMap mW1b, const __grid_constant__ CUtensorMap mW2, const __grid_constant__ CUtensorMap mW2b,
             const __grid_constant__ CUtensorMap mX, const __nv_bfloat16* __restrict__ wqkv, const __nv_bfloat16* __restrict__ wphi,
             const __nv_bfloat16* __restrict__ wo, const __nv_bfloat16* __restrict__ w1, const __nv_bfloat16* __restrict__ b1,
             const __nv_bfloat16* __restrict__ w2, const __nv_bfloat16* __restrict__ b2, __nv_bfloat16* __restrict__ out) {
  extern __shared__ __align__(1024) uint8_t sm[];
  const uint32_t sb = s2u(sm);
  const int tid = threadIdx.x, warp = __shfl_sync(~0u, tid >> 5, 0), lane = tid & 31,
            t = MAPPING ? (blockIdx.x >> 4) * 2 + (blockIdx.x & 1) : blockIdx.x >> 3, c = MAPPING ? (blockIdx.x >> 1) & 7 : blockIdx.x & 7;
  const uint32_t bfull = sb + OFF_BAR, bempty = bfull + 8 * NST;

#define XOFF(l) ((t * 128 + c * 16 + ((l) >> 2)) * 448 + warp * 16 + 2 * ((l) & 3))
  if (warp < 8) { MARK(0); GT(19); }
  if (tid == 256) {
    for (int s = 0; s < NST; s++) { mbar_init(bfull + 8 * s, 1); mbar_init(bempty + 8 * s, MC ? 16 : 8); }
    mbar_init(bempty + 8 * NST, 1);
    asm volatile("fence.mbarrier_init.release.cluster;" ::: "memory");
    fence_async();
    mbar_expect(bempty + 8 * NST, 114688);
    for (int i = 0; i < 7; i++)
      asm volatile("cp.async.bulk.tensor.2d.shared::cluster.global.mbarrier::complete_tx::bytes [%0], [%1, {%3, %4}], [%2];"
                   ::"r"(sb + 2 * STAGE + i * 16384), "l"(&mX), "r"(bempty + 8 * NST), "r"(64 * i), "r"(128 * t) : "memory");
  }
  asm volatile("barrier.cluster.arrive.release.aligned; barrier.cluster.wait.acquire.aligned;" ::: "memory");
  if (warp >= 8) {
    asm volatile("setmaxnreg.dec.sync.aligned.u32 24;");
    auto issue = [&](int i, int s) {
      const uint32_t dst = sb + s * STAGE, bar = bfull + 8 * s;
      mbar_expect(bar, STAGE);
#pragma unroll 1
      for (int rk = MC ? (blockIdx.x & 1) : 0; rk < (MC ? (blockIdx.x & 1) + 1 : 2); rk++)
      if (i < 4) tma2d(dst + rk * 14336, &mQKV, 448 + 448 * rk + 56 * c, 112 * i, bar);
      else if (i < 8) tma2d(dst + rk * 14336, i < 6 ? &mQKV : &mWO, (i < 6 ? 56 : 64) * c, 224 * (i & 1) + 112 * rk, bar);
      else if (i < 15) { const int k0 = 64 * ((i - 8 + c) % 7) + 32 * rk;
        tma3d(dst + rk * 12288, &mW1, 0, k0, 3 * c, bar); tma2d(dst + 24576 + rk * 2048, &mW1b, 1536 + 32 * c, k0, bar); }
      else { tma2d(dst + rk * 12288, &mW2, 64 * (i - 15), 192 * c + 96 * rk, bar); tma2d(dst + 24576 + rk * 2048, &mW2b, 64 * (i - 15), 1536 + 32 * c + 16 * rk, bar); }
    };
    auto colsum = [&](int job) {
        const int ld4 = job < 112 ? 448 : 336;
        const uint2* wp = (job < 112 ? (const uint2*)w1 + job * 4 : (const uint2*)wqkv + (job - 112) * 4) + (lane >> 2) * ld4 + (lane & 3);
        float s0 = 0.f, s1 = 0.f, s2 = 0.f, s3 = 0.f;
#pragma unroll 8
        for (int i = 0; i < 56; i++) { const uint2 v = __ldg(wp + i * 8 * ld4); s0 += blo(v.x); s1 += bhi(v.x); s2 += blo(v.y); s3 += bhi(v.y); }
#pragma unroll 1
        for (int o = 4; o < 32; o <<= 1) { s0 += __shfl_xor_sync(~0u, s0, o); s1 += __shfl_xor_sync(~0u, s1, o); s2 += __shfl_xor_sync(~0u, s2, o); s3 += __shfl_xor_sync(~0u, s3, o); }
        if (lane < 4) stll(g_CS + job * 4 + lane, tg(__float_as_uint(s0), 1), __float_as_uint(s1), __float_as_uint(s2), __float_as_uint(s3));
      };
    if (warp == 8) {
      int s = 0; uint32_t ph = 1;
      for (int n = 0; n < 44; n++) {
        if (n == PACE) asm volatile("bar.sync 2, 288;" ::: "memory");
        mbar_wait(bempty + 8 * s, ph);
        if (n == 22) {
          uint32_t v = 0;
#pragma unroll 1
          for (int it = 0; it < SPIN && v < 32; it++) asm volatile("ld.acquire.gpu.global.u32 %0, [%1];" : "=r"(v) : "l"(g_WQF + c) : "memory");
          asm volatile("fence.proxy.async.global;" ::: "memory");
        }
        if (lane == 0) {
          if (n >= 22 && n < 28) {
            mbar_expect(bfull + 8 * s, STAGE);
            asm volatile("cp.async.bulk.shared::cluster.global.mbarrier::complete_tx::bytes [%0], [%1], %2, [%3];"
                         ::"r"(sb + s * STAGE), "l"(g_WQ + c * 10752 + (n - 22) * (STAGE / 16)), "r"(STAGE), "r"(bfull + 8 * s) : "memory");
          } else issue(n >= 22 ? n - 22 : n, s);
        }
        __syncwarp();
        if (++s == NST) { s = 0; ph ^= 1; }
      }
    } else if (warp == 9) {
      mbar_wait(bfull + 8 * PFS, 0);
      if (lane == 0) {
        l2pf((const uint8_t*)wo + blockIdx.x * 3136, 3136);
        l2pf((const uint8_t*)w1 + blockIdx.x * 12544, 12544);
        l2pf((const uint8_t*)w2 + blockIdx.x * 12544, 12544);
      }
      if (blockIdx.x < 112) colsum(blockIdx.x);
      asm volatile("bar.sync 6, 96;" ::: "memory");
#pragma unroll 1
      for (int i = 0; i < 4; i++) {
        const int e = lane < 28 ? lane + 28 * (i & 1) : 0;
        const bool ok = i < 2 || (e < 48 && (e & 15) < 14);
        const int e4 = i < 2 ? (e < 48 ? 48 * c + e : 336 + 8 * c + e) : ok ? 448 + 112 * (e >> 4) + 14 * c + (e & 15) : 448;
        uint4 cv[1];
        ll_issue<0, 1>(cv, g_CS + e4, 0); ll_check<0, 1, false>(cv, g_CS + e4, 0, 1u);
        const uint2 bb = __ldg((const uint2*)b1 + (i < 2 ? e4 : 0));
        const uint32_t h0 = pack(__uint_as_float(cv[0].x), __uint_as_float(cv[0].y)), h1 = pack(__uint_as_float(cv[0].z), __uint_as_float(cv[0].w));
        const uint32_t l0 = pack(__uint_as_float(cv[0].x) - blo(h0), __uint_as_float(cv[0].y) - bhi(h0)), l1 = pack(__uint_as_float(cv[0].z) - blo(h1), __uint_as_float(cv[0].w) - bhi(h1));
#pragma unroll 1
        for (int j = 0; j < (i < 2 ? 5 : 3); j++) {
          const int r = i < 2 ? j : j + 5;
          const uint32_t ad = sb + OFF_CB + (e >> 3) * 512 + r * 64 + ((((e >> 1) ^ (r >> 1)) & 3) << 4) + (e & 1) * 8;
          sts32(ad, j < 2 ? h0 : j == 2 ? l0 : bb.x); sts32(ad + 4, j < 2 ? h1 : j == 2 ? l1 : bb.y);
        }
        if (i & 1) { fence_async(); if (i == 1) asm volatile("bar.arrive 4, 288;" ::: "memory"); else asm volatile("bar.arrive 8, 288;" ::: "memory"); }
      }
    } else if (warp >= 10) {
      const int h = warp - 10;
      uint4 wv[4];
#pragma unroll
      for (int i = 0; i < 4; i++) wv[i] = __ldg((const uint4*)wphi + (2 * c + h) * 98 + min(lane + 32 * i, 97));
#pragma unroll 1
      for (int e = h * 32 + lane; e < 672; e += 64) sts128(sb + OFF_WPHI + e * 16, 0, 0, 0, 0);
      asm volatile("bar.arrive 6, 96;" ::: "memory");
#pragma unroll 1
      for (int i = 0; i < 4; i++) sts128(sb + OFF_PHIK + sw128(h * 128 + i * 32 + lane, 56), 0, 0, 0, 0);
      asm volatile("bar.sync 5, 64;" ::: "memory");
#pragma unroll
      for (int i = 0; i < 4; i++) sts128(sb + OFF_V + h * 2048 + (lane + 32 * i) * 16, wv[i].x, wv[i].y, wv[i].z, wv[i].w);
      __syncwarp();
#pragma unroll 1
      for (int e = lane; e < 392; e += 32) {
        const int d = e / 14, f2 = 2 * (e - 14 * d), k = 28 * h + d;
        const uint32_t v = *(volatile uint32_t*)(sm + OFF_V + h * 2048 + e * 4);
        if (f2 < 24) sts32(sb + OFF_WPHI + sw128(k, 32 * h + f2), v);
        else { sts16(sb + OFF_WPHI + sw128(k, 2 * f2 - 24 + h), v); sts16(sb + OFF_WPHI + sw128(k, 2 * f2 - 22 + h), v >> 16); }
      }
      fence_async();
      asm volatile("bar.arrive 3, 320;" ::: "memory");
      mbar_wait(bfull + 8 * 5, 0);
#pragma unroll 2
      for (int e = t * 672 + h * 32 + lane; e < t * 672 + 672; e += 64) {
        const int r = e >> 3, st = r / 224, rr = r - st * 224, ch = (e & 7) ^ (rr & 7);
        const int k = st < 4 ? 112 * st + (rr >= 112 ? rr - 112 : rr) : 224 * (st - 4) + rr, col = (st < 4 ? (rr >= 112 ? 896 : 448) : 0) + 56 * c + 8 * ch;
        g_WQ[c * 10752 + e] = ch < 7 ? __ldg((const uint4*)(wqkv + k * 1344 + col)) : make_uint4(0, 0, 0, 0);
      }
      __syncwarp();
      if (lane == 0) asm volatile("red.release.gpu.global.add.u32 [%0], 1;" ::"l"(g_WQF + c) : "memory");
      if (h == 0 && blockIdx.x < 84) colsum(112 + blockIdx.x);
    }
  } else {
  asm volatile("setmaxnreg.inc.sync.aligned.u32 240;");

  const int wg = warp >> 2, g = lane >> 2, q = lane & 3;
  const int row0 = warp * 16 + g;
#define PTRS const int ln_ = laneid(); \
  uint4* const fm = g_F + ((t * 8 + warp) * 28) * 32 + ln_;            \
  uint4* const fr = g_F + ((t * 8 + c) * 28 + warp) * 32 + ln_;        \
  uint4* const sf = fm + (7 * (c >> 1) + 4 * (c & 1)) * 32;             \
  uint2* const f2 = (uint2*)(fm - ln_) + ln_;                           \
  uint2* const sh = f2 + (7 * (c >> 1) + 3) * 64 + 32 * (c & 1);        \
  uint32_t* const hme = g_H + (t * 8 + warp) * 8 + c; \
  const uint32_t* const hrow = g_H + (t * 8 + warp) * 8 + (ln_ & 7); \
  (void)fm; (void)fr; (void)sf; (void)f2; (void)sh; (void)hme; (void)hrow;
  float* sLN = (float*)(sm + OFF_V);
  const uint32_t sPK = sb + OFF_PHIK, sV = sb + OFF_V, d16 = (sb & 0x3FFFF) >> 4;
    uint32_t xw[4][4];
#pragma unroll
  for (int i = 0; i < 16; i++) xw[i >> 2][i & 3] = 0;
  int cs = 0, rs = 0; uint32_t cph = 0;
  auto acquire = [&]() -> uint32_t { mbar_wait(bfull + 8 * cs, cph); const uint32_t a = d16 + cs * (STAGE >> 4); if (++cs == NST) { cs = 0; cph ^= 1; } return a; };
  int nrel = 44 - NST;
  auto release = [&]() { if (lane < 1 + MC && nrel > 0) mbar_arrive_cl(bempty + 8 * rs, lane); nrel--; if (++rs == NST) rs = 0; };

#define RISSUE(m, P, XA, XB, BA, BB) { ll_issue<0, 8>(P, pr + (m) * 256, 896); \
      { const uint4 v_ = ldll(fr + X1 + (m) * 256); XA = make_uint2(v_.x, v_.y); XB = make_uint2(v_.z, v_.w); } \
      const uint32_t* bp = (const uint32_t*)(b2 + 128 * (m) + 16 * warp) + (ln_ & 3); BA = __ldg(bp); BB = __ldg(bp + 4); }
#define REDU(m, P, XA, XB, BA, BB) { ll_check<0, 8, false>(P, pr + (m) * 256, 896, ptag); \
      float e[8] = {blo(XA.x) + blo(BA), bhi(XA.x) + bhi(BA), blo(XA.y) + blo(BA), bhi(XA.y) + bhi(BA), blo(XB.x) + blo(BB), bhi(XB.x) + bhi(BB), blo(XB.y) + blo(BB), bhi(XB.y) + bhi(BB)}; \
      _Pragma("unroll") for (int i = 0; i < 8; i++) { e[0] += blo(P[i].x); e[1] += bhi(P[i].x); e[2] += blo(P[i].y); e[3] += bhi(P[i].y); \
        e[4] += blo(P[i].z); e[5] += bhi(P[i].z); e[6] += blo(P[i].w); e[7] += bhi(P[i].w); } \
      xw[m][0] = pack(e[0], e[1]); xw[m][1] = pack(e[2], e[3]); xw[m][2] = pack(e[4], e[5]); xw[m][3] = pack(e[6], e[7]); }
#define RPUB(m) stll(fr + XR + (m) * 256, tg(xw[m][0], 0), xw[m][1], xw[m][2], xw[m][3]);
#define RLAST(ptag_, hv) { const uint32_t ptag = ptag_; const uint4* pr = g_P + ((t * 8 + c) * 8 * 28 + warp) * 32 + ln_; uint4 p[8]; uint2 xa, xb; uint32_t ba, bb; \
      hint_wait(g_H + (t * 8 + c) * 8 + (ln_ & 7), hv); RISSUE(3, p, xa, xb, ba, bb) REDU(3, p, xa, xb, ba, bb) }
#pragma unroll 1
  for (int L = 0; L < 2; L++) {
    const uint32_t tag = 1 - L;
    uint32_t phq[2][2][7];
    const uint32_t hs = 10 * L;
    {
      PTRS
      uint4 a[28];
      const uint4* pa = fm + XR;
      uint32_t fa = 0, fb = 0;
      float r0 = 1.f, r1 = 1.f;
      if (L == 0) {
        hint_post(hme, 1, lane);
        mbar_wait(bempty + 8 * NST, 0);
        MARK(1);
        const int row = warp * 16 + (ln_ & 15);
        const uint32_t xb = sb + 2 * STAGE + row * 128;
        float cs_[4][4] = {};
#pragma unroll
        for (int ks = 0; ks < 28; ks++) { a[ks] = ldsm4(xb + (ks >> 2) * 16384 + (((2 * (ks & 3) + (ln_ >> 4)) ^ (row & 7)) << 4)); mma16816(cs_[ks & 3], a[ks], 0x3F803F80u, 0x3F803F80u); }
        if (c < 7) {
#pragma unroll
          for (int u = 0; u < 4; u++) { const uint4 v = ldsm4(xb + c * 16384 + (((2 * u + (ln_ >> 4)) ^ (row & 7)) << 4)); stll(fm + XR + 128 * c + u * 32, tg(v.x, tag), v.y, v.z, v.w); }
        }
        const float m0 = ((cs_[0][0] + cs_[1][0]) + (cs_[2][0] + cs_[3][0])) * (1.f / 448), m1 = ((cs_[0][2] + cs_[1][2]) + (cs_[2][2] + cs_[3][2])) * (1.f / 448);
        const uint32_t mb0 = pack(m0, m0), mb1 = pack(m1, m1);
        asm volatile("bar.arrive 2, 288;" ::"r"(mb0) : "memory");
#pragma unroll
        for (int ks = 0; ks < 28; ks++) {
          a[ks].x = bsub(a[ks].x, mb0); a[ks].y = bsub(a[ks].y, mb1); a[ks].z = bsub(a[ks].z, mb0); a[ks].w = bsub(a[ks].w, mb1);
        }
        r0 = m0 - blo(mb0); r1 = m1 - blo(mb1);
      } else {
        ll_issue<0, 14>(a, pa, 32);
        if (wg == 0) { RLAST(1u, 10u) xw[3][0] = tg(xw[3][0], 0); RPUB(3) } else { xw[3][0] = xw[3][1] = xw[3][2] = xw[3][3] = 0; }
        MARK(20);
        ll_issue<14, 7>(a, pa, 32);
        ln_stats(xw, sLN, warp, lane, g_S2 + (t * 8 + c) * 8);
      }
      MARK(2 + L * 19);
      float ak[28], av[28], aq[28], pp[28];
#define KVSTAGE(i) { if (L) ll_check<7 * i, 7, false>(a, pa, 32, tag); const uint32_t st = acquire(); wg_fence(); \
      _Pragma("unroll") for (int ks = 0; ks < 7; ks++) { const uint4 f = a[7 * i + ks]; \
        wgmma_rs56(ak, f.x, f.y, f.z, f.w, mkdesc(st, ks * 2048, 1024, 1024, 1), i | ks); \
        wgmma_rs56(av, f.x, f.y, f.z, f.w, mkdesc(st, 14336 + ks * 2048, 1024, 1024, 1), i | ks); } \
      wg_commit(); if (i > 0) { wg_wait<1>(); release(); } }
      KVSTAGE(0) KVSTAGE(1)
      uint4 sv[1];
      const uint4* ps = g_S2 + (t * 8 + warp) * 8 + (ln_ >> 2);
      if (L) { ll_issue<21, 7>(a, pa, 32); ll_issue<0, 1>(sv, ps, 0); }
      else {
        float c0[2][4] = {}, c1[2][4] = {};
#pragma unroll
        for (int ks = 0; ks < 28; ks++) { mma16816(c0[ks & 1], a[ks], a[ks].x, a[ks].z); mma16816(c1[ks & 1], a[ks], a[ks].y, a[ks].w); }
        const int src = (ln_ & 28) | (g >> 1);
        const float q0 = __shfl_sync(~0u, (g & 1) ? c0[0][1] + c0[1][1] : c0[0][0] + c0[1][0], src), q1 = __shfl_sync(~0u, (g & 1) ? c1[0][3] + c1[1][3] : c1[0][2] + c1[1][2], src);
        r0 = rsqrtf(fmaxf(q0 * (1.f / 448) - r0 * r0, 0.f) + 1e-5f); r1 = rsqrtf(fmaxf(q1 * (1.f / 448) - r1 * r1, 0.f) + 1e-5f);
      }
      KVSTAGE(2) KVSTAGE(3)
      if (L) {
        ll_check<0, 1, false>(sv, ps, 0, 1u);
        const float m0 = -__uint_as_float(sv[0].x), m1 = -__uint_as_float(sv[0].z), h0 = blo(pack(m0, 0.f)), h1 = blo(pack(m1, 0.f));
        r0 = __uint_as_float(sv[0].y); r1 = __uint_as_float(sv[0].w);
        fa = q == 2 ? pack(0.f, h0) : q == 3 ? pack(m0 - h0, h0) : 0u; fb = q == 2 ? pack(0.f, h1) : q == 3 ? pack(m1 - h1, h1) : 0u;
      } else {
        asm volatile("bar.sync 3, 320;" ::: "memory");
      }
      wg_fence();
      wgmma_rs56(ak, fa, fb, 0u, 0u, mkdesc(d16, OFF_CB + 1024, 512, 0, 2), 1);
      wgmma_rs56(av, fa, fb, 0u, 0u, mkdesc(d16, OFF_CB + 2048, 512, 0, 2), 1);
      wg_commit();
      wg_wait<0>(); release(); regfence(ak); regfence(av);
      MARK(3 + L * 19);
      phi_gemm(ak, pp, d16 + (OFF_WPHI >> 4), r0, r1);
#pragma unroll
      for (int j = 0; j < 7; j++) {
        const int n = 8 * j + 2 * q, n2 = n < 28 ? n : n + 4;
        sts32(sV + sw128(row0, n2), pack(av[4 * j] * r0, av[4 * j + 1] * r0)); sts32(sV + sw128(row0 + 8, n2), pack(av[4 * j + 2] * r1, av[4 * j + 3] * r1));
      }
      { const int n2 = 28 + 2 * (q & 1) + 32 * (q >> 1); const uint32_t v = (q & 1) ? 0u : 0x3F80u; sts32(sV + sw128(row0, n2), v); sts32(sV + sw128(row0 + 8, n2), v); }
      wg_wait<0>(); regfence(pp);
      hedgehog(pp, [&](int r, int h, int p, uint32_t v) { sts32(sPK + h * 16384 + sw128(row0 + 8 * r, 8 * p + 2 * q), v); }, [] {});
      fence_async();
      bar_cons();
      MARK(4 + L * 19);
      float kv[16];
      wg_fence();
#pragma unroll
      for (int ks = 0; ks < 8; ks++) wgmma_ss32(kv, mkdesc(d16 + wg * 1024, OFF_PHIK + ks * 2048, 1024, 1024, 1), mkdesc(d16 + wg * 4, OFF_V + ks * 2048, 1024, 1024, 1), ks);
      wg_commit(); wg_wait<0>(); regfence(kv);
      const int ln2 = laneid();
#pragma unroll
      for (int u = 0; u < 4; u++) {
        float e[4];
#pragma unroll
        for (int i = 0; i < 4; i++) e[i] = kv[4 * u + i];
        stll(g_KVP + (c * 16 + t) * 1024 + wg * 512 + u * 128 + (warp & 3) * 32 + ln2, tg(__float_as_uint(e[0]), tag), __float_as_uint(e[1]), __float_as_uint(e[2]), __float_as_uint(e[3]));
      }
      MARK(5 + L * 19);
      uint4 k4[4];
      const uint4* pk = g_KVP + (c * 16 + 4 * (ln2 & 3)) * 1024 + 64 * t + warp * 8 + (ln2 >> 2);
#pragma unroll
      for (int i = 0; i < 2; i++) {
        const uint32_t st = acquire(); wg_fence();
#pragma unroll
        for (int ks = 0; ks < 14; ks++) { const uint4 f = a[14 * i + ks]; wgmma_rs56(aq, f.x, f.y, f.z, f.w, mkdesc(st, ks * 2048, 1024, 1024, 1), i | ks); }
        if (i == 1) wgmma_rs56(aq, fa, fb, 0u, 0u, mkdesc(d16, OFF_CB, 512, 0, 2), 1);
        wg_commit();
        if (i == 1) ll_issue<0, 4>(k4, pk, 1024);
      }
      ll_check<0, 4, false>(k4, pk, 1024, tag);
      float s0 = 0, s1 = 0, s2 = 0, s3 = 0;
#pragma unroll
      for (int i = 0; i < 4; i++) { s0 += __uint_as_float(k4[i].x); s1 += __uint_as_float(k4[i].y); s2 += __uint_as_float(k4[i].z); s3 += __uint_as_float(k4[i].w); }
      s0 = qsum(s0); s1 = qsum(s1); s2 = qsum(s2); s3 = qsum(s3);
      if (q == 0) stll2(g_KVR + c * 1024 + 64 * t + warp * 8 + (ln2 >> 2), tg(pack(s0, s1), tag), pack(s2, s3));
      MARK(6 + L * 19);
      wg_wait<0>(); release(); release(); regfence(aq);
      phi_gemm(aq, pp, d16 + (OFF_WPHI >> 4), r0, r1);
      bar_cons();
#pragma unroll
      for (int i = 0; i < 4; i++) sts128(sV + warp * 2048 + (lane + i * 32) * 16, 0, 0, 0, 0);
      wg_wait<0>(); regfence(pp);
      uint2 r[4];
      const uint2* pr = g_KVR + c * 1024 + wg * 512 + (warp & 3) * 32 + ln2;
      hedgehog(pp, [&](int r, int h, int p, uint32_t v) { phq[r][h][p] = v; }, [&] {
#pragma unroll
        for (int u = 0; u < 4; u++) r[u] = ldll2(pr + u * 128); });
      MARK(7 + L * 19);
#pragma unroll 1
      for (int it = 0; it < SPIN; it++) {
        if (!__any_sync(~0u, ((r[0].x ^ tag) | (r[1].x ^ tag) | (r[2].x ^ tag) | (r[3].x ^ tag)) & 1)) break;
#pragma unroll
        for (int u = 0; u < 4; u++) r[u] = ldll2(pr + u * 128);
      }
#pragma unroll
      for (int u = 0; u < 4; u++) {
        const int d = 8 * u + 2 * q;
        if (d < 28) { sts32(sV + sw128(row0, 28 * wg + d), r[u].x); sts32(sV + sw128(row0 + 8, 28 * wg + d), r[u].y); }
        else if (d == 28) {
#pragma unroll
          for (int j = 0; j < 4; j++) { sts16(sV + sw128(row0, 56 + 2 * j + wg), r[u].x); sts16(sV + sw128(row0 + 8, 56 + 2 * j + wg), r[u].y); }
        }
      }
      fence_async();
      bar_cons();
      MARK(8 + L * 19);
      float o[32];
      wg_fence();
#pragma unroll
      for (int ks = 0; ks < 8; ks++) {
        const int h = ks >> 2, p = 2 * (ks & 3);
        wgmma_rs64(o, phq[0][h][p], phq[1][h][p], p < 6 ? phq[0][h][p < 6 ? p + 1 : 0] : 0u, p < 6 ? phq[1][h][p < 6 ? p + 1 : 0] : 0u, mkdesc(d16, OFF_V + ks * 2048, 1024, 1024, 1), ks);
      }
      wg_commit(); wg_wait<0>(); regfence(o);
      const float iA0 = rcp(o[28] + 1e-6f), iB0 = rcp(o[29] + 1e-6f), iA1 = rcp(o[30] + 1e-6f), iB1 = rcp(o[31] + 1e-6f);
      uint32_t w[14];
      { PTRS
#pragma unroll
      for (int j = 0; j < 7; j++) {
        const bool hb = 8 * j + 2 * q >= 28; const float i0 = hb ? iB0 : iA0, i1 = hb ? iB1 : iA1;
        w[2 * j] = pack(o[4 * j] * i0, o[4 * j + 1] * i0); w[2 * j + 1] = pack(o[4 * j + 2] * i1, o[4 * j + 3] * i1);
        if (j == 0 || ((j ^ c) & 1) == 0) w[2 * j] = tg(w[2 * j], tag);
      }
      slice_store(sf + OO, sh + 2 * OO, w, c & 1);
      hint_post(hme, hs + 2, lane); }
    }
    MARK(9 + L * 19);
    uint4 xr[4];
    if (c < 7) {
      PTRS
      ll_issue<0, 4>(xr, fm + XR + 128 * c, 32);
      uint4 a[28];
      const uint4* pa = fm + OO;
      hint_wait(hrow, hs + 2);
      MARK(10 + L * 19);
      ll_issue<0, 28, true>(a, pa, 32, f2 + 2 * OO);
      float y[32];
      uint32_t st;
#define WOSTEP(i) { ll_check<7 * i, 7, true>(a, pa, 32, tag, f2 + 2 * OO); if (!(i & 1)) st = acquire(); wg_fence(); \
      _Pragma("unroll") for (int ks = 0; ks < 7; ks++) { const uint4 f = a[7 * i + ks]; \
        wgmma_rs64(y, f.x, f.y, f.z, f.w, mkdesc(st, ((i & 1) * 7 + ks) * 2048, 1024, 1024, 1), i | ks); } wg_commit(); }
      WOSTEP(0) WOSTEP(1) WOSTEP(2) WOSTEP(3)
      ll_check<0, 4, false>(xr, fm + XR + 128 * c, 32, tag);
      wg_wait<0>(); regfence(y);
      MARK(11 + L * 19);
#pragma unroll
      for (int u = 0; u < 4; u++) {
        xr[u].x = tg(pack(blo(xr[u].x) + y[8 * u], bhi(xr[u].x) + y[8 * u + 1]), tag); xr[u].y = pack(blo(xr[u].y) + y[8 * u + 2], bhi(xr[u].y) + y[8 * u + 3]);
        xr[u].z = pack(blo(xr[u].z) + y[8 * u + 4], bhi(xr[u].z) + y[8 * u + 5]); xr[u].w = pack(blo(xr[u].w) + y[8 * u + 6], bhi(xr[u].w) + y[8 * u + 7]);
        stll(fm + X1 + 128 * c + u * 32, xr[u].x, xr[u].y, xr[u].z, xr[u].w);
      }
      hint_post(hme, hs + 3, lane);
    } else {
      PTRS
      hint_post(hme, hs + 3, lane);
      acquire(); acquire();
      hint_wait(g_H + (t * 8 + warp) * 8, hs + 3);
      ll_issue<0, 4>(xr, fm + X1, 32); ll_check<0, 4, false>(xr, fm + X1, 32, tag);
      MARK(10 + L * 19); MARK(11 + L * 19);
    }
    uint32_t hf[56];
    float rr0, rr1;
    {
      PTRS
      uint4 a[28];
      const uint4* pa = fm + X1;
      auto grp = [&](int i) -> const uint4* { const int k = i + c; return pa + ((k >= 7 ? k - 7 : k) - i) * 128; };
#pragma unroll
      for (int u = 0; u < 4; u++) a[u] = xr[u];
      float y[96], z[16];
#define F1STAGE(i) { if (i > 0) ll_check<4 * i, 4, false>(a, grp(i), 32, tag); const uint32_t st = acquire(); wg_fence(); \
      _Pragma("unroll") for (int ks = 0; ks < 4; ks++) { const uint4 f = a[4 * i + ks]; \
        wgmma_rs192(y, f.x, f.y, f.z, f.w, mkdesc(st, (ks >> 1) * 12288 + (ks & 1) * 2048, 4096, 1024, 1), i | ks); \
        wgmma_rs32(z, f.x, f.y, f.z, f.w, mkdesc(st, 24576 + ks * 1024, 512, 512, 2), i | ks); } \
      wg_commit(); if (i > 0) { wg_wait<1>(); release(); if (i < 4) ll_issue<(i < 4 ? 4 * i + 12 : 0), 4>(a, grp(i + 3), 32); } }
      F1STAGE(0)
      hint_wait(hrow, hs + 3);
      MARK(12 + L * 19);
      ll_issue<4, 4>(a, grp(1), 32); ll_issue<8, 4>(a, grp(2), 32); ll_issue<12, 4>(a, grp(3), 32);
      if (c < 7) {
        float s0 = 0.f, s1 = 0.f, v0 = 0.f, v1 = 0.f;
#pragma unroll
        for (int u = 0; u < 4; u++) { s0 += (blo(xr[u].x) + bhi(xr[u].x)) + (blo(xr[u].z) + bhi(xr[u].z)); s1 += (blo(xr[u].y) + bhi(xr[u].y)) + (blo(xr[u].w) + bhi(xr[u].w)); }
        s0 = qsum(s0) * (1.f / 64); s1 = qsum(s1) * (1.f / 64);
#pragma unroll
        for (int u = 0; u < 4; u++) {
          const float d0 = blo(xr[u].x) - s0, d1 = bhi(xr[u].x) - s0, d2 = blo(xr[u].z) - s0, d3 = bhi(xr[u].z) - s0;
          const float d4 = blo(xr[u].y) - s1, d5 = bhi(xr[u].y) - s1, d6 = blo(xr[u].w) - s1, d7 = bhi(xr[u].w) - s1;
          v0 += (d0 * d0 + d1 * d1) + (d2 * d2 + d3 * d3); v1 += (d4 * d4 + d5 * d5) + (d6 * d6 + d7 * d7);
        }
        v0 = qsum(v0); v1 = qsum(v1);
        if (q == 0) stll(g_ST + ((t * 8 + warp) * 8 + c) * 8 + (ln_ >> 2), tg(__float_as_uint(s0), tag), __float_as_uint(v0), __float_as_uint(s1), __float_as_uint(v1));
      }
      if (LAG < 2) release();
      if (LAG < 1) release();
#define LAGREL if (LAG > 0) release(); if (LAG > 1) release();
      F1STAGE(1) MARK(13 + L * 19); F1STAGE(2) F1STAGE(3)
      uint4 sv[2];
      const uint4* ps = g_ST + ((t * 8 + warp) * 8 + 2 * (laneid() & 3)) * 8 + (laneid() >> 2);
      ll_issue<0, 2>(sv, ps, q < 3 ? 8 : 0);
      F1STAGE(4)
      ll_check<0, 2, false>(sv, ps, q < 3 ? 8 : 0, tag);
      const float wb = q < 3 ? 1.f : 0.f;
      const float ma = __uint_as_float(sv[0].x), mb = __uint_as_float(sv[1].x), mc = __uint_as_float(sv[0].z), md = __uint_as_float(sv[1].z);
      const float m0 = qsum(ma + wb * mb) * (1.f / 7), m1 = qsum(mc + wb * md) * (1.f / 7);
      const float v0 = qsum(__uint_as_float(sv[0].y) + 64.f * (ma - m0) * (ma - m0) + wb * (__uint_as_float(sv[1].y) + 64.f * (mb - m0) * (mb - m0)));
      const float v1 = qsum(__uint_as_float(sv[0].w) + 64.f * (mc - m1) * (mc - m1) + wb * (__uint_as_float(sv[1].w) + 64.f * (md - m1) * (md - m1)));
      const float e0 = v0 * (1.f / 448) + 1e-5f, e1 = v1 * (1.f / 448) + 1e-5f;
      rr0 = 1.f / e0; rr1 = 1.f / e1;
      auto fold = [&](float m, float sd) -> uint32_t {
        const float mh = blo(pack(-m, 0.f)), sh_ = blo(pack(sd, 0.f));
        return q == 0 ? pack(mh, -m - mh) : q == 1 ? pack(mh, sh_) : q == 2 ? pack(sd - sh_, 0.f) : 0u;
      };
      const uint32_t fa = fold(m0, sqrtf(e0)), fb = fold(m1, sqrtf(e1));
      if (L == 0) asm volatile("bar.sync 4, 288;" ::: "memory");
      wg_fence();
      wgmma_rs192(y, fa, fb, 0u, 0u, mkdesc(d16, OFF_CB, 512, 0, 2), 1);
      wgmma_rs32(z, fa, fb, 0u, 0u, mkdesc(d16, OFF_CB + 3072, 512, 0, 2), 1);
      F1STAGE(5) F1STAGE(6)
      wg_wait<0>(); release(); LAGREL regfence(y); regfence(z);
      MARK(14 + L * 19);
#pragma unroll
      for (int j = 0; j < 56; j++) {
        uint32_t r; asm("cvt.rn.relu.bf16x2.f32 %0, %1, %2;" : "=r"(r) : "f"(j < 48 ? y[j < 48 ? 2 * j + 1 : 0] : z[j < 48 ? 0 : 2 * j - 95]), "f"(j < 48 ? y[j < 48 ? 2 * j : 0] : z[j < 48 ? 0 : 2 * j - 96]));
        asm("mul.bf16x2 %0, %1, %1;" : "=r"(hf[j]) : "r"(r));
      }
    }
    MARK(15 + L * 19);
    {
      PTRS
      float ya[32], yb[32];
      uint4* pp = g_P + ((t * 8 + warp) * 8 + c) * 28 * 32 + ln_;
#define F2STORE(j, Y) { regfence(Y); _Pragma("unroll") for (int u = 0; u < 4; u++) \
      stll(pp + (4 * (j) + u) * 32, tg(pack(Y[8 * u] * rr0, Y[8 * u + 1] * rr0), tag), pack(Y[8 * u + 2] * rr1, Y[8 * u + 3] * rr1), \
           pack(Y[8 * u + 4] * rr0, Y[8 * u + 5] * rr0), pack(Y[8 * u + 6] * rr1, Y[8 * u + 7] * rr1)); if ((j) >= 5) hint_post(hme, hs + (4 + (j)), lane); }
#define F2PASS(j, Y, Z) { const uint32_t st = acquire(); wg_fence(); \
      _Pragma("unroll") for (int ks = 0; ks < 14; ks++) wgmma_rs64(Y, hf[4 * ks], hf[4 * ks + 1], hf[4 * ks + 2], hf[4 * ks + 3], mkdesc(st, ks * 2048, 1024, 1024, 1), ks); \
      wg_commit(); if (j > 0) { wg_wait<1>(); release(); F2STORE(j - 1, Z) } }
      const uint4* pr = g_P + ((t * 8 + c) * 8 * 28 + warp) * 32 + ln_;
      uint4 p[8], p2[8]; uint2 xa, xb, xc, xd; uint32_t ba, bb, bc, bd;
      const uint32_t ptag = tag;
      const uint32_t* hred = g_H + (t * 8 + c) * 8 + (ln_ & 7);
      F2PASS(0, ya, yb) F2PASS(1, yb, ya) F2PASS(2, ya, yb) F2PASS(3, yb, ya)
      F2PASS(4, ya, yb)
      RISSUE(0, p, xa, xb, ba, bb)
      F2PASS(5, yb, ya)
      REDU(0, p, xa, xb, ba, bb)
      if (L == 0) { xw[0][0] = tg(xw[0][0], 0); RPUB(0) }
      F2PASS(6, ya, yb)
      RISSUE(1, p, xa, xb, ba, bb)
      wg_wait<0>(); release(); F2STORE(6, ya)
      MARK(16 + L * 19);
      if (L == 0) asm volatile("bar.sync 8, 288;" ::: "memory");
      if (wg) hint_wait(hred, hs + 9);
      RISSUE(2, p2, xc, xd, bc, bd)
      REDU(1, p, xa, xb, ba, bb)
      if (L == 0) { xw[1][0] = tg(xw[1][0], 0); RPUB(1) }
      MARK(17 + L * 19);
      REDU(2, p2, xc, xd, bc, bd)
      if (L == 0) { xw[2][0] = tg(xw[2][0], 0); RPUB(2) }
    }
    MARK(18 + L * 19);
  }
  {
    PTRS
    uint32_t* op = (uint32_t*)(out + XOFF(ln_));
#define OUT(u) { op[u * 64] = xw[u][0]; op[u * 64 + 1792] = xw[u][1]; op[u * 64 + 4] = xw[u][2]; op[u * 64 + 1796] = xw[u][3]; }
    OUT(0) OUT(1) OUT(2)
    if (wg == 0) { RLAST(0u, 20u) OUT(3) }
    else if (warp == 7) {
      if (t == 0 && lane == 0) g_WQF[c] = 0;
      if (lane < 8) stll(g_S2 + (t * 8 + c) * 8 + lane, 0, 0, 0, 0);
      if (lane < 4) { stll(g_CS + blockIdx.x * 4 + lane, 0, 0, 0, 0); if (blockIdx.x < 68) stll(g_CS + 512 + blockIdx.x * 4 + lane, 0, 0, 0, 0); }
    }
  }
  MARK(38); GT(39);
  }
}

typedef CUresult (*EncFn)(CUtensorMap*, CUtensorMapDataType, cuuint32_t, void*, const cuuint64_t*, const cuuint64_t*, const cuuint32_t*, const cuuint32_t*,
                          CUtensorMapInterleave, CUtensorMapSwizzle, CUtensorMapL2promotion, CUtensorMapFloatOOBfill);

extern "C" void kernel_launch(void* const* d_in, const int* in_sizes, int n_in, void* d_out, int out_size) {
  static EncFn enc = nullptr;
  if (!enc) {
    void* fn = nullptr; cudaDriverEntryPointQueryResult qr;
    cudaGetDriverEntryPoint("cuTensorMapEncodeTiled", &fn, cudaEnableDefault, &qr);
    enc = (EncFn)fn;
    cudaFuncSetAttribute(fused_kernel, cudaFuncAttributeMaxDynamicSharedMemorySize, SMEM_BYTES);
  }
  CUtensorMap mQKV, mWO, mW1, mW1b, mW2, mW2b, mX;
  const cuuint32_t es[3] = {1, 1, 1};
  auto enc2 = [&](CUtensorMap* m, void* p, cuuint64_t cols, cuuint64_t rows, cuuint32_t bc, cuuint32_t br) {
    const cuuint64_t dims[2] = {cols, rows}, str[1] = {cols * 2}; const cuuint32_t box[2] = {bc, br};
    enc(m, CU_TENSOR_MAP_DATA_TYPE_BFLOAT16, 2, p, dims, str, box, es, CU_TENSOR_MAP_INTERLEAVE_NONE,
        bc == 64 ? CU_TENSOR_MAP_SWIZZLE_128B : CU_TENSOR_MAP_SWIZZLE_64B, CU_TENSOR_MAP_L2_PROMOTION_L2_128B, CU_TENSOR_MAP_FLOAT_OOB_FILL_NONE);
  };
  enc2(&mQKV, d_in[1], 1344, 448, 64, 112); enc2(&mWO, d_in[3], 448, 448, 64, 112); enc2(&mW1b, d_in[5], 1792, 448, 32, 32);
  enc2(&mX, d_in[0], 448, 2048, 64, 128);
  enc2(&mW2, d_in[7], 448, 1792, 64, 96); enc2(&mW2b, d_in[7], 448, 1792, 64, 16);
  {
    const cuuint64_t dims[3] = {64, 448, 28}, str[2] = {3584, 128}; const cuuint32_t box[3] = {64, 32, 3};
    enc(&mW1, CU_TENSOR_MAP_DATA_TYPE_BFLOAT16, 3, d_in[5], dims, str, box, es, CU_TENSOR_MAP_INTERLEAVE_NONE, CU_TENSOR_MAP_SWIZZLE_128B,
        CU_TENSOR_MAP_L2_PROMOTION_L2_128B, CU_TENSOR_MAP_FLOAT_OOB_FILL_NONE);
  }
  typedef const __nv_bfloat16* BP;
  fused_kernel<<<128, 384, SMEM_BYTES>>>(mQKV, mWO, mW1, mW1b, mW2, mW2b, mX, (BP)d_in[1], (BP)d_in[2], (BP)d_in[3], (BP)d_in[5], (BP)d_in[6], (BP)d_in[7], (BP)d_in[8],
                                         (__nv_bfloat16*)d_out);
}
```

```cpp
#include <cuda_runtime.h>
#include <cuda_bf16.h>
#include <cuda.h>
#include <stdint.h>

constexpr int NST = 6, STAGE = 28672;
constexpr int OFF_PHIK = NST * STAGE;
constexpr int OFF_V = OFF_PHIK + 32768;
constexpr int OFF_WPHI = OFF_V + 16384;
constexpr int OFF_CB = OFF_WPHI + 7168;
constexpr int OFF_BAR = OFF_CB + 3584;
constexpr int SMEM_BYTES = OFF_BAR + 16 * NST + 8;
constexpr int FR = 16 * 8 * 28 * 32;
constexpr int SPIN = 1 << 18;

__device__ uint4 g_F[3 * FR];
constexpr int XR = 0, OO = FR, X1 = 2 * FR;
__device__ uint4 g_P[8 * FR];
__device__ uint4 g_ST[16 * 8 * 8 * 8];
__device__ uint4 g_KVP[8 * 16 * 1024];
__device__ uint2 g_KVR[8 * 1024];
__device__ uint4 g_CS[784];
__device__ uint4 g_S2[16 * 8 * 8];
__device__ uint4 g_WQ[8 * 6 * (STAGE / 16)];
__device__ uint32_t g_WQF[8];
__device__ uint32_t g_H[16 * 8 * 8];
#define MARK(i)
#define GT(i)

__device__ __forceinline__ uint32_t s2u(const void* p) { return (uint32_t)__cvta_generic_to_shared(p); }
__device__ __forceinline__ void mbar_init(uint32_t b, uint32_t c) { asm volatile("mbarrier.init.shared::cta.b64 [%0], %1;" ::"r"(b), "r"(c)); }
__device__ __forceinline__ void mbar_expect(uint32_t b, uint32_t tx) { asm volatile("mbarrier.arrive.expect_tx.shared::cta.b64 _, [%0], %1;" ::"r"(b), "r"(tx) : "memory"); }
__device__ __forceinline__ void mbar_arrive(uint32_t b) { asm volatile("mbarrier.arrive.shared::cta.b64 _, [%0];" ::"r"(b) : "memory"); }
__device__ __forceinline__ void mbar_wait(uint32_t b, uint32_t ph) {
  uint32_t ok = 0;
#pragma unroll 1
  for (int it = 0; it < SPIN && !ok; it++)
    asm volatile("{.reg .pred p; mbarrier.try_wait.parity.shared::cta.b64 p,[%1],%2; selp.u32 %0,1,0,p;}" : "=r"(ok) : "r"(b), "r"(ph) : "memory");
}
__device__ __forceinline__ void tma2d(uint32_t dst, const CUtensorMap* m, int c0, int c1, uint32_t bar) {
  asm volatile("cp.async.bulk.tensor.2d.shared::cluster.global.mbarrier::complete_tx::bytes [%0], [%1, {%3, %4}], [%2];"
               ::"r"(dst), "l"(m), "r"(bar), "r"(c0), "r"(c1) : "memory");
}
__device__ __forceinline__ void tma3d(uint32_t dst, const CUtensorMap* m, int c0, int c1, int c2, uint32_t bar) {
  asm volatile("cp.async.bulk.tensor.3d.shared::cluster.global.mbarrier::complete_tx::bytes [%0], [%1, {%3, %4, %5}], [%2];"
               ::"r"(dst), "l"(m), "r"(bar), "r"(c0), "r"(c1), "r"(c2) : "memory");
}
__device__ __forceinline__ void l2pf(const void* p, uint32_t bytes) { asm volatile("cp.async.bulk.prefetch.L2.global [%0], %1;" ::"l"(p), "r"(bytes) : "memory"); }
__device__ __forceinline__ void wg_fence() { asm volatile("wgmma.fence.sync.aligned;" ::: "memory"); }
__device__ __forceinline__ void wg_commit() { asm volatile("wgmma.commit_group.sync.aligned;" ::: "memory"); }
template <int N> __device__ __forceinline__ void wg_wait() { asm volatile("wgmma.wait_group.sync.aligned %0;" ::"n"(N) : "memory"); }
template <int N> __device__ __forceinline__ void regfence(float (&d)[N]) {
#pragma unroll
  for (int i = 0; i < N; i++) asm volatile("" : "+f"(d[i])::"memory");
}
__device__ __forceinline__ void bar_cons() { asm volatile("bar.sync 1, 256;" ::: "memory"); }
__device__ __forceinline__ void fence_async() { asm volatile("fence.proxy.async.shared::cta;" ::: "memory"); }
struct Desc { uint32_t lo, hi; };
__device__ __forceinline__ Desc mkdesc(uint32_t base16, uint32_t off, uint32_t lbo, uint32_t sbo, uint32_t swz) {
  return Desc{base16 + ((off >> 4) | ((lbo >> 4) << 16)), (sbo >> 4) | (swz << 30)};
}
__device__ __forceinline__ uint4 ldll(const uint4* p) {
  uint4 v; asm volatile("ld.relaxed.gpu.global.v4.u32 {%0,%1,%2,%3}, [%4];" : "=r"(v.x), "=r"(v.y), "=r"(v.z), "=r"(v.w) : "l"(p) : "memory"); return v;
}
__device__ __forceinline__ uint2 ldll2(const uint2* p) {
  uint2 v; asm volatile("ld.relaxed.gpu.global.v2.u32 {%0,%1}, [%2];" : "=r"(v.x), "=r"(v.y) : "l"(p) : "memory"); return v;
}
__device__ __forceinline__ void stll(uint4* p, uint32_t x, uint32_t y, uint32_t z, uint32_t w) {
  asm volatile("st.relaxed.gpu.global.v4.u32 [%0], {%1,%2,%3,%4};" ::"l"(p), "r"(x), "r"(y), "r"(z), "r"(w) : "memory");
}
__device__ __forceinline__ void stll2(void* p, uint32_t x, uint32_t y) {
  asm volatile("st.relaxed.gpu.global.v2.u32 [%0], {%1,%2};" ::"l"(p), "r"(x), "r"(y) : "memory");
}
__device__ __forceinline__ int laneid() { int l; asm volatile("mov.u32 %0, %%laneid;" : "=r"(l)); return l; }
__device__ __forceinline__ uint32_t tg(uint32_t w, uint32_t tag) { return (w & ~1u) | tag; }
__device__ __forceinline__ uint32_t pack(float lo, float hi) {
  uint32_t r; asm("cvt.rn.bf16x2.f32 %0, %1, %2;" : "=r"(r) : "f"(hi), "f"(lo)); return r;
}
__device__ __forceinline__ float blo(uint32_t w) { return __uint_as_float(w << 16); }
__device__ __forceinline__ float bhi(uint32_t w) { return __uint_as_float(w & 0xffff0000u); }
__device__ __forceinline__ float ex2(float x) { float r; asm("ex2.approx.ftz.f32 %0, %1;" : "=f"(r) : "f"(x)); return r; }
__device__ __forceinline__ float rcp(float x) { float r; asm("rcp.approx.ftz.f32 %0, %1;" : "=f"(r) : "f"(x)); return r; }
__device__ __forceinline__ float qsum(float v) { v += __shfl_xor_sync(~0u, v, 1); v += __shfl_xor_sync(~0u, v, 2); return v; }
__device__ __forceinline__ void sts32(uint32_t a, uint32_t v) { asm volatile("st.shared.u32 [%0], %1;" ::"r"(a), "r"(v) : "memory"); }
__device__ __forceinline__ void sts16(uint32_t a, uint32_t v) { asm volatile("st.shared.u16 [%0], %1;" ::"r"(a), "h"((uint16_t)v) : "memory"); }
__device__ __forceinline__ void sts128(uint32_t a, uint32_t x, uint32_t y, uint32_t z, uint32_t w) {
  asm volatile("st.shared.v4.u32 [%0], {%1,%2,%3,%4};" ::"r"(a), "r"(x), "r"(y), "r"(z), "r"(w) : "memory");
}
__device__ __forceinline__ uint32_t sw128(int row, int col) { return row * 128 + ((((col >> 3) ^ row) & 7) << 4) + (col & 7) * 2; }

__device__ __forceinline__ void wgmma_rs56(float (&d)[28], const uint32_t a0, const uint32_t a1, const uint32_t a2, const uint32_t a3, Desc db, int sd) {
  asm volatile("{.reg .pred p; .reg .b64 da, db; setp.ne.b32 p, %33, 0; mov.b64 db, {%32, %34};\n wgmma.mma_async.sync.aligned.m64n56k16.f32.bf16.bf16 {%0,%1,%2,%3,%4,%5,%6,%7,%8,%9,%10,%11,%12,%13,%14,%15,%16,%17,%18,%19,%20,%21,%22,%23,%24,%25,%26,%27}, {%28,%29,%30,%31}, db, p, 1, 1, 1;}"
   : "+f"(d[0]),"+f"(d[1]),"+f"(d[2]),"+f"(d[3]),"+f"(d[4]),"+f"(d[5]),"+f"(d[6]),"+f"(d[7]),"+f"(d[8]),"+f"(d[9]),"+f"(d[10]),"+f"(d[11]),"+f"(d[12]),"+f"(d[13]),"+f"(d[14]),"+f"(d[15]),"+f"(d[16]),"+f"(d[17]),"+f"(d[18]),"+f"(d[19]),"+f"(d[20]),"+f"(d[21]),"+f"(d[22]),"+f"(d[23]),"+f"(d[24]),"+f"(d[25]),"+f"(d[26]),"+f"(d[27])
   : "r"(a0),"r"(a1),"r"(a2),"r"(a3),"r"(db.lo),"r"(sd),"r"(db.hi));
}
__device__ __forceinline__ void wgmma_rs64(float (&d)[32], const uint32_t a0, const uint32_t a1, const uint32_t a2, const uint32_t a3, Desc db, int sd) {
  asm volatile("{.reg .pred p; .reg .b64 da, db; setp.ne.b32 p, %37, 0; mov.b64 db, {%36, %38};\n wgmma.mma_async.sync.aligned.m64n64k16.f32.bf16.bf16 {%0,%1,%2,%3,%4,%5,%6,%7,%8,%9,%10,%11,%12,%13,%14,%15,%16,%17,%18,%19,%20,%21,%22,%23,%24,%25,%26,%27,%28,%29,%30,%31}, {%32,%33,%34,%35}, db, p, 1, 1, 1;}"
   : "+f"(d[0]),"+f"(d[1]),"+f"(d[2]),"+f"(d[3]),"+f"(d[4]),"+f"(d[5]),"+f"(d[6]),"+f"(d[7]),"+f"(d[8]),"+f"(d[9]),"+f"(d[10]),"+f"(d[11]),"+f"(d[12]),"+f"(d[13]),"+f"(d[14]),"+f"(d[15]),"+f"(d[16]),"+f"(d[17]),"+f"(d[18]),"+f"(d[19]),"+f"(d[20]),"+f"(d[21]),"+f"(d[22]),"+f"(d[23]),"+f"(d[24]),"+f"(d[25]),"+f"(d[26]),"+f"(d[27]),"+f"(d[28]),"+f"(d[29]),"+f"(d[30]),"+f"(d[31])
   : "r"(a0),"r"(a1),"r"(a2),"r"(a3),"r"(db.lo),"r"(sd),"r"(db.hi));
}
__device__ __forceinline__ void wgmma_rs192(float (&d)[96], const uint32_t a0, const uint32_t a1, const uint32_t a2, const uint32_t a3, Desc db, int sd) {
  asm volatile("{.reg .pred p; .reg .b64 db; setp.ne.b32 p, %101, 0; mov.b64 db, {%100, %102};\n wgmma.mma_async.sync.aligned.m64n192k16.f32.bf16.bf16 {%0,%1,%2,%3,%4,%5,%6,%7,%8,%9,%10,%11,%12,%13,%14,%15,%16,%17,%18,%19,%20,%21,%22,%23,%24,%25,%26,%27,%28,%29,%30,%31,%32,%33,%34,%35,%36,%37,%38,%39,%40,%41,%42,%43,%44,%45,%46,%47,%48,%49,%50,%51,%52,%53,%54,%55,%56,%57,%58,%59,%60,%61,%62,%63,%64,%65,%66,%67,%68,%69,%70,%71,%72,%73,%74,%75,%76,%77,%78,%79,%80,%81,%82,%83,%84,%85,%86,%87,%88,%89,%90,%91,%92,%93,%94,%95}, {%96,%97,%98,%99}, db, p, 1, 1, 1;}"
   : "+f"(d[0]),"+f"(d[1]),"+f"(d[2]),"+f"(d[3]),"+f"(d[4]),"+f"(d[5]),"+f"(d[6]),"+f"(d[7]),"+f"(d[8]),"+f"(d[9]),"+f"(d[10]),"+f"(d[11]),"+f"(d[12]),"+f"(d[13]),"+f"(d[14]),"+f"(d[15]),"+f"(d[16]),"+f"(d[17]),"+f"(d[18]),"+f"(d[19]),"+f"(d[20]),"+f"(d[21]),"+f"(d[22]),"+f"(d[23]),"+f"(d[24]),"+f"(d[25]),"+f"(d[26]),"+f"(d[27]),"+f"(d[28]),"+f"(d[29]),"+f"(d[30]),"+f"(d[31]),"+f"(d[32]),"+f"(d[33]),"+f"(d[34]),"+f"(d[35]),"+f"(d[36]),"+f"(d[37]),"+f"(d[38]),"+f"(d[39]),"+f"(d[40]),"+f"(d[41]),"+f"(d[42]),"+f"(d[43]),"+f"(d[44]),"+f"(d[45]),"+f"(d[46]),"+f"(d[47]),"+f"(d[48]),"+f"(d[49]),"+f"(d[50]),"+f"(d[51]),"+f"(d[52]),"+f"(d[53]),"+f"(d[54]),"+f"(d[55]),"+f"(d[56]),"+f"(d[57]),"+f"(d[58]),"+f"(d[59]),"+f"(d[60]),"+f"(d[61]),"+f"(d[62]),"+f"(d[63]),"+f"(d[64]),"+f"(d[65]),"+f"(d[66]),"+f"(d[67]),"+f"(d[68]),"+f"(d[69]),"+f"(d[70]),"+f"(d[71]),"+f"(d[72]),"+f"(d[73]),"+f"(d[74]),"+f"(d[75]),"+f"(d[76]),"+f"(d[77]),"+f"(d[78]),"+f"(d[79]),"+f"(d[80]),"+f"(d[81]),"+f"(d[82]),"+f"(d[83]),"+f"(d[84]),"+f"(d[85]),"+f"(d[86]),"+f"(d[87]),"+f"(d[88]),"+f"(d[89]),"+f"(d[90]),"+f"(d[91]),"+f"(d[92]),"+f"(d[93]),"+f"(d[94]),"+f"(d[95])
   : "r"(a0),"r"(a1),"r"(a2),"r"(a3),"r"(db.lo),"r"(sd),"r"(db.hi));
}
__device__ __forceinline__ void wgmma_rs32(float (&d)[16], const uint32_t a0, const uint32_t a1, const uint32_t a2, const uint32_t a3, Desc db, int sd) {
  asm volatile("{.reg .pred p; .reg .b64 db; setp.ne.b32 p, %21, 0; mov.b64 db, {%20, %22};\n wgmma.mma_async.sync.aligned.m64n32k16.f32.bf16.bf16 {%0,%1,%2,%3,%4,%5,%6,%7,%8,%9,%10,%11,%12,%13,%14,%15}, {%16,%17,%18,%19}, db, p, 1, 1, 1;}"
   : "+f"(d[0]),"+f"(d[1]),"+f"(d[2]),"+f"(d[3]),"+f"(d[4]),"+f"(d[5]),"+f"(d[6]),"+f"(d[7]),"+f"(d[8]),"+f"(d[9]),"+f"(d[10]),"+f"(d[11]),"+f"(d[12]),"+f"(d[13]),"+f"(d[14]),"+f"(d[15])
   : "r"(a0),"r"(a1),"r"(a2),"r"(a3),"r"(db.lo),"r"(sd),"r"(db.hi));
}
__device__ __forceinline__ void wgmma_ss32(float (&d)[16], Desc da, Desc db, int sd) {
  asm volatile("{.reg .pred p; .reg .b64 da, db; setp.ne.b32 p, %18, 0; mov.b64 da, {%16, %19}; mov.b64 db, {%17, %19};\n wgmma.mma_async.sync.aligned.m64n32k16.f32.bf16.bf16 {%0,%1,%2,%3,%4,%5,%6,%7,%8,%9,%10,%11,%12,%13,%14,%15}, da, db, p, 1, 1, 1, 1;}"
   : "+f"(d[0]),"+f"(d[1]),"+f"(d[2]),"+f"(d[3]),"+f"(d[4]),"+f"(d[5]),"+f"(d[6]),"+f"(d[7]),"+f"(d[8]),"+f"(d[9]),"+f"(d[10]),"+f"(d[11]),"+f"(d[12]),"+f"(d[13]),"+f"(d[14]),"+f"(d[15])
   : "r"(da.lo),"r"(db.lo),"r"(sd),"r"(db.hi));
}

__device__ __forceinline__ uint4 ldsm4(uint32_t a) {
  uint4 v; asm volatile("ldmatrix.sync.aligned.m8n8.x4.shared.b16 {%0,%1,%2,%3}, [%4];" : "=r"(v.x), "=r"(v.y), "=r"(v.z), "=r"(v.w) : "r"(a) : "memory"); return v;
}
__device__ __forceinline__ void mma16816(float (&d)[4], const uint4& a, uint32_t b0, uint32_t b1) {
  asm("mma.sync.aligned.m16n8k16.row.col.f32.bf16.bf16.f32 {%0,%1,%2,%3}, {%4,%5,%6,%7}, {%8,%9}, {%0,%1,%2,%3};"
      : "+f"(d[0]), "+f"(d[1]), "+f"(d[2]), "+f"(d[3]) : "r"(a.x), "r"(a.y), "r"(a.z), "r"(a.w), "r"(b0), "r"(b1));
}
__device__ __forceinline__ uint32_t bsub(uint32_t a, uint32_t b) { uint32_t r; asm("sub.bf16x2 %0, %1, %2;" : "=r"(r) : "r"(a), "r"(b)); return r; }
__device__ __forceinline__ uint32_t hint_ld(const uint32_t* p) { uint32_t v; asm volatile("ld.relaxed.gpu.global.u32 %0, [%1];" : "=r"(v) : "l"(p) : "memory"); return v; }
template <int S, int N, bool SPL = false, int T> __device__ __forceinline__ void ll_issue(uint4 (&v)[T], const uint4* p, int stride, const uint2* p2 = nullptr) {
#pragma unroll
  for (int i = S; i < S + N; i++) {
    if (SPL && i % 7 == 3) { const uint2 lo = ldll2(p2 + i * 64), hi = ldll2(p2 + i * 64 + 32); v[i] = make_uint4(lo.x, lo.y, hi.x, hi.y); }
    else v[i] = ldll(p + i * stride);
  }
}
template <int S, int N, bool SPL, int T> __device__ __forceinline__ void ll_check(uint4 (&v)[T], const uint4* p, int stride, uint32_t tag, const uint2* p2 = nullptr) {
#pragma unroll 1
  for (int it = 0; it < SPIN; it++) {
    uint32_t bad = 0;
#pragma unroll
    for (int i = S; i < S + N; i++) bad |= (v[i].x ^ tag) | ((SPL && i % 7 == 3) ? (v[i].z ^ tag) : 0u);
    if (!__any_sync(~0u, bad & 1)) break;
    ll_issue<S, N, SPL>(v, p, stride, p2);
  }
}
__device__ __forceinline__ void hint_post(uint32_t* p, uint32_t v, int lane) {
  if (lane == 0) asm volatile("st.relaxed.gpu.global.u32 [%0], %1;" ::"l"(p), "r"(v) : "memory");
}
__device__ __forceinline__ void hint_wait(const uint32_t* p, uint32_t s, uint32_t v = 0xffffu) {
#pragma unroll 1
  for (int it = 0; it < SPIN; it++) {
    if (__all_sync(~0u, v - s < 10u)) break;
    v = hint_ld(p);
  }
}
__device__ __forceinline__ void slice_store(uint4* pf, uint2* ph, const uint32_t (&w)[14], bool odd) {
#pragma unroll
  for (int u = 0; u < 3; u++)
    stll(pf + u * 32, odd ? w[4 * u + 2] : w[4 * u], odd ? w[4 * u + 3] : w[4 * u + 1], odd ? w[4 * u + 4] : w[4 * u + 2], odd ? w[4 * u + 5] : w[4 * u + 3]);
  stll2(ph, odd ? w[0] : w[12], odd ? w[1] : w[13]);
}
template <class F, class M> __device__ __forceinline__ void hedgehog(const float (&d)[28], F sink, M mid) {
  const float L2E = 1.4426950408889634f;
#define HX(G, p) ((p) < 6 ? d[((G) & 1) * 16 + ((p) >> 1) * 4 + ((p) & 1) + ((G) & 2)] : d[12 + (G)])
  float mx[4], mn[4], sp[4], sn[4], ep[4][7], en[4][7];
#pragma unroll
  for (int G = 0; G < 4; G++) {
    mx[G] = mn[G] = HX(G, 0);
#pragma unroll
    for (int p = 1; p < 7; p++) { mx[G] = fmaxf(mx[G], HX(G, p)); mn[G] = fminf(mn[G], HX(G, p)); }
  }
#pragma unroll
  for (int o = 1; o < 4; o <<= 1)
#pragma unroll
    for (int G = 0; G < 4; G++) { mx[G] = fmaxf(mx[G], __shfl_xor_sync(~0u, mx[G], o)); mn[G] = fminf(mn[G], __shfl_xor_sync(~0u, mn[G], o)); }
#pragma unroll
  for (int G = 0; G < 4; G++) {
    const float a = -mx[G] * L2E, b = mn[G] * L2E;
#pragma unroll
    for (int p = 0; p < 7; p++) { ep[G][p] = ex2(fmaf(HX(G, p), L2E, a)); en[G][p] = ex2(fmaf(HX(G, p), -L2E, b)); }
    sp[G] = ((ep[G][0] + ep[G][1]) + (ep[G][2] + ep[G][3])) + ((ep[G][4] + ep[G][5]) + ep[G][6]);
    sn[G] = ((en[G][0] + en[G][1]) + (en[G][2] + en[G][3])) + ((en[G][4] + en[G][5]) + en[G][6]);
    if (G == 1) mid();
  }
#pragma unroll
  for (int o = 1; o < 4; o <<= 1)
#pragma unroll
    for (int G = 0; G < 4; G++) { sp[G] += __shfl_xor_sync(~0u, sp[G], o); sn[G] += __shfl_xor_sync(~0u, sn[G], o); }
#pragma unroll
  for (int G = 0; G < 4; G++) {
    const float a = rcp(sp[G]), b = rcp(sn[G]);
#pragma unroll
    for (int p = 0; p < 7; p++) sink(G >> 1, G & 1, p, pack(ep[G][p] * a, en[G][p] * b));
  }
}
__device__ __forceinline__ void phi_gemm(const float (&x)[28], float (&y)[28], uint32_t wphi, float r0, float r1) {
  uint32_t f[14];
#pragma unroll
  for (int j = 0; j < 14; j++) f[j] = pack(x[2 * j] * (j & 1 ? r1 : r0), x[2 * j + 1] * (j & 1 ? r1 : r0));
  wg_fence();
#pragma unroll
  for (int ks = 0; ks < 3; ks++) wgmma_rs56(y, f[4 * ks], f[4 * ks + 1], f[4 * ks + 2], f[4 * ks + 3], mkdesc(wphi, ks * 2048, 1024, 1024, 1), ks);
  wgmma_rs56(y, f[12], f[13], 0u, 0u, mkdesc(wphi, 3 * 2048, 1024, 1024, 1), 1);
  wg_commit();
}
__device__ __forceinline__ void ln_stats(uint32_t (&xw)[4][4], float* sLN, int warp, int lane, uint4* dst) {
  const int g = lane >> 2; const bool full = warp < 4;
  float s0 = 0.f, s1 = 0.f;
#pragma unroll
  for (int u = 0; u < 4; u++) {
    s0 += (blo(xw[u][0]) + bhi(xw[u][0])) + (blo(xw[u][2]) + bhi(xw[u][2]));
    s1 += (blo(xw[u][1]) + bhi(xw[u][1])) + (blo(xw[u][3]) + bhi(xw[u][3]));
  }
  const float rc = full ? 1.f / 64 : 1.f / 48;
  s0 = qsum(s0); s1 = qsum(s1);
  const float a0 = s0 * rc, a1 = s1 * rc;
  float v0 = 0.f, v1 = 0.f;
#pragma unroll
  for (int u = 0; u < 4; u++)
    if (u < 3 || full) {
#pragma unroll
      for (int k = 0; k < 4; k += 2) {
        float a = blo(xw[u][k]) - a0, b = bhi(xw[u][k]) - a0, c2 = blo(xw[u][k + 1]) - a1, d2 = bhi(xw[u][k + 1]) - a1;
        v0 += a * a + b * b; v1 += c2 * c2 + d2 * d2;
      }
    }
  v0 = qsum(v0); v1 = qsum(v1);
  if ((lane & 3) == 0) *(float4*)(sLN + (g * 8 + warp) * 4) = make_float4(s0, v0, s1, v1);
  if (warp) { asm volatile("bar.arrive 7, 256;" ::: "memory"); return; }
  asm volatile("bar.sync 7, 256;" ::: "memory");
  const float4 ea = *(const float4*)(sLN + (g * 8 + (lane & 3)) * 4), eb = *(const float4*)(sLN + (g * 8 + 4 + (lane & 3)) * 4);
  const float m0 = qsum(ea.x + eb.x) * (1.f / 448), m1 = qsum(ea.z + eb.z) * (1.f / 448);
  const float d0 = ea.x * (1.f / 64) - m0, d1 = eb.x * (1.f / 48) - m0, d2 = ea.z * (1.f / 64) - m1, d3 = eb.z * (1.f / 48) - m1;
  v0 = qsum(ea.y + eb.y + 64.f * d0 * d0 + 48.f * d1 * d1); v1 = qsum(ea.w + eb.w + 64.f * d2 * d2 + 48.f * d3 * d3);
  if ((lane & 3) == 0) stll(dst + g, tg(__float_as_uint(m0), 1), __float_as_uint(rsqrtf(v0 * (1.f / 448) + 1e-5f)), __float_as_uint(m1), __float_as_uint(rsqrtf(v1 * (1.f / 448) + 1e-5f)));
}

__global__ void __launch_bounds__(384, 1)
fused_kernel(const __grid_constant__ CUtensorMap mQKV, const __grid_constant__ CUtensorMap mWO, const __grid_constant__ CUtensorMap mW1,
             const __grid_constant__ CUtensorMap mW1b, const __grid_constant__ CUtensorMap mW2, const __grid_constant__ CUtensorMap mW2b,
             const __grid_constant__ CUtensorMap mX, const __nv_bfloat16* __restrict__ wqkv, const __nv_bfloat16* __restrict__ wphi,
             const __nv_bfloat16* __restrict__ wo, const __nv_bfloat16* __restrict__ w1, const __nv_bfloat16* __restrict__ b1,
             const __nv_bfloat16* __restrict__ w2, const __nv_bfloat16* __restrict__ b2, __nv_bfloat16* __restrict__ out) {
  extern __shared__ __align__(1024) uint8_t sm[];
  const uint32_t sb = s2u(sm);
  const int tid = threadIdx.x, warp = __shfl_sync(~0u, tid >> 5, 0), lane = tid & 31,
            t = blockIdx.x >> 3, c = blockIdx.x & 7;
  const uint32_t bfull = sb + OFF_BAR, bempty = bfull + 8 * NST;

#define XOFF(l) ((t * 128 + c * 16 + ((l) >> 2)) * 448 + warp * 16 + 2 * ((l) & 3))
  if (warp < 8) { MARK(0); GT(19); }
  if (tid == 256) {
    for (int s = 0; s < NST; s++) { mbar_init(bfull + 8 * s, 1); mbar_init(bempty + 8 * s, 8); }
    mbar_init(bempty + 8 * NST, 1);
    asm volatile("fence.mbarrier_init.release.cluster;" ::: "memory");
    fence_async();
    mbar_expect(bempty + 8 * NST, 114688);
    for (int i = 0; i < 7; i++)
      asm volatile("cp.async.bulk.tensor.2d.shared::cluster.global.mbarrier::complete_tx::bytes [%0], [%1, {%3, %4}], [%2];"
                   ::"r"(sb + 2 * STAGE + i * 16384), "l"(&mX), "r"(bempty + 8 * NST), "r"(64 * i), "r"(128 * t) : "memory");
  }
  __syncthreads();
  if (warp >= 8) {
    asm volatile("setmaxnreg.dec.sync.aligned.u32 24;");
    auto issue = [&](int i, int s) {
      const uint32_t dst = sb + s * STAGE, bar = bfull + 8 * s;
      mbar_expect(bar, STAGE);
#pragma unroll 1
      for (int rk = 0; rk < 2; rk++)
      if (i < 4) tma2d(dst + rk * 14336, &mQKV, 448 + 448 * rk + 56 * c, 112 * i, bar);
      else if (i < 8) tma2d(dst + rk * 14336, i < 6 ? &mQKV : &mWO, (i < 6 ? 56 : 64) * c, 224 * (i & 1) + 112 * rk, bar);
      else if (i < 15) { const int k0 = 64 * ((i - 8 + c) % 7) + 32 * rk;
        tma3d(dst + rk * 12288, &mW1, 0, k0, 3 * c, bar); tma2d(dst + 24576 + rk * 2048, &mW1b, 1536 + 32 * c, k0, bar); }
      else { tma2d(dst + rk * 12288, &mW2, 64 * (i - 15), 192 * c + 96 * rk, bar); tma2d(dst + 24576 + rk * 2048, &mW2b, 64 * (i - 15), 1536 + 32 * c + 16 * rk, bar); }
    };
    auto colsum = [&](int job) {
        const int ld4 = job < 112 ? 448 : 336;
        const uint2* wp = (job < 112 ? (const uint2*)w1 + job * 4 : (const uint2*)wqkv + (job - 112) * 4) + (lane >> 2) * ld4 + (lane & 3);
        float s0 = 0.f, s1 = 0.f, s2 = 0.f, s3 = 0.f;
#pragma unroll 8
        for (int i = 0; i < 56; i++) { const uint2 v = __ldg(wp + i * 8 * ld4); s0 += blo(v.x); s1 += bhi(v.x); s2 += blo(v.y); s3 += bhi(v.y); }
#pragma unroll 1
        for (int o = 4; o < 32; o <<= 1) { s0 += __shfl_xor_sync(~0u, s0, o); s1 += __shfl_xor_sync(~0u, s1, o); s2 += __shfl_xor_sync(~0u, s2, o); s3 += __shfl_xor_sync(~0u, s3, o); }
        if (lane < 4) stll(g_CS + job * 4 + lane, tg(__float_as_uint(s0), 1), __float_as_uint(s1), __float_as_uint(s2), __float_as_uint(s3));
      };
    if (warp == 8) {
#pragma unroll 1
      for (int n = 0; n < 44; n++) {
        const int L = n >= 22, i = L ? (n < 28 ? (n - 18) % 6 : n - 22) : n, s = i % 6;
        if (n == 2) asm volatile("bar.sync 2, 288;" ::: "memory");
        mbar_wait(bempty + 8 * s, (i / 6 + (s >= 4 ? L : 0) + 1) & 1);
        if (n == 22) {
          uint32_t v = 0;
#pragma unroll 1
          for (int it = 0; it < SPIN && v < 32; it++) asm volatile("ld.acquire.gpu.global.u32 %0, [%1];" : "=r"(v) : "l"(g_WQF + c) : "memory");
          asm volatile("fence.proxy.async.global;" ::: "memory");
        }
        if (lane == 0) {
          if (n >= 22 && n < 28) {
            mbar_expect(bfull + 8 * s, STAGE);
            asm volatile("cp.async.bulk.shared::cluster.global.mbarrier::complete_tx::bytes [%0], [%1], %2, [%3];"
                         ::"r"(sb + s * STAGE), "l"(g_WQ + c * 10752 + i * (STAGE / 16)), "r"(STAGE), "r"(bfull + 8 * s) : "memory");
          } else issue(i, s);
        }
        __syncwarp();
      }
    } else if (warp == 9) {
      mbar_wait(bfull + 8 * 3, 0);
      if (lane == 0) {
        l2pf((const uint8_t*)wo + blockIdx.x * 3136, 3136);
        l2pf((const uint8_t*)w1 + blockIdx.x * 12544, 12544);
        l2pf((const uint8_t*)w2 + blockIdx.x * 12544, 12544);
      }
      if (blockIdx.x < 112) colsum(blockIdx.x);
      asm volatile("bar.sync 6, 96;" ::: "memory");
#pragma unroll 1
      for (int i = 0; i < 4; i++) {
        const int e = lane < 28 ? lane + 28 * (i & 1) : 0;
        const bool ok = i < 2 || (e < 48 && (e & 15) < 14);
        const int e4 = i < 2 ? (e < 48 ? 48 * c + e : 336 + 8 * c + e) : ok ? 448 + 112 * (e >> 4) + 14 * c + (e & 15) : 448;
        uint4 cv[1];
        ll_issue<0, 1>(cv, g_CS + e4, 0); ll_check<0, 1, false>(cv, g_CS + e4, 0, 1u);
        const uint2 bb = __ldg((const uint2*)b1 + (i < 2 ? e4 : 0));
        const uint32_t h0 = pack(__uint_as_float(cv[0].x), __uint_as_float(cv[0].y)), h1 = pack(__uint_as_float(cv[0].z), __uint_as_float(cv[0].w));
        const uint32_t l0 = pack(__uint_as_float(cv[0].x) - blo(h0), __uint_as_float(cv[0].y) - bhi(h0)), l1 = pack(__uint_as_float(cv[0].z) - blo(h1), __uint_as_float(cv[0].w) - bhi(h1));
#pragma unroll 1
        for (int j = 0; j < (i < 2 ? 5 : 3); j++) {
          const int r = i < 2 ? j : j + 5;
          const uint32_t ad = sb + OFF_CB + (e >> 3) * 512 + r * 64 + ((((e >> 1) ^ (r >> 1)) & 3) << 4) + (e & 1) * 8;
          sts32(ad, j < 2 ? h0 : j == 2 ? l0 : bb.x); sts32(ad + 4, j < 2 ? h1 : j == 2 ? l1 : bb.y);
        }
        if (i & 1) { fence_async(); if (i == 1) asm volatile("bar.arrive 4, 288;" ::: "memory"); else asm volatile("bar.arrive 8, 160; bar.arrive 9, 160;" ::: "memory"); }
      }
    } else if (warp >= 10) {
      const int h = warp - 10;
      uint4 wv[4];
#pragma unroll
      for (int i = 0; i < 4; i++) wv[i] = __ldg((const uint4*)wphi + (2 * c + h) * 98 + min(lane + 32 * i, 97));
#pragma unroll 1
      for (int e = h * 32 + lane; e < 672; e += 64) sts128(sb + OFF_WPHI + e * 16, 0, 0, 0, 0);
      asm volatile("bar.arrive 6, 96;" ::: "memory");
#pragma unroll 1
      for (int i = 0; i < 4; i++) sts128(sb + OFF_PHIK + sw128(h * 128 + i * 32 + lane, 56), 0, 0, 0, 0);
      asm volatile("bar.sync 5, 64;" ::: "memory");
#pragma unroll
      for (int i = 0; i < 4; i++) sts128(sb + OFF_V + h * 2048 + (lane + 32 * i) * 16, wv[i].x, wv[i].y, wv[i].z, wv[i].w);
      __syncwarp();
#pragma unroll 1
      for (int e = lane; e < 392; e += 32) {
        const int d = e / 14, f2 = 2 * (e - 14 * d), k = 28 * h + d;
        const uint32_t v = *(volatile uint32_t*)(sm + OFF_V + h * 2048 + e * 4);
        if (f2 < 24) sts32(sb + OFF_WPHI + sw128(k, 32 * h + f2), v);
        else { sts16(sb + OFF_WPHI + sw128(k, 2 * f2 - 24 + h), v); sts16(sb + OFF_WPHI + sw128(k, 2 * f2 - 22 + h), v >> 16); }
      }
      fence_async();
      asm volatile("bar.arrive 3, 320;" ::: "memory");
      mbar_wait(bfull + 8 * 5, 0);
#pragma unroll 2
      for (int e = t * 672 + h * 32 + lane; e < t * 672 + 672; e += 64) {
        const int r = e >> 3, st = r / 224, rr = r - st * 224, ch = (e & 7) ^ (rr & 7);
        const int k = st < 4 ? 112 * st + (rr >= 112 ? rr - 112 : rr) : 224 * (st - 4) + rr, col = (st < 4 ? (rr >= 112 ? 896 : 448) : 0) + 56 * c + 8 * ch;
        g_WQ[c * 10752 + e] = ch < 7 ? __ldg((const uint4*)(wqkv + k * 1344 + col)) : make_uint4(0, 0, 0, 0);
      }
      __syncwarp();
      if (lane == 0) asm volatile("red.release.gpu.global.add.u32 [%0], 1;" ::"l"(g_WQF + c) : "memory");
      if (h == 0 && blockIdx.x < 84) colsum(112 + blockIdx.x);
    }
  } else {
  asm volatile("setmaxnreg.inc.sync.aligned.u32 240;");

  const int wg = warp >> 2, g = lane >> 2, q = lane & 3;
  const int row0 = warp * 16 + g;
#define PTRS const int ln_ = laneid(); \
  uint4* const fm = g_F + ((t * 8 + warp) * 28) * 32 + ln_;            \
  uint4* const fr = g_F + ((t * 8 + c) * 28 + warp) * 32 + ln_;        \
  uint4* const sf = fm + (7 * (c >> 1) + 4 * (c & 1)) * 32;             \
  uint2* const f2 = (uint2*)(fm - ln_) + ln_;                           \
  uint2* const sh = f2 + (7 * (c >> 1) + 3) * 64 + 32 * (c & 1);        \
  uint32_t* const hme = g_H + (t * 8 + warp) * 8 + c; \
  const uint32_t* const hrow = g_H + (t * 8 + warp) * 8 + (ln_ & 7); \
  (void)fm; (void)fr; (void)sf; (void)f2; (void)sh; (void)hme; (void)hrow;
  float* sLN = (float*)(sm + OFF_V);
  const uint32_t sPK = sb + OFF_PHIK, sV = sb + OFF_V, d16 = (sb & 0x3FFFF) >> 4;
    uint32_t xw[4][4];
#pragma unroll
  for (int i = 0; i < 16; i++) xw[i >> 2][i & 3] = 0;
#define ACQ(I) (mbar_wait(bfull + 8 * ((I) % 6), ((I) / 6 + ((I) % 6 >= 4 ? L : 0)) & 1), d16 + ((I) % 6) * (STAGE >> 4))
#define REL(I) { if (lane == 0) mbar_arrive(bempty + 8 * ((I) % 6)); }
#define RISSUE(m, P, XA, XB, BA, BB) { ll_issue<0, 8>(P, pr + (m) * 256, 896); \
      { const uint4 v_ = ldll(fr + X1 + (m) * 256); XA = make_uint2(v_.x, v_.y); XB = make_uint2(v_.z, v_.w); } \
      const uint32_t* bp = (const uint32_t*)(b2 + 128 * (m) + 16 * warp) + (ln_ & 3); BA = __ldg(bp); BB = __ldg(bp + 4); }
#define REDU(m, P, XA, XB, BA, BB) { ll_check<0, 8, false>(P, pr + (m) * 256, 896, ptag); \
      float e[8] = {blo(XA.x) + blo(BA), bhi(XA.x) + bhi(BA), blo(XA.y) + blo(BA), bhi(XA.y) + bhi(BA), blo(XB.x) + blo(BB), bhi(XB.x) + bhi(BB), blo(XB.y) + blo(BB), bhi(XB.y) + bhi(BB)}; \
      _Pragma("unroll") for (int i = 0; i < 8; i++) { e[0] += blo(P[i].x); e[1] += bhi(P[i].x); e[2] += blo(P[i].y); e[3] += bhi(P[i].y); \
        e[4] += blo(P[i].z); e[5] += bhi(P[i].z); e[6] += blo(P[i].w); e[7] += bhi(P[i].w); } \
      xw[m][0] = pack(e[0], e[1]); xw[m][1] = pack(e[2], e[3]); xw[m][2] = pack(e[4], e[5]); xw[m][3] = pack(e[6], e[7]); }
#define RPUB(m) stll(fr + XR + (m) * 256, tg(xw[m][0], 0), xw[m][1], xw[m][2], xw[m][3]);
#define RLAST(ptag_, hv) { const uint32_t ptag = ptag_; const uint4* pr = g_P + ((t * 8 + c) * 8 * 28 + warp) * 32 + ln_; uint4 p[8]; uint2 xa, xb; uint32_t ba, bb; \
      hint_wait(g_H + (t * 8 + c) * 8 + (ln_ & 7), hv); RISSUE(3, p, xa, xb, ba, bb) REDU(3, p, xa, xb, ba, bb) }
#pragma unroll 1
  for (int L = 0; L < 2; L++) {
    const uint32_t tag = 1 - L;
    uint32_t phq[2][2][7];
    const uint32_t hs = 10 * L;
    {
      PTRS
      uint4 a[28];
      const uint4* pa = fm + XR;
      uint32_t fa = 0, fb = 0;
      float r0 = 1.f, r1 = 1.f;
      if (L == 0) {
        hint_post(hme, 1, lane);
        mbar_wait(bempty + 8 * NST, 0);
        MARK(1);
        const int row = warp * 16 + (ln_ & 15);
        const uint32_t xb = sb + 2 * STAGE + row * 128;
        float cs_[4][4] = {};
#pragma unroll
        for (int ks = 0; ks < 28; ks++) { a[ks] = ldsm4(xb + (ks >> 2) * 16384 + (((2 * (ks & 3) + (ln_ >> 4)) ^ (row & 7)) << 4)); mma16816(cs_[ks & 3], a[ks], 0x3F803F80u, 0x3F803F80u); }
        if (c < 7) {
#pragma unroll
          for (int u = 0; u < 4; u++) { const uint4 v = ldsm4(xb + c * 16384 + (((2 * u + (ln_ >> 4)) ^ (row & 7)) << 4)); stll(fm + XR + 128 * c + u * 32, tg(v.x, tag), v.y, v.z, v.w); }
        }
        const float m0 = ((cs_[0][0] + cs_[1][0]) + (cs_[2][0] + cs_[3][0])) * (1.f / 448), m1 = ((cs_[0][2] + cs_[1][2]) + (cs_[2][2] + cs_[3][2])) * (1.f / 448);
        const uint32_t mb0 = pack(m0, m0), mb1 = pack(m1, m1);
        asm volatile("bar.arrive 2, 288;" ::"r"(mb0) : "memory");
#pragma unroll
        for (int ks = 0; ks < 28; ks++) {
          a[ks].x = bsub(a[ks].x, mb0); a[ks].y = bsub(a[ks].y, mb1); a[ks].z = bsub(a[ks].z, mb0); a[ks].w = bsub(a[ks].w, mb1);
        }
        r0 = m0 - blo(mb0); r1 = m1 - blo(mb1);
      } else {
        ll_issue<0, 14>(a, pa, 32);
        if (wg == 0) { RLAST(1u, 10u) xw[3][0] = tg(xw[3][0], 0); RPUB(3) } else { xw[3][0] = xw[3][1] = xw[3][2] = xw[3][3] = 0; }
        MARK(20);
        ll_issue<14, 7>(a, pa, 32);
        ln_stats(xw, sLN, warp, lane, g_S2 + (t * 8 + c) * 8);
      }
      MARK(2 + L * 19);
      float ak[28], av[28], aq[28], pp[28];
#define KVSTAGE(i) { if (L) ll_check<7 * i, 7, false>(a, pa, 32, tag); const uint32_t st = ACQ(i); wg_fence(); \
      _Pragma("unroll") for (int ks = 0; ks < 7; ks++) { const uint4 f = a[7 * i + ks]; \
        wgmma_rs56(ak, f.x, f.y, f.z, f.w, mkdesc(st, ks * 2048, 1024, 1024, 1), i | ks); \
        wgmma_rs56(av, f.x, f.y, f.z, f.w, mkdesc(st, 14336 + ks * 2048, 1024, 1024, 1), i | ks); } \
      wg_commit(); if (i > 0) { wg_wait<1>(); REL(i + 5) } }
      KVSTAGE(0) KVSTAGE(1)
      uint4 sv[1];
      const uint4* ps = g_S2 + (t * 8 + warp) * 8 + (ln_ >> 2);
      if (L) { ll_issue<21, 7>(a, pa, 32); ll_issue<0, 1>(sv, ps, 0); }
      else {
        float c0[2][4] = {}, c1[2][4] = {};
#pragma unroll
        for (int ks = 0; ks < 28; ks++) { mma16816(c0[ks & 1], a[ks], a[ks].x, a[ks].z); mma16816(c1[ks & 1], a[ks], a[ks].y, a[ks].w); }
        const int src = (ln_ & 28) | (g >> 1);
        const float q0 = __shfl_sync(~0u, (g & 1) ? c0[0][1] + c0[1][1] : c0[0][0] + c0[1][0], src), q1 = __shfl_sync(~0u, (g & 1) ? c1[0][3] + c1[1][3] : c1[0][2] + c1[1][2], src);
        r0 = rsqrtf(fmaxf(q0 * (1.f / 448) - r0 * r0, 0.f) + 1e-5f); r1 = rsqrtf(fmaxf(q1 * (1.f / 448) - r1 * r1, 0.f) + 1e-5f);
      }
      KVSTAGE(2) KVSTAGE(3)
      if (L) {
        if (wg) asm volatile("bar.sync 9, 160;" ::: "memory"); else asm volatile("bar.sync 8, 160;" ::: "memory");
        ll_check<0, 1, false>(sv, ps, 0, 1u);
        const float m0 = -__uint_as_float(sv[0].x), m1 = -__uint_as_float(sv[0].z), h0 = blo(pack(m0, 0.f)), h1 = blo(pack(m1, 0.f));
        r0 = __uint_as_float(sv[0].y); r1 = __uint_as_float(sv[0].w);
        fa = q == 2 ? pack(0.f, h0) : q == 3 ? pack(m0 - h0, h0) : 0u; fb = q == 2 ? pack(0.f, h1) : q == 3 ? pack(m1 - h1, h1) : 0u;
      } else {
        asm volatile("bar.sync 3, 320;" ::: "memory");
      }
      wg_fence();
      wgmma_rs56(ak, fa, fb, 0u, 0u, mkdesc(d16, OFF_CB + 1024, 512, 0, 2), 1);
      wgmma_rs56(av, fa, fb, 0u, 0u, mkdesc(d16, OFF_CB + 2048, 512, 0, 2), 1);
      wg_commit();
      wg_wait<0>(); REL(3) regfence(ak); regfence(av);
      MARK(3 + L * 19);
      phi_gemm(ak, pp, d16 + (OFF_WPHI >> 4), r0, r1);
#pragma unroll
      for (int j = 0; j < 7; j++) {
        const int n = 8 * j + 2 * q, n2 = n < 28 ? n : n + 4;
        sts32(sV + sw128(row0, n2), pack(av[4 * j] * r0, av[4 * j + 1] * r0)); sts32(sV + sw128(row0 + 8, n2), pack(av[4 * j + 2] * r1, av[4 * j + 3] * r1));
      }
      { const int n2 = 28 + 2 * (q & 1) + 32 * (q >> 1); const uint32_t v = (q & 1) ? 0u : 0x3F80u; sts32(sV + sw128(row0, n2), v); sts32(sV + sw128(row0 + 8, n2), v); }
      wg_wait<0>(); regfence(pp);
      hedgehog(pp, [&](int r, int h, int p, uint32_t v) { sts32(sPK + h * 16384 + sw128(row0 + 8 * r, 8 * p + 2 * q), v); }, [] {});
      fence_async();
      bar_cons();
      MARK(4 + L * 19);
      float kv[16];
      wg_fence();
#pragma unroll
      for (int ks = 0; ks < 8; ks++) wgmma_ss32(kv, mkdesc(d16 + wg * 1024, OFF_PHIK + ks * 2048, 1024, 1024, 1), mkdesc(d16 + wg * 4, OFF_V + ks * 2048, 1024, 1024, 1), ks);
      wg_commit(); wg_wait<0>(); regfence(kv);
      const int ln2 = laneid();
#pragma unroll
      for (int u = 0; u < 4; u++) {
        float e[4];
#pragma unroll
        for (int i = 0; i < 4; i++) e[i] = kv[4 * u + i];
        stll(g_KVP + (c * 16 + t) * 1024 + wg * 512 + u * 128 + (warp & 3) * 32 + ln2, tg(__float_as_uint(e[0]), tag), __float_as_uint(e[1]), __float_as_uint(e[2]), __float_as_uint(e[3]));
      }
      MARK(5 + L * 19);
      uint4 k4[4];
      const uint4* pk = g_KVP + (c * 16 + 4 * (ln2 & 3)) * 1024 + 64 * t + warp * 8 + (ln2 >> 2);
#pragma unroll
      for (int i = 0; i < 2; i++) {
        const uint32_t st = ACQ(4 + i); wg_fence();
#pragma unroll
        for (int ks = 0; ks < 14; ks++) { const uint4 f = a[14 * i + ks]; wgmma_rs56(aq, f.x, f.y, f.z, f.w, mkdesc(st, ks * 2048, 1024, 1024, 1), i | ks); }
        if (i == 1) wgmma_rs56(aq, fa, fb, 0u, 0u, mkdesc(d16, OFF_CB, 512, 0, 2), 1);
        wg_commit();
        if (i == 1) ll_issue<0, 4>(k4, pk, 1024);
      }
      ll_check<0, 4, false>(k4, pk, 1024, tag);
      float s0 = 0, s1 = 0, s2 = 0, s3 = 0;
#pragma unroll
      for (int i = 0; i < 4; i++) { s0 += __uint_as_float(k4[i].x); s1 += __uint_as_float(k4[i].y); s2 += __uint_as_float(k4[i].z); s3 += __uint_as_float(k4[i].w); }
      s0 = qsum(s0); s1 = qsum(s1); s2 = qsum(s2); s3 = qsum(s3);
      if (q == 0) stll2(g_KVR + c * 1024 + 64 * t + warp * 8 + (ln2 >> 2), tg(pack(s0, s1), tag), pack(s2, s3));
      MARK(6 + L * 19);
      wg_wait<0>(); REL(4) REL(5) regfence(aq);
      phi_gemm(aq, pp, d16 + (OFF_WPHI >> 4), r0, r1);
      bar_cons();
#pragma unroll
      for (int i = 0; i < 4; i++) sts128(sV + warp * 2048 + (lane + i * 32) * 16, 0, 0, 0, 0);
      wg_wait<0>(); regfence(pp);
      uint2 r[4];
      const uint2* pr = g_KVR + c * 1024 + wg * 512 + (warp & 3) * 32 + ln2;
      hedgehog(pp, [&](int r, int h, int p, uint32_t v) { phq[r][h][p] = v; }, [&] {
#pragma unroll
        for (int u = 0; u < 4; u++) r[u] = ldll2(pr + u * 128); });
      MARK(7 + L * 19);
#pragma unroll 1
      for (int it = 0; it < SPIN; it++) {
        if (!__any_sync(~0u, ((r[0].x ^ tag) | (r[1].x ^ tag) | (r[2].x ^ tag) | (r[3].x ^ tag)) & 1)) break;
#pragma unroll
        for (int u = 0; u < 4; u++) r[u] = ldll2(pr + u * 128);
      }
#pragma unroll
      for (int u = 0; u < 4; u++) {
        const int d = 8 * u + 2 * q;
        if (d < 28) { sts32(sV + sw128(row0, 28 * wg + d), r[u].x); sts32(sV + sw128(row0 + 8, 28 * wg + d), r[u].y); }
        else if (d == 28) {
#pragma unroll
          for (int j = 0; j < 4; j++) { sts16(sV + sw128(row0, 56 + 2 * j + wg), r[u].x); sts16(sV + sw128(row0 + 8, 56 + 2 * j + wg), r[u].y); }
        }
      }
      fence_async();
      bar_cons();
      MARK(8 + L * 19);
      float o[32];
      wg_fence();
#pragma unroll
      for (int ks = 0; ks < 8; ks++) {
        const int h = ks >> 2, p = 2 * (ks & 3);
        wgmma_rs64(o, phq[0][h][p], phq[1][h][p], p < 6 ? phq[0][h][p < 6 ? p + 1 : 0] : 0u, p < 6 ? phq[1][h][p < 6 ? p + 1 : 0] : 0u, mkdesc(d16, OFF_V + ks * 2048, 1024, 1024, 1), ks);
      }
      wg_commit(); wg_wait<0>(); regfence(o);
      const float iA0 = rcp(o[28] + 1e-6f), iB0 = rcp(o[29] + 1e-6f), iA1 = rcp(o[30] + 1e-6f), iB1 = rcp(o[31] + 1e-6f);
      uint32_t w[14];
      { PTRS
#pragma unroll
      for (int j = 0; j < 7; j++) {
        const bool hb = 8 * j + 2 * q >= 28; const float i0 = hb ? iB0 : iA0, i1 = hb ? iB1 : iA1;
        w[2 * j] = pack(o[4 * j] * i0, o[4 * j + 1] * i0); w[2 * j + 1] = pack(o[4 * j + 2] * i1, o[4 * j + 3] * i1);
        if (j == 0 || ((j ^ c) & 1) == 0) w[2 * j] = tg(w[2 * j], tag);
      }
      slice_store(sf + OO, sh + 2 * OO, w, c & 1);
      hint_post(hme, hs + 2, lane); }
    }
    MARK(9 + L * 19);
    uint4 xr[4];
    if (c < 7) {
      PTRS
      ll_issue<0, 4>(xr, fm + XR + 128 * c, 32);
      uint4 a[28];
      const uint4* pa = fm + OO;
      hint_wait(hrow, hs + 2);
      MARK(10 + L * 19);
      ll_issue<0, 28, true>(a, pa, 32, f2 + 2 * OO);
      float y[32];
      uint32_t st;
#define WOSTEP(i) { ll_check<7 * i, 7, true>(a, pa, 32, tag, f2 + 2 * OO); if (!(i & 1)) st = ACQ(6 + i / 2); wg_fence(); \
      _Pragma("unroll") for (int ks = 0; ks < 7; ks++) { const uint4 f = a[7 * i + ks]; \
        wgmma_rs64(y, f.x, f.y, f.z, f.w, mkdesc(st, ((i & 1) * 7 + ks) * 2048, 1024, 1024, 1), i | ks); } wg_commit(); }
      WOSTEP(0) WOSTEP(1) WOSTEP(2) WOSTEP(3)
      ll_check<0, 4, false>(xr, fm + XR + 128 * c, 32, tag);
      wg_wait<0>(); regfence(y);
      MARK(11 + L * 19);
#pragma unroll
      for (int u = 0; u < 4; u++) {
        xr[u].x = tg(pack(blo(xr[u].x) + y[8 * u], bhi(xr[u].x) + y[8 * u + 1]), tag); xr[u].y = pack(blo(xr[u].y) + y[8 * u + 2], bhi(xr[u].y) + y[8 * u + 3]);
        xr[u].z = pack(blo(xr[u].z) + y[8 * u + 4], bhi(xr[u].z) + y[8 * u + 5]); xr[u].w = pack(blo(xr[u].w) + y[8 * u + 6], bhi(xr[u].w) + y[8 * u + 7]);
        stll(fm + X1 + 128 * c + u * 32, xr[u].x, xr[u].y, xr[u].z, xr[u].w);
      }
      hint_post(hme, hs + 3, lane);
    } else {
      PTRS
      hint_post(hme, hs + 3, lane);
      (void)ACQ(6); (void)ACQ(7);
      hint_wait(g_H + (t * 8 + warp) * 8, hs + 3);
      ll_issue<0, 4>(xr, fm + X1, 32); ll_check<0, 4, false>(xr, fm + X1, 32, tag);
      MARK(10 + L * 19); MARK(11 + L * 19);
    }
    uint32_t hf[56];
    float rr0, rr1;
    {
      PTRS
      uint4 a[28];
      const uint4* pa = fm + X1;
      auto grp = [&](int i) -> const uint4* { const int k = i + c; return pa + ((k >= 7 ? k - 7 : k) - i) * 128; };
#pragma unroll
      for (int u = 0; u < 4; u++) a[u] = xr[u];
      float y[96], z[16];
#define F1STAGE(i) { if (i > 0) ll_check<4 * i, 4, false>(a, grp(i), 32, tag); const uint32_t st = ACQ(8 + i); wg_fence(); \
      _Pragma("unroll") for (int ks = 0; ks < 4; ks++) { const uint4 f = a[4 * i + ks]; \
        wgmma_rs192(y, f.x, f.y, f.z, f.w, mkdesc(st, (ks >> 1) * 12288 + (ks & 1) * 2048, 4096, 1024, 1), i | ks); \
        wgmma_rs32(z, f.x, f.y, f.z, f.w, mkdesc(st, 24576 + ks * 1024, 512, 512, 2), i | ks); } \
      wg_commit(); if (i > 0) { wg_wait<1>(); REL(6 + i) if (i < 4) ll_issue<(i < 4 ? 4 * i + 12 : 0), 4>(a, grp(i + 3), 32); } }
      F1STAGE(0)
      hint_wait(hrow, hs + 3);
      MARK(12 + L * 19);
      ll_issue<4, 4>(a, grp(1), 32); ll_issue<8, 4>(a, grp(2), 32); ll_issue<12, 4>(a, grp(3), 32);
      if (c < 7) {
        float s0 = 0.f, s1 = 0.f, v0 = 0.f, v1 = 0.f;
#pragma unroll
        for (int u = 0; u < 4; u++) { s0 += (blo(xr[u].x) + bhi(xr[u].x)) + (blo(xr[u].z) + bhi(xr[u].z)); s1 += (blo(xr[u].y) + bhi(xr[u].y)) + (blo(xr[u].w) + bhi(xr[u].w)); }
        s0 = qsum(s0) * (1.f / 64); s1 = qsum(s1) * (1.f / 64);
#pragma unroll
        for (int u = 0; u < 4; u++) {
          const float d0 = blo(xr[u].x) - s0, d1 = bhi(xr[u].x) - s0, d2 = blo(xr[u].z) - s0, d3 = bhi(xr[u].z) - s0;
          const float d4 = blo(xr[u].y) - s1, d5 = bhi(xr[u].y) - s1, d6 = blo(xr[u].w) - s1, d7 = bhi(xr[u].w) - s1;
          v0 += (d0 * d0 + d1 * d1) + (d2 * d2 + d3 * d3); v1 += (d4 * d4 + d5 * d5) + (d6 * d6 + d7 * d7);
        }
        v0 = qsum(v0); v1 = qsum(v1);
        if (q == 0) stll(g_ST + ((t * 8 + warp) * 8 + c) * 8 + (ln_ >> 2), tg(__float_as_uint(s0), tag), __float_as_uint(v0), __float_as_uint(s1), __float_as_uint(v1));
      }
      REL(6)
      F1STAGE(1) MARK(13 + L * 19); F1STAGE(2) F1STAGE(3)
      uint4 sv[2];
      const uint4* ps = g_ST + ((t * 8 + warp) * 8 + 2 * (laneid() & 3)) * 8 + (laneid() >> 2);
      ll_issue<0, 2>(sv, ps, q < 3 ? 8 : 0);
      F1STAGE(4)
      ll_check<0, 2, false>(sv, ps, q < 3 ? 8 : 0, tag);
      const float wb = q < 3 ? 1.f : 0.f;
      const float ma = __uint_as_float(sv[0].x), mb = __uint_as_float(sv[1].x), mc = __uint_as_float(sv[0].z), md = __uint_as_float(sv[1].z);
      const float m0 = qsum(ma + wb * mb) * (1.f / 7), m1 = qsum(mc + wb * md) * (1.f / 7);
      const float v0 = qsum(__uint_as_float(sv[0].y) + 64.f * (ma - m0) * (ma - m0) + wb * (__uint_as_float(sv[1].y) + 64.f * (mb - m0) * (mb - m0)));
      const float v1 = qsum(__uint_as_float(sv[0].w) + 64.f * (mc - m1) * (mc - m1) + wb * (__uint_as_float(sv[1].w) + 64.f * (md - m1) * (md - m1)));
      const float e0 = v0 * (1.f / 448) + 1e-5f, e1 = v1 * (1.f / 448) + 1e-5f;
      rr0 = 1.f / e0; rr1 = 1.f / e1;
      auto fold = [&](float m, float sd) -> uint32_t {
        const float mh = blo(pack(-m, 0.f)), sh_ = blo(pack(sd, 0.f));
        return q == 0 ? pack(mh, -m - mh) : q == 1 ? pack(mh, sh_) : q == 2 ? pack(sd - sh_, 0.f) : 0u;
      };
      const uint32_t fa = fold(m0, sqrtf(e0)), fb = fold(m1, sqrtf(e1));
      if (L == 0) asm volatile("bar.sync 4, 288;" ::: "memory");
      wg_fence();
      wgmma_rs192(y, fa, fb, 0u, 0u, mkdesc(d16, OFF_CB, 512, 0, 2), 1);
      wgmma_rs32(z, fa, fb, 0u, 0u, mkdesc(d16, OFF_CB + 3072, 512, 0, 2), 1);
      F1STAGE(5) F1STAGE(6)
      wg_wait<0>(); REL(13) REL(14) regfence(y); regfence(z);
      MARK(14 + L * 19);
#pragma unroll
      for (int j = 0; j < 56; j++) {
        uint32_t r; asm("cvt.rn.relu.bf16x2.f32 %0, %1, %2;" : "=r"(r) : "f"(j < 48 ? y[j < 48 ? 2 * j + 1 : 0] : z[j < 48 ? 0 : 2 * j - 95]), "f"(j < 48 ? y[j < 48 ? 2 * j : 0] : z[j < 48 ? 0 : 2 * j - 96]));
        asm("mul.bf16x2 %0, %1, %1;" : "=r"(hf[j]) : "r"(r));
      }
    }
    MARK(15 + L * 19);
    {
      PTRS
      float ya[32], yb[32];
      uint4* pp = g_P + ((t * 8 + warp) * 8 + c) * 28 * 32 + ln_;
#define F2STORE(j, Y) { regfence(Y); _Pragma("unroll") for (int u = 0; u < 4; u++) \
      stll(pp + (4 * (j) + u) * 32, tg(pack(Y[8 * u] * rr0, Y[8 * u + 1] * rr0), tag), pack(Y[8 * u + 2] * rr1, Y[8 * u + 3] * rr1), \
           pack(Y[8 * u + 4] * rr0, Y[8 * u + 5] * rr0), pack(Y[8 * u + 6] * rr1, Y[8 * u + 7] * rr1)); if ((j) >= 5) hint_post(hme, hs + (4 + (j)), lane); }
#define F2PASS(j, Y, Z) { const uint32_t st = ACQ(15 + j); wg_fence(); \
      _Pragma("unroll") for (int ks = 0; ks < 14; ks++) wgmma_rs64(Y, hf[4 * ks], hf[4 * ks + 1], hf[4 * ks + 2], hf[4 * ks + 3], mkdesc(st, ks * 2048, 1024, 1024, 1), ks); \
      wg_commit(); if (j > 0) { wg_wait<1>(); REL(14 + j) F2STORE(j - 1, Z) } }
      const uint4* pr = g_P + ((t * 8 + c) * 8 * 28 + warp) * 32 + ln_;
      uint4 p[8], p2[8]; uint2 xa, xb, xc, xd; uint32_t ba, bb, bc, bd;
      const uint32_t ptag = tag;
      const uint32_t* hred = g_H + (t * 8 + c) * 8 + (ln_ & 7);
      F2PASS(0, ya, yb) F2PASS(1, yb, ya) F2PASS(2, ya, yb) F2PASS(3, yb, ya)
      F2PASS(4, ya, yb)
      RISSUE(0, p, xa, xb, ba, bb)
      F2PASS(5, yb, ya)
      REDU(0, p, xa, xb, ba, bb)
      if (L == 0) { xw[0][0] = tg(xw[0][0], 0); RPUB(0) }
      F2PASS(6, ya, yb)
      RISSUE(1, p, xa, xb, ba, bb)
      wg_wait<0>(); REL(21) F2STORE(6, ya)
      MARK(16 + L * 19);
      if (wg) hint_wait(hred, hs + 9);
      RISSUE(2, p2, xc, xd, bc, bd)
      REDU(1, p, xa, xb, ba, bb)
      if (L == 0) { xw[1][0] = tg(xw[1][0], 0); RPUB(1) }
      MARK(17 + L * 19);
      REDU(2, p2, xc, xd, bc, bd)
      if (L == 0) { xw[2][0] = tg(xw[2][0], 0); RPUB(2) }
    }
    MARK(18 + L * 19);
  }
  {
    PTRS
    uint32_t* op = (uint32_t*)(out + XOFF(ln_));
#define OUT(u) { op[u * 64] = xw[u][0]; op[u * 64 + 1792] = xw[u][1]; op[u * 64 + 4] = xw[u][2]; op[u * 64 + 1796] = xw[u][3]; }
    OUT(0) OUT(1) OUT(2)
    if (wg == 0) { RLAST(0u, 20u) OUT(3) }
    else if (warp == 7) {
      if (t == 0 && lane == 0) g_WQF[c] = 0;
      if (lane < 8) stll(g_S2 + (t * 8 + c) * 8 + lane, 0, 0, 0, 0);
      if (lane < 4) { stll(g_CS + blockIdx.x * 4 + lane, 0, 0, 0, 0); if (blockIdx.x < 68) stll(g_CS + 512 + blockIdx.x * 4 + lane, 0, 0, 0, 0); }
    }
  }
  MARK(38); GT(39);
  }
}

typedef CUresult (*EncFn)(CUtensorMap*, CUtensorMapDataType, cuuint32_t, void*, const cuuint64_t*, const cuuint64_t*, const cuuint32_t*, const cuuint32_t*,
                          CUtensorMapInterleave, CUtensorMapSwizzle, CUtensorMapL2promotion, CUtensorMapFloatOOBfill);

extern "C" void kernel_launch(void* const* d_in, const int* in_sizes, int n_in, void* d_out, int out_size) {
  static EncFn enc = nullptr;
  if (!enc) {
    void* fn = nullptr; cudaDriverEntryPointQueryResult qr;
    cudaGetDriverEntryPoint("cuTensorMapEncodeTiled", &fn, cudaEnableDefault, &qr);
    enc = (EncFn)fn;
    cudaFuncSetAttribute(fused_kernel, cudaFuncAttributeMaxDynamicSharedMemorySize, SMEM_BYTES);
  }
  CUtensorMap mQKV, mWO, mW1, mW1b, mW2, mW2b, mX;
  const cuuint32_t es[3] = {1, 1, 1};
  auto enc2 = [&](CUtensorMap* m, void* p, cuuint64_t cols, cuuint64_t rows, cuuint32_t bc, cuuint32_t br) {
    const cuuint64_t dims[2] = {cols, rows}, str[1] = {cols * 2}; const cuuint32_t box[2] = {bc, br};
    enc(m, CU_TENSOR_MAP_DATA_TYPE_BFLOAT16, 2, p, dims, str, box, es, CU_TENSOR_MAP_INTERLEAVE_NONE,
        bc == 64 ? CU_TENSOR_MAP_SWIZZLE_128B : CU_TENSOR_MAP_SWIZZLE_64B, CU_TENSOR_MAP_L2_PROMOTION_L2_128B, CU_TENSOR_MAP_FLOAT_OOB_FILL_NONE);
  };
  enc2(&mQKV, d_in[1], 1344, 448, 64, 112); enc2(&mWO, d_in[3], 448, 448, 64, 112); enc2(&mW1b, d_in[5], 1792, 448, 32, 32);
  enc2(&mX, d_in[0], 448, 2048, 64, 128);
  enc2(&mW2, d_in[7], 448, 1792, 64, 96); enc2(&mW2b, d_in[7], 448, 1792, 64, 16);
  {
    const cuuint64_t dims[3] = {64, 448, 28}, str[2] = {3584, 128}; const cuuint32_t box[3] = {64, 32, 3};
    enc(&mW1, CU_TENSOR_MAP_DATA_TYPE_BFLOAT16, 3, d_in[5], dims, str, box, es, CU_TENSOR_MAP_INTERLEAVE_NONE, CU_TENSOR_MAP_SWIZZLE_128B,
        CU_TENSOR_MAP_L2_PROMOTION_L2_128B, CU_TENSOR_MAP_FLOAT_OOB_FILL_NONE);
  }
  typedef const __nv_bfloat16* BP;
  fused_kernel<<<128, 384, SMEM_BYTES>>>(mQKV, mWO, mW1, mW1b, mW2, mW2b, mX, (BP)d_in[1], (BP)d_in[2], (BP)d_in[3], (BP)d_in[5], (BP)d_in[6], (BP)d_in[7], (BP)d_in[8],
                                         (__nv_bfloat16*)d_out);
}
```

```cpp
#include <cuda_runtime.h>
#include <cuda_bf16.h>
#include <cuda.h>
#include <stdint.h>

constexpr int NST = 6, STAGE = 28672;
constexpr int OFF_PHIK = NST * STAGE;
constexpr int OFF_V = OFF_PHIK + 32768;
constexpr int OFF_WPHI = OFF_V + 16384;
constexpr int OFF_CB = OFF_WPHI + 7168;
constexpr int OFF_BAR = OFF_CB + 3584;
constexpr int SMEM_BYTES = OFF_BAR + 16 * NST + 8;
constexpr int FR = 16 * 8 * 28 * 32;
constexpr int SPIN = 1 << 18;

__device__ uint4 g_F[3 * FR];
constexpr int XR = 0, OO = FR, X1 = 2 * FR;
__device__ uint4 g_P[8 * FR];
__device__ uint4 g_ST[16 * 8 * 8 * 8];
__device__ uint4 g_KVP[8 * 16 * 1024];
__device__ uint2 g_KVR[8 * 1024];
__device__ uint4 g_CS[784];
__device__ uint4 g_S2[16 * 8 * 8];
__device__ uint4 g_WQ[8 * 6 * (STAGE / 16)];
__device__ uint32_t g_WQF[8];
__device__ uint32_t g_H[16 * 8 * 8];
#define MARK(i)
#define GT(i)

__device__ __forceinline__ uint32_t s2u(const void* p) { return (uint32_t)__cvta_generic_to_shared(p); }
__device__ __forceinline__ void mbar_init(uint32_t b, uint32_t c) { asm volatile("mbarrier.init.shared::cta.b64 [%0], %1;" ::"r"(b), "r"(c)); }
__device__ __forceinline__ void mbar_expect(uint32_t b, uint32_t tx) { asm volatile("mbarrier.arrive.expect_tx.shared::cta.b64 _, [%0], %1;" ::"r"(b), "r"(tx) : "memory"); }
__device__ __forceinline__ void mbar_arrive(uint32_t b) { asm volatile("mbarrier.arrive.shared::cta.b64 _, [%0];" ::"r"(b) : "memory"); }
__device__ __forceinline__ void mbar_wait(uint32_t b, uint32_t ph) {
  uint32_t ok = 0;
#pragma unroll 1
  for (int it = 0; it < SPIN && !ok; it++)
    asm volatile("{.reg .pred p; mbarrier.try_wait.parity.shared::cta.b64 p,[%1],%2; selp.u32 %0,1,0,p;}" : "=r"(ok) : "r"(b), "r"(ph) : "memory");
}
__device__ __forceinline__ void tma2d(uint32_t dst, const CUtensorMap* m, int c0, int c1, uint32_t bar) {
  asm volatile("cp.async.bulk.tensor.2d.shared::cluster.global.mbarrier::complete_tx::bytes [%0], [%1, {%3, %4}], [%2];"
               ::"r"(dst), "l"(m), "r"(bar), "r"(c0), "r"(c1) : "memory");
}
__device__ __forceinline__ void tma3d(uint32_t dst, const CUtensorMap* m, int c0, int c1, int c2, uint32_t bar) {
  asm volatile("cp.async.bulk.tensor.3d.shared::cluster.global.mbarrier::complete_tx::bytes [%0], [%1, {%3, %4, %5}], [%2];"
               ::"r"(dst), "l"(m), "r"(bar), "r"(c0), "r"(c1), "r"(c2) : "memory");
}
__device__ __forceinline__ void l2pf(const void* p, uint32_t bytes) { asm volatile("cp.async.bulk.prefetch.L2.global [%0], %1;" ::"l"(p), "r"(bytes) : "memory"); }
__device__ __forceinline__ void wg_fence() { asm volatile("wgmma.fence.sync.aligned;" ::: "memory"); }
__device__ __forceinline__ void wg_commit() { asm volatile("wgmma.commit_group.sync.aligned;" ::: "memory"); }
template <int N> __device__ __forceinline__ void wg_wait() { asm volatile("wgmma.wait_group.sync.aligned %0;" ::"n"(N) : "memory"); }
template <int N> __device__ __forceinline__ void regfence(float (&d)[N]) {
#pragma unroll
  for (int i = 0; i < N; i++) asm volatile("" : "+f"(d[i])::"memory");
}
__device__ __forceinline__ void bar_cons() { asm volatile("bar.sync 1, 256;" ::: "memory"); }
__device__ __forceinline__ void fence_async() { asm volatile("fence.proxy.async.shared::cta;" ::: "memory"); }
struct Desc { uint32_t lo, hi; };
__device__ __forceinline__ Desc mkdesc(uint32_t base16, uint32_t off, uint32_t lbo, uint32_t sbo, uint32_t swz) {
  return Desc{base16 + ((off >> 4) | ((lbo >> 4) << 16)), (sbo >> 4) | (swz << 30)};
}
__device__ __forceinline__ uint4 ldll(const uint4* p) {
  uint4 v; asm volatile("ld.relaxed.gpu.global.v4.u32 {%0,%1,%2,%3}, [%4];" : "=r"(v.x), "=r"(v.y), "=r"(v.z), "=r"(v.w) : "l"(p) : "memory"); return v;
}
__device__ __forceinline__ uint2 ldll2(const uint2* p) {
  uint2 v; asm volatile("ld.relaxed.gpu.global.v2.u32 {%0,%1}, [%2];" : "=r"(v.x), "=r"(v.y) : "l"(p) : "memory"); return v;
}
__device__ __forceinline__ void stll(uint4* p, uint32_t x, uint32_t y, uint32_t z, uint32_t w) {
  asm volatile("st.relaxed.gpu.global.v4.u32 [%0], {%1,%2,%3,%4};" ::"l"(p), "r"(x), "r"(y), "r"(z), "r"(w) : "memory");
}
__device__ __forceinline__ void stll2(void* p, uint32_t x, uint32_t y) {
  asm volatile("st.relaxed.gpu.global.v2.u32 [%0], {%1,%2};" ::"l"(p), "r"(x), "r"(y) : "memory");
}
__device__ __forceinline__ int laneid() { int l; asm volatile("mov.u32 %0, %%laneid;" : "=r"(l)); return l; }
__device__ __forceinline__ uint32_t tg(uint32_t w, uint32_t tag) { return (w & ~1u) | tag; }
__device__ __forceinline__ uint32_t pack(float lo, float hi) {
  uint32_t r; asm("cvt.rn.bf16x2.f32 %0, %1, %2;" : "=r"(r) : "f"(hi), "f"(lo)); return r;
}
__device__ __forceinline__ float blo(uint32_t w) { return __uint_as_float(w << 16); }
__device__ __forceinline__ float bhi(uint32_t w) { return __uint_as_float(w & 0xffff0000u); }
__device__ __forceinline__ float ex2(float x) { float r; asm("ex2.approx.ftz.f32 %0, %1;" : "=f"(r) : "f"(x)); return r; }
__device__ __forceinline__ float rcp(float x) { float r; asm("rcp.approx.ftz.f32 %0, %1;" : "=f"(r) : "f"(x)); return r; }
__device__ __forceinline__ float qsum(float v) { v += __shfl_xor_sync(~0u, v, 1); v += __shfl_xor_sync(~0u, v, 2); return v; }
__device__ __forceinline__ void sts32(uint32_t a, uint32_t v) { asm volatile("st.shared.u32 [%0], %1;" ::"r"(a), "r"(v) : "memory"); }
__device__ __forceinline__ void sts16(uint32_t a, uint32_t v) { asm volatile("st.shared.u16 [%0], %1;" ::"r"(a), "h"((uint16_t)v) : "memory"); }
__device__ __forceinline__ void sts128(uint32_t a, uint32_t x, uint32_t y, uint32_t z, uint32_t w) {
  asm volatile("st.shared.v4.u32 [%0], {%1,%2,%3,%4};" ::"r"(a), "r"(x), "r"(y), "r"(z), "r"(w) : "memory");
}
__device__ __forceinline__ uint32_t sw128(int row, int col) { return row * 128 + ((((col >> 3) ^ row) & 7) << 4) + (col & 7) * 2; }

__device__ __forceinline__ void wgmma_rs56(float (&d)[28], const uint32_t a0, const uint32_t a1, const uint32_t a2, const uint32_t a3, Desc db, int sd) {
  asm volatile("{.reg .pred p; .reg .b64 da, db; setp.ne.b32 p, %33, 0; mov.b64 db, {%32, %34};\n wgmma.mma_async.sync.aligned.m64n56k16.f32.bf16.bf16 {%0,%1,%2,%3,%4,%5,%6,%7,%8,%9,%10,%11,%12,%13,%14,%15,%16,%17,%18,%19,%20,%21,%22,%23,%24,%25,%26,%27}, {%28,%29,%30,%31}, db, p, 1, 1, 1;}"
   : "+f"(d[0]),"+f"(d[1]),"+f"(d[2]),"+f"(d[3]),"+f"(d[4]),"+f"(d[5]),"+f"(d[6]),"+f"(d[7]),"+f"(d[8]),"+f"(d[9]),"+f"(d[10]),"+f"(d[11]),"+f"(d[12]),"+f"(d[13]),"+f"(d[14]),"+f"(d[15]),"+f"(d[16]),"+f"(d[17]),"+f"(d[18]),"+f"(d[19]),"+f"(d[20]),"+f"(d[21]),"+f"(d[22]),"+f"(d[23]),"+f"(d[24]),"+f"(d[25]),"+f"(d[26]),"+f"(d[27])
   : "r"(a0),"r"(a1),"r"(a2),"r"(a3),"r"(db.lo),"r"(sd),"r"(db.hi));
}
__device__ __forceinline__ void wgmma_rs64(float (&d)[32], const uint32_t a0, const uint32_t a1, const uint32_t a2, const uint32_t a3, Desc db, int sd) {
  asm volatile("{.reg .pred p; .reg .b64 da, db; setp.ne.b32 p, %37, 0; mov.b64 db, {%36, %38};\n wgmma.mma_async.sync.aligned.m64n64k16.f32.bf16.bf16 {%0,%1,%2,%3,%4,%5,%6,%7,%8,%9,%10,%11,%12,%13,%14,%15,%16,%17,%18,%19,%20,%21,%22,%23,%24,%25,%26,%27,%28,%29,%30,%31}, {%32,%33,%34,%35}, db, p, 1, 1, 1;}"
   : "+f"(d[0]),"+f"(d[1]),"+f"(d[2]),"+f"(d[3]),"+f"(d[4]),"+f"(d[5]),"+f"(d[6]),"+f"(d[7]),"+f"(d[8]),"+f"(d[9]),"+f"(d[10]),"+f"(d[11]),"+f"(d[12]),"+f"(d[13]),"+f"(d[14]),"+f"(d[15]),"+f"(d[16]),"+f"(d[17]),"+f"(d[18]),"+f"(d[19]),"+f"(d[20]),"+f"(d[21]),"+f"(d[22]),"+f"(d[23]),"+f"(d[24]),"+f"(d[25]),"+f"(d[26]),"+f"(d[27]),"+f"(d[28]),"+f"(d[29]),"+f"(d[30]),"+f"(d[31])
   : "r"(a0),"r"(a1),"r"(a2),"r"(a3),"r"(db.lo),"r"(sd),"r"(db.hi));
}
__device__ __forceinline__ void wgmma_rs192(float (&d)[96], const uint32_t a0, const uint32_t a1, const uint32_t a2, const uint32_t a3, Desc db, int sd) {
  asm volatile("{.reg .pred p; .reg .b64 db; setp.ne.b32 p, %101, 0; mov.b64 db, {%100, %102};\n wgmma.mma_async.sync.aligned.m64n192k16.f32.bf16.bf16 {%0,%1,%2,%3,%4,%5,%6,%7,%8,%9,%10,%11,%12,%13,%14,%15,%16,%17,%18,%19,%20,%21,%22,%23,%24,%25,%26,%27,%28,%29,%30,%31,%32,%33,%34,%35,%36,%37,%38,%39,%40,%41,%42,%43,%44,%45,%46,%47,%48,%49,%50,%51,%52,%53,%54,%55,%56,%57,%58,%59,%60,%61,%62,%63,%64,%65,%66,%67,%68,%69,%70,%71,%72,%73,%74,%75,%76,%77,%78,%79,%80,%81,%82,%83,%84,%85,%86,%87,%88,%89,%90,%91,%92,%93,%94,%95}, {%96,%97,%98,%99}, db, p, 1, 1, 1;}"
   : "+f"(d[0]),"+f"(d[1]),"+f"(d[2]),"+f"(d[3]),"+f"(d[4]),"+f"(d[5]),"+f"(d[6]),"+f"(d[7]),"+f"(d[8]),"+f"(d[9]),"+f"(d[10]),"+f"(d[11]),"+f"(d[12]),"+f"(d[13]),"+f"(d[14]),"+f"(d[15]),"+f"(d[16]),"+f"(d[17]),"+f"(d[18]),"+f"(d[19]),"+f"(d[20]),"+f"(d[21]),"+f"(d[22]),"+f"(d[23]),"+f"(d[24]),"+f"(d[25]),"+f"(d[26]),"+f"(d[27]),"+f"(d[28]),"+f"(d[29]),"+f"(d[30]),"+f"(d[31]),"+f"(d[32]),"+f"(d[33]),"+f"(d[34]),"+f"(d[35]),"+f"(d[36]),"+f"(d[37]),"+f"(d[38]),"+f"(d[39]),"+f"(d[40]),"+f"(d[41]),"+f"(d[42]),"+f"(d[43]),"+f"(d[44]),"+f"(d[45]),"+f"(d[46]),"+f"(d[47]),"+f"(d[48]),"+f"(d[49]),"+f"(d[50]),"+f"(d[51]),"+f"(d[52]),"+f"(d[53]),"+f"(d[54]),"+f"(d[55]),"+f"(d[56]),"+f"(d[57]),"+f"(d[58]),"+f"(d[59]),"+f"(d[60]),"+f"(d[61]),"+f"(d[62]),"+f"(d[63]),"+f"(d[64]),"+f"(d[65]),"+f"(d[66]),"+f"(d[67]),"+f"(d[68]),"+f"(d[69]),"+f"(d[70]),"+f"(d[71]),"+f"(d[72]),"+f"(d[73]),"+f"(d[74]),"+f"(d[75]),"+f"(d[76]),"+f"(d[77]),"+f"(d[78]),"+f"(d[79]),"+f"(d[80]),"+f"(d[81]),"+f"(d[82]),"+f"(d[83]),"+f"(d[84]),"+f"(d[85]),"+f"(d[86]),"+f"(d[87]),"+f"(d[88]),"+f"(d[89]),"+f"(d[90]),"+f"(d[91]),"+f"(d[92]),"+f"(d[93]),"+f"(d[94]),"+f"(d[95])
   : "r"(a0),"r"(a1),"r"(a2),"r"(a3),"r"(db.lo),"r"(sd),"r"(db.hi));
}
__device__ __forceinline__ void wgmma_rs32(float (&d)[16], const uint32_t a0, const uint32_t a1, const uint32_t a2, const uint32_t a3, Desc db, int sd) {
  asm volatile("{.reg .pred p; .reg .b64 db; setp.ne.b32 p, %21, 0; mov.b64 db, {%20, %22};\n wgmma.mma_async.sync.aligned.m64n32k16.f32.bf16.bf16 {%0,%1,%2,%3,%4,%5,%6,%7,%8,%9,%10,%11,%12,%13,%14,%15}, {%16,%17,%18,%19}, db, p, 1, 1, 1;}"
   : "+f"(d[0]),"+f"(d[1]),"+f"(d[2]),"+f"(d[3]),"+f"(d[4]),"+f"(d[5]),"+f"(d[6]),"+f"(d[7]),"+f"(d[8]),"+f"(d[9]),"+f"(d[10]),"+f"(d[11]),"+f"(d[12]),"+f"(d[13]),"+f"(d[14]),"+f"(d[15])
   : "r"(a0),"r"(a1),"r"(a2),"r"(a3),"r"(db.lo),"r"(sd),"r"(db.hi));
}
__device__ __forceinline__ void wgmma_ss32(float (&d)[16], Desc da, Desc db, int sd) {
  asm volatile("{.reg .pred p; .reg .b64 da, db; setp.ne.b32 p, %18, 0; mov.b64 da, {%16, %19}; mov.b64 db, {%17, %19};\n wgmma.mma_async.sync.aligned.m64n32k16.f32.bf16.bf16 {%0,%1,%2,%3,%4,%5,%6,%7,%8,%9,%10,%11,%12,%13,%14,%15}, da, db, p, 1, 1, 1, 1;}"
   : "+f"(d[0]),"+f"(d[1]),"+f"(d[2]),"+f"(d[3]),"+f"(d[4]),"+f"(d[5]),"+f"(d[6]),"+f"(d[7]),"+f"(d[8]),"+f"(d[9]),"+f"(d[10]),"+f"(d[11]),"+f"(d[12]),"+f"(d[13]),"+f"(d[14]),"+f"(d[15])
   : "r"(da.lo),"r"(db.lo),"r"(sd),"r"(db.hi));
}

__device__ __forceinline__ uint4 ldsm4(uint32_t a) {
  uint4 v; asm volatile("ldmatrix.sync.aligned.m8n8.x4.shared.b16 {%0,%1,%2,%3}, [%4];" : "=r"(v.x), "=r"(v.y), "=r"(v.z), "=r"(v.w) : "r"(a) : "memory"); return v;
}
__device__ __forceinline__ void mma16816(float (&d)[4], const uint4& a, uint32_t b0, uint32_t b1) {
  asm("mma.sync.aligned.m16n8k16.row.col.f32.bf16.bf16.f32 {%0,%1,%2,%3}, {%4,%5,%6,%7}, {%8,%9}, {%0,%1,%2,%3};"
      : "+f"(d[0]), "+f"(d[1]), "+f"(d[2]), "+f"(d[3]) : "r"(a.x), "r"(a.y), "r"(a.z), "r"(a.w), "r"(b0), "r"(b1));
}
__device__ __forceinline__ uint32_t bsub(uint32_t a, uint32_t b) { uint32_t r; asm("sub.bf16x2 %0, %1, %2;" : "=r"(r) : "r"(a), "r"(b)); return r; }
__device__ __forceinline__ uint32_t hint_ld(const uint32_t* p) { uint32_t v; asm volatile("ld.relaxed.gpu.global.u32 %0, [%1];" : "=r"(v) : "l"(p) : "memory"); return v; }
template <int S, int N, bool SPL = false, int T> __device__ __forceinline__ void ll_issue(uint4 (&v)[T], const uint4* p, int stride, const uint2* p2 = nullptr) {
#pragma unroll
  for (int i = S; i < S + N; i++) {
    if (SPL && i % 7 == 3) { const uint2 lo = ldll2(p2 + i * 64), hi = ldll2(p2 + i * 64 + 32); v[i] = make_uint4(lo.x, lo.y, hi.x, hi.y); }
    else v[i] = ldll(p + i * stride);
  }
}
template <int S, int N, bool SPL, int T> __device__ __forceinline__ void ll_check(uint4 (&v)[T], const uint4* p, int stride, uint32_t tag, const uint2* p2 = nullptr) {
#pragma unroll 1
  for (int it = 0; it < SPIN; it++) {
    uint32_t bad = 0;
#pragma unroll
    for (int i = S; i < S + N; i++) bad |= (v[i].x ^ tag) | ((SPL && i % 7 == 3) ? (v[i].z ^ tag) : 0u);
    if (!__any_sync(~0u, bad & 1)) break;
    ll_issue<S, N, SPL>(v, p, stride, p2);
  }
}
__device__ __forceinline__ void hint_post(uint32_t* p, uint32_t v, int lane) {
  if (lane == 0) asm volatile("st.relaxed.gpu.global.u32 [%0], %1;" ::"l"(p), "r"(v) : "memory");
}
__device__ __forceinline__ void hint_wait(const uint32_t* p, uint32_t s, uint32_t v = 0xffffu) {
#pragma unroll 1
  for (int it = 0; it < SPIN; it++) {
    if (__all_sync(~0u, v - s < 10u)) break;
    v = hint_ld(p);
  }
}
__device__ __forceinline__ void slice_store(uint4* pf, uint2* ph, const uint32_t (&w)[14], bool odd) {
#pragma unroll
  for (int u = 0; u < 3; u++)
    stll(pf + u * 32, odd ? w[4 * u + 2] : w[4 * u], odd ? w[4 * u + 3] : w[4 * u + 1], odd ? w[4 * u + 4] : w[4 * u + 2], odd ? w[4 * u + 5] : w[4 * u + 3]);
  stll2(ph, odd ? w[0] : w[12], odd ? w[1] : w[13]);
}
template <class F, class M> __device__ __forceinline__ void hedgehog(const float (&d)[28], F sink, M mid) {
  const float L2E = 1.4426950408889634f;
#define HX(G, p) ((p) < 6 ? d[((G) & 1) * 16 + ((p) >> 1) * 4 + ((p) & 1) + ((G) & 2)] : d[12 + (G)])
  float mx[4], mn[4], sp[4], sn[4], ep[4][7], en[4][7];
#pragma unroll
  for (int G = 0; G < 4; G++) {
    mx[G] = mn[G] = HX(G, 0);
#pragma unroll
    for (int p = 1; p < 7; p++) { mx[G] = fmaxf(mx[G], HX(G, p)); mn[G] = fminf(mn[G], HX(G, p)); }
  }
#pragma unroll
  for (int o = 1; o < 4; o <<= 1)
#pragma unroll
    for (int G = 0; G < 4; G++) { mx[G] = fmaxf(mx[G], __shfl_xor_sync(~0u, mx[G], o)); mn[G] = fminf(mn[G], __shfl_xor_sync(~0u, mn[G], o)); }
#pragma unroll
  for (int G = 0; G < 4; G++) {
    const float a = -mx[G] * L2E, b = mn[G] * L2E;
#pragma unroll
    for (int p = 0; p < 7; p++) { ep[G][p] = ex2(fmaf(HX(G, p), L2E, a)); en[G][p] = ex2(fmaf(HX(G, p), -L2E, b)); }
    sp[G] = ((ep[G][0] + ep[G][1]) + (ep[G][2] + ep[G][3])) + ((ep[G][4] + ep[G][5]) + ep[G][6]);
    sn[G] = ((en[G][0] + en[G][1]) + (en[G][2] + en[G][3])) + ((en[G][4] + en[G][5]) + en[G][6]);
    if (G == 1) mid();
  }
#pragma unroll
  for (int o = 1; o < 4; o <<= 1)
#pragma unroll
    for (int G = 0; G < 4; G++) { sp[G] += __shfl_xor_sync(~0u, sp[G], o); sn[G] += __shfl_xor_sync(~0u, sn[G], o); }
#pragma unroll
  for (int G = 0; G < 4; G++) {
    const float a = rcp(sp[G]), b = rcp(sn[G]);
#pragma unroll
    for (int p = 0; p < 7; p++) sink(G >> 1, G & 1, p, pack(ep[G][p] * a, en[G][p] * b));
  }
}
__device__ __forceinline__ void phi_gemm(const float (&x)[28], float (&y)[28], uint32_t wphi, float r0, float r1) {
  uint32_t f[14];
#pragma unroll
  for (int j = 0; j < 14; j++) f[j] = pack(x[2 * j] * (j & 1 ? r1 : r0), x[2 * j + 1] * (j & 1 ? r1 : r0));
  wg_fence();
#pragma unroll
  for (int ks = 0; ks < 3; ks++) wgmma_rs56(y, f[4 * ks], f[4 * ks + 1], f[4 * ks + 2], f[4 * ks + 3], mkdesc(wphi, ks * 2048, 1024, 1024, 1), ks);
  wgmma_rs56(y, f[12], f[13], 0u, 0u, mkdesc(wphi, 3 * 2048, 1024, 1024, 1), 1);
  wg_commit();
}
__device__ __forceinline__ void ln_stats(uint32_t (&xw)[4][4], float* sLN, int warp, int lane, uint4* dst) {
  const int g = lane >> 2; const bool full = warp < 4;
  float s0 = 0.f, s1 = 0.f;
#pragma unroll
  for (int u = 0; u < 4; u++) {
    s0 += (blo(xw[u][0]) + bhi(xw[u][0])) + (blo(xw[u][2]) + bhi(xw[u][2]));
    s1 += (blo(xw[u][1]) + bhi(xw[u][1])) + (blo(xw[u][3]) + bhi(xw[u][3]));
  }
  const float rc = full ? 1.f / 64 : 1.f / 48;
  s0 = qsum(s0); s1 = qsum(s1);
  const float a0 = s0 * rc, a1 = s1 * rc;
  float v0 = 0.f, v1 = 0.f;
#pragma unroll
  for (int u = 0; u < 4; u++)
    if (u < 3 || full) {
#pragma unroll
      for (int k = 0; k < 4; k += 2) {
        float a = blo(xw[u][k]) - a0, b = bhi(xw[u][k]) - a0, c2 = blo(xw[u][k + 1]) - a1, d2 = bhi(xw[u][k + 1]) - a1;
        v0 += a * a + b * b; v1 += c2 * c2 + d2 * d2;
      }
    }
  v0 = qsum(v0); v1 = qsum(v1);
  if ((lane & 3) == 0) *(float4*)(sLN + (g * 8 + warp) * 4) = make_float4(s0, v0, s1, v1);
  if (warp) { asm volatile("bar.arrive 7, 256;" ::: "memory"); return; }
  asm volatile("bar.sync 7, 256;" ::: "memory");
  const float4 ea = *(const float4*)(sLN + (g * 8 + (lane & 3)) * 4), eb = *(const float4*)(sLN + (g * 8 + 4 + (lane & 3)) * 4);
  const float m0 = qsum(ea.x + eb.x) * (1.f / 448), m1 = qsum(ea.z + eb.z) * (1.f / 448);
  const float d0 = ea.x * (1.f / 64) - m0, d1 = eb.x * (1.f / 48) - m0, d2 = ea.z * (1.f / 64) - m1, d3 = eb.z * (1.f / 48) - m1;
  v0 = qsum(ea.y + eb.y + 64.f * d0 * d0 + 48.f * d1 * d1); v1 = qsum(ea.w + eb.w + 64.f * d2 * d2 + 48.f * d3 * d3);
  if ((lane & 3) == 0) stll(dst + g, tg(__float_as_uint(m0), 1), __float_as_uint(rsqrtf(v0 * (1.f / 448) + 1e-5f)), __float_as_uint(m1), __float_as_uint(rsqrtf(v1 * (1.f / 448) + 1e-5f)));
}

__global__ void __launch_bounds__(384, 1)
fused_kernel(const __grid_constant__ CUtensorMap mQKV, const __grid_constant__ CUtensorMap mWO, const __grid_constant__ CUtensorMap mW1,
             const __grid_constant__ CUtensorMap mW1b, const __grid_constant__ CUtensorMap mW2, const __grid_constant__ CUtensorMap mW2b,
             const __grid_constant__ CUtensorMap mX, const __nv_bfloat16* __restrict__ wqkv, const __nv_bfloat16* __restrict__ wphi,
             const __nv_bfloat16* __restrict__ wo, const __nv_bfloat16* __restrict__ w1, const __nv_bfloat16* __restrict__ b1,
             const __nv_bfloat16* __restrict__ w2, const __nv_bfloat16* __restrict__ b2, __nv_bfloat16* __restrict__ out) {
  extern __shared__ __align__(1024) uint8_t sm[];
  const uint32_t sb = s2u(sm);
  const int tid = threadIdx.x, warp = __shfl_sync(~0u, tid >> 5, 0), lane = tid & 31,
            t = blockIdx.x >> 3, c = blockIdx.x & 7;
  const uint32_t bfull = sb + OFF_BAR, bempty = bfull + 8 * NST;

#define XOFF(l) ((t * 128 + c * 16 + ((l) >> 2)) * 448 + warp * 16 + 2 * ((l) & 3))
  if (warp < 8) { MARK(0); GT(19); }
  if (tid == 256) {
    for (int s = 0; s < NST; s++) { mbar_init(bfull + 8 * s, 1); mbar_init(bempty + 8 * s, 8); }
    mbar_init(bempty + 8 * NST, 1);
    asm volatile("fence.mbarrier_init.release.cluster;" ::: "memory");
    fence_async();
    mbar_expect(bempty + 8 * NST, 114688);
    for (int i = 0; i < 7; i++)
      asm volatile("cp.async.bulk.tensor.2d.shared::cluster.global.mbarrier::complete_tx::bytes [%0], [%1, {%3, %4}], [%2];"
                   ::"r"(sb + 2 * STAGE + i * 16384), "l"(&mX), "r"(bempty + 8 * NST), "r"(64 * i), "r"(128 * t) : "memory");
  }
  __syncthreads();
  if (warp >= 8) {
    asm volatile("setmaxnreg.dec.sync.aligned.u32 24;");
    auto issue = [&](int i, int s) {
      const uint32_t dst = sb + s * STAGE, bar = bfull + 8 * s;
      mbar_expect(bar, STAGE);
#pragma unroll 1
      for (int rk = 0; rk < 2; rk++)
      if (i < 4) tma2d(dst + rk * 14336, &mQKV, 448 + 448 * rk + 56 * c, 112 * i, bar);
      else if (i < 8) tma2d(dst + rk * 14336, i < 6 ? &mQKV : &mWO, (i < 6 ? 56 : 64) * c, 224 * (i & 1) + 112 * rk, bar);
      else if (i < 15) { const int k0 = 64 * ((i - 8 + c) % 7) + 32 * rk;
        tma3d(dst + rk * 12288, &mW1, 0, k0, 3 * c, bar); tma2d(dst + 24576 + rk * 2048, &mW1b, 1536 + 32 * c, k0, bar); }
      else { tma2d(dst + rk * 12288, &mW2, 64 * (i - 15), 192 * c + 96 * rk, bar); tma2d(dst + 24576 + rk * 2048, &mW2b, 64 * (i - 15), 1536 + 32 * c + 16 * rk, bar); }
    };
    auto colsum = [&](int job) {
        const int ld4 = job < 112 ? 448 : 336;
        const uint2* wp = (job < 112 ? (const uint2*)w1 + job * 4 : (const uint2*)wqkv + (job - 112) * 4) + (lane >> 2) * ld4 + (lane & 3);
        float s0 = 0.f, s1 = 0.f, s2 = 0.f, s3 = 0.f;
#pragma unroll 8
        for (int i = 0; i < 56; i++) { const uint2 v = __ldg(wp + i * 8 * ld4); s0 += blo(v.x); s1 += bhi(v.x); s2 += blo(v.y); s3 += bhi(v.y); }
#pragma unroll 1
        for (int o = 4; o < 32; o <<= 1) { s0 += __shfl_xor_sync(~0u, s0, o); s1 += __shfl_xor_sync(~0u, s1, o); s2 += __shfl_xor_sync(~0u, s2, o); s3 += __shfl_xor_sync(~0u, s3, o); }
        if (lane < 4) stll(g_CS + job * 4 + lane, tg(__float_as_uint(s0), 1), __float_as_uint(s1), __float_as_uint(s2), __float_as_uint(s3));
      };
    if (warp == 8) {
#pragma unroll 1
      for (int n = 0; n < 44; n++) {
        const int L = n >= 22, i = L ? (n < 28 ? (n - 18) % 6 : n - 22) : n, s = i % 6;
        if (n == 2) asm volatile("bar.sync 2, 288;" ::: "memory");
        mbar_wait(bempty + 8 * s, (i / 6 + (s >= 4 ? L : 0) + 1) & 1);
        if (n == 22) {
          uint32_t v = 0;
#pragma unroll 1
          for (int it = 0; it < SPIN && v < 32; it++) asm volatile("ld.acquire.gpu.global.u32 %0, [%1];" : "=r"(v) : "l"(g_WQF + c) : "memory");
          asm volatile("fence.proxy.async.global;" ::: "memory");
        }
        if (lane == 0) {
          if (n >= 22 && n < 28) {
            mbar_expect(bfull + 8 * s, STAGE);
            asm volatile("cp.async.bulk.shared::cluster.global.mbarrier::complete_tx::bytes [%0], [%1], %2, [%3];"
                         ::"r"(sb + s * STAGE), "l"(g_WQ + c * 10752 + i * (STAGE / 16)), "r"(STAGE), "r"(bfull + 8 * s) : "memory");
          } else issue(i, s);
        }
        __syncwarp();
      }
    } else if (warp == 9) {
      mbar_wait(bfull + 8 * 3, 0);
      if (lane == 0) {
        l2pf((const uint8_t*)wo + blockIdx.x * 3136, 3136);
        l2pf((const uint8_t*)w1 + blockIdx.x * 12544, 12544);
        l2pf((const uint8_t*)w2 + blockIdx.x * 12544, 12544);
      }
      if (blockIdx.x < 112) colsum(blockIdx.x);
      asm volatile("bar.sync 6, 96;" ::: "memory");
#pragma unroll 1
      for (int i = 0; i < 4; i++) {
        const int e = lane < 28 ? lane + 28 * (i & 1) : 0;
        const bool ok = i < 2 || (e < 48 && (e & 15) < 14);
        const int e4 = i < 2 ? (e < 48 ? 48 * c + e : 336 + 8 * c + e) : ok ? 448 + 112 * (e >> 4) + 14 * c + (e & 15) : 448;
        uint4 cv[1];
        ll_issue<0, 1>(cv, g_CS + e4, 0); ll_check<0, 1, false>(cv, g_CS + e4, 0, 1u);
        const uint2 bb = __ldg((const uint2*)b1 + (i < 2 ? e4 : 0));
        const uint32_t h0 = pack(__uint_as_float(cv[0].x), __uint_as_float(cv[0].y)), h1 = pack(__uint_as_float(cv[0].z), __uint_as_float(cv[0].w));
        const uint32_t l0 = pack(__uint_as_float(cv[0].x) - blo(h0), __uint_as_float(cv[0].y) - bhi(h0)), l1 = pack(__uint_as_float(cv[0].z) - blo(h1), __uint_as_float(cv[0].w) - bhi(h1));
#pragma unroll 1
        for (int j = 0; j < (i < 2 ? 5 : 3); j++) {
          const int r = i < 2 ? j : j + 5;
          const uint32_t ad = sb + OFF_CB + (e >> 3) * 512 + r * 64 + ((((e >> 1) ^ (r >> 1)) & 3) << 4) + (e & 1) * 8;
          sts32(ad, j < 2 ? h0 : j == 2 ? l0 : bb.x); sts32(ad + 4, j < 2 ? h1 : j == 2 ? l1 : bb.y);
        }
        if (i & 1) { fence_async(); if (i == 1) asm volatile("bar.arrive 4, 288;" ::: "memory"); else asm volatile("bar.arrive 8, 160; bar.arrive 9, 160;" ::: "memory"); }
      }
    } else if (warp >= 10) {
      const int h = warp - 10;
      uint4 wv[4];
#pragma unroll
      for (int i = 0; i < 4; i++) wv[i] = __ldg((const uint4*)wphi + (2 * c + h) * 98 + min(lane + 32 * i, 97));
#pragma unroll 1
      for (int e = h * 32 + lane; e < 672; e += 64) sts128(sb + OFF_WPHI + e * 16, 0, 0, 0, 0);
      asm volatile("bar.arrive 6, 96;" ::: "memory");
#pragma unroll 1
      for (int i = 0; i < 4; i++) sts128(sb + OFF_PHIK + sw128(h * 128 + i * 32 + lane, 56), 0, 0, 0, 0);
      asm volatile("bar.sync 5, 64;" ::: "memory");
#pragma unroll
      for (int i = 0; i < 4; i++) sts128(sb + OFF_V + h * 2048 + (lane + 32 * i) * 16, wv[i].x, wv[i].y, wv[i].z, wv[i].w);
      __syncwarp();
#pragma unroll 1
      for (int e = lane; e < 392; e += 32) {
        const int d = e / 14, f2 = 2 * (e - 14 * d), k = 28 * h + d;
        const uint32_t v = *(volatile uint32_t*)(sm + OFF_V + h * 2048 + e * 4);
        if (f2 < 24) sts32(sb + OFF_WPHI + sw128(k, 32 * h + f2), v);
        else { sts16(sb + OFF_WPHI + sw128(k, 2 * f2 - 24 + h), v); sts16(sb + OFF_WPHI + sw128(k, 2 * f2 - 22 + h), v >> 16); }
      }
      fence_async();
      asm volatile("bar.arrive 3, 320;" ::: "memory");
      mbar_wait(bfull + 8 * 5, 0);
#pragma unroll 2
      for (int e = t * 672 + h * 32 + lane; e < t * 672 + 672; e += 64) {
        const int r = e >> 3, st = r / 224, rr = r - st * 224, ch = (e & 7) ^ (rr & 7);
        const int k = st < 4 ? 112 * st + (rr >= 112 ? rr - 112 : rr) : 224 * (st - 4) + rr, col = (st < 4 ? (rr >= 112 ? 896 : 448) : 0) + 56 * c + 8 * ch;
        g_WQ[c * 10752 + e] = ch < 7 ? __ldg((const uint4*)(wqkv + k * 1344 + col)) : make_uint4(0, 0, 0, 0);
      }
      __syncwarp();
      if (lane == 0) asm volatile("red.release.gpu.global.add.u32 [%0], 1;" ::"l"(g_WQF + c) : "memory");
      if (h == 0 && blockIdx.x < 84) colsum(112 + blockIdx.x);
    }
  } else {
  asm volatile("setmaxnreg.inc.sync.aligned.u32 240;");

  const int wg = warp >> 2, g = lane >> 2, q = lane & 3;
  const int row0 = warp * 16 + g;
#define PTRS const int ln_ = laneid(); \
  uint4* const fm = g_F + ((t * 8 + warp) * 28) * 32 + ln_;            \
  uint4* const fr = g_F + ((t * 8 + c) * 28 + warp) * 32 + ln_;        \
  uint4* const sf = fm + (7 * (c >> 1) + 4 * (c & 1)) * 32;             \
  uint2* const f2 = (uint2*)(fm - ln_) + ln_;                           \
  uint2* const sh = f2 + (7 * (c >> 1) + 3) * 64 + 32 * (c & 1);        \
  uint32_t* const hme = g_H + (t * 8 + warp) * 8 + c; \
  const uint32_t* const hrow = g_H + (t * 8 + warp) * 8 + (ln_ & 7); \
  (void)fm; (void)fr; (void)sf; (void)f2; (void)sh; (void)hme; (void)hrow;
  float* sLN = (float*)(sm + OFF_V);
  const uint32_t sPK = sb + OFF_PHIK, sV = sb + OFF_V, d16 = (sb & 0x3FFFF) >> 4;
    uint32_t xw[4][4];
#pragma unroll
  for (int i = 0; i < 16; i++) xw[i >> 2][i & 3] = 0;
#define ACQ(I) (mbar_wait(bfull + 8 * ((I) % 6), ((I) / 6 + ((I) % 6 >= 4 ? L : 0)) & 1), d16 + ((I) % 6) * (STAGE >> 4))
#define REL(I) { if (lane == 0) mbar_arrive(bempty + 8 * ((I) % 6)); }
#define RISSUE(m, P, XA, XB, BA, BB) { ll_issue<0, 8>(P, pr + (m) * 256, 896); \
      { const uint4 v_ = ldll(fr + X1 + (m) * 256); XA = make_uint2(v_.x, v_.y); XB = make_uint2(v_.z, v_.w); } \
      const uint32_t* bp = (const uint32_t*)(b2 + 128 * (m) + 16 * warp) + (ln_ & 3); BA = __ldg(bp); BB = __ldg(bp + 4); }
#define REDU(m, P, XA, XB, BA, BB) { ll_check<0, 8, false>(P, pr + (m) * 256, 896, ptag); \
      float e[8] = {blo(XA.x) + blo(BA), bhi(XA.x) + bhi(BA), blo(XA.y) + blo(BA), bhi(XA.y) + bhi(BA), blo(XB.x) + blo(BB), bhi(XB.x) + bhi(BB), blo(XB.y) + blo(BB), bhi(XB.y) + bhi(BB)}; \
      _Pragma("unroll") for (int i = 0; i < 8; i++) { e[0] += blo(P[i].x); e[1] += bhi(P[i].x); e[2] += blo(P[i].y); e[3] += bhi(P[i].y); \
        e[4] += blo(P[i].z); e[5] += bhi(P[i].z); e[6] += blo(P[i].w); e[7] += bhi(P[i].w); } \
      xw[m][0] = pack(e[0], e[1]); xw[m][1] = pack(e[2], e[3]); xw[m][2] = pack(e[4], e[5]); xw[m][3] = pack(e[6], e[7]); }
#define RPUB(m) stll(fr + XR + (m) * 256, tg(xw[m][0], 0), xw[m][1], xw[m][2], xw[m][3]);
#define RLAST(ptag_, hv) { const uint32_t ptag = ptag_; const uint4* pr = g_P + ((t * 8 + c) * 8 * 28 + warp) * 32 + ln_; uint4 p[8]; uint2 xa, xb; uint32_t ba, bb; \
      if (ptag_) hint_wait(g_H + (t * 8 + c) * 8 + (ln_ & 7), hv); RISSUE(3, p, xa, xb, ba, bb) REDU(3, p, xa, xb, ba, bb) }
#pragma unroll 1
  for (int L = 0; L < 2; L++) {
    const uint32_t tag = 1 - L;
    uint32_t phq[2][2][7];
    const uint32_t hs = 10 * L;
    {
      PTRS
      uint4 a[28];
      const uint4* pa = fm + XR;
      uint32_t fa = 0, fb = 0;
      float r0 = 1.f, r1 = 1.f;
      if (L == 0) {
        hint_post(hme, 1, lane);
        mbar_wait(bempty + 8 * NST, 0);
        MARK(1);
        const int row = warp * 16 + (ln_ & 15);
        const uint32_t xb = sb + 2 * STAGE + row * 128;
        float cs_[4][4] = {};
#pragma unroll
        for (int ks = 0; ks < 28; ks++) { a[ks] = ldsm4(xb + (ks >> 2) * 16384 + (((2 * (ks & 3) + (ln_ >> 4)) ^ (row & 7)) << 4)); mma16816(cs_[ks & 3], a[ks], 0x3F803F80u, 0x3F803F80u); }
        if (c < 7) {
#pragma unroll
          for (int u = 0; u < 4; u++) { const uint4 v = ldsm4(xb + c * 16384 + (((2 * u + (ln_ >> 4)) ^ (row & 7)) << 4)); stll(fm + XR + 128 * c + u * 32, tg(v.x, tag), v.y, v.z, v.w); }
        }
        const float m0 = ((cs_[0][0] + cs_[1][0]) + (cs_[2][0] + cs_[3][0])) * (1.f / 448), m1 = ((cs_[0][2] + cs_[1][2]) + (cs_[2][2] + cs_[3][2])) * (1.f / 448);
        const uint32_t mb0 = pack(m0, m0), mb1 = pack(m1, m1);
        asm volatile("bar.arrive 2, 288;" ::"r"(mb0) : "memory");
#pragma unroll
        for (int ks = 0; ks < 28; ks++) {
          a[ks].x = bsub(a[ks].x, mb0); a[ks].y = bsub(a[ks].y, mb1); a[ks].z = bsub(a[ks].z, mb0); a[ks].w = bsub(a[ks].w, mb1);
        }
        r0 = m0 - blo(mb0); r1 = m1 - blo(mb1);
      } else {
        ll_issue<0, 14>(a, pa, 32);
        if (wg == 0) { RLAST(1u, 10u) xw[3][0] = tg(xw[3][0], 0); RPUB(3) } else { xw[3][0] = xw[3][1] = xw[3][2] = xw[3][3] = 0; }
        MARK(20);
        ll_issue<14, 7>(a, pa, 32);
#pragma unroll
        for (int u = 21; u < 28; u++) a[u] = make_uint4(0, 0, 0, 0);
      }
      MARK(2 + L * 19);
      float ak[28], av[28], aq[28], pp[28];
#define KVSTAGE(i) { if (L) ll_check<7 * i, 7, false>(a, pa, 32, tag); const uint32_t st = ACQ(i); wg_fence(); \
      _Pragma("unroll") for (int ks = 0; ks < 7; ks++) { const uint4 f = a[7 * i + ks]; \
        wgmma_rs56(ak, f.x, f.y, f.z, f.w, mkdesc(st, ks * 2048, 1024, 1024, 1), i | ks); \
        wgmma_rs56(av, f.x, f.y, f.z, f.w, mkdesc(st, 14336 + ks * 2048, 1024, 1024, 1), i | ks); } \
      wg_commit(); if (i > 0) { wg_wait<1>(); REL(i + 5) } }
      KVSTAGE(0)
      if (L) ln_stats(xw, sLN, warp, lane, g_S2 + (t * 8 + c) * 8);
      KVSTAGE(1)
      uint4 sv[1] = {make_uint4(0, 0, 0, 0)};
      const uint4* ps = g_S2 + (t * 8 + warp) * 8 + (ln_ >> 2);
      if (L) { ll_issue<21, 7>(a, pa, 32); ll_issue<0, 1>(sv, ps, 0); }
      else {
        float c0[2][4] = {}, c1[2][4] = {};
#pragma unroll
        for (int ks = 0; ks < 28; ks++) { mma16816(c0[ks & 1], a[ks], a[ks].x, a[ks].z); mma16816(c1[ks & 1], a[ks], a[ks].y, a[ks].w); }
        const int src = (ln_ & 28) | (g >> 1);
        const float q0 = __shfl_sync(~0u, (g & 1) ? c0[0][1] + c0[1][1] : c0[0][0] + c0[1][0], src), q1 = __shfl_sync(~0u, (g & 1) ? c1[0][3] + c1[1][3] : c1[0][2] + c1[1][2], src);
        r0 = rsqrtf(fmaxf(q0 * (1.f / 448) - r0 * r0, 0.f) + 1e-5f); r1 = rsqrtf(fmaxf(q1 * (1.f / 448) - r1 * r1, 0.f) + 1e-5f);
      }
      KVSTAGE(2) KVSTAGE(3)
      if (L) {
        if (wg) asm volatile("bar.sync 9, 160;" ::: "memory"); else asm volatile("bar.sync 8, 160;" ::: "memory");
        ll_check<0, 1, false>(sv, ps, 0, 1u);
        const float m0 = -__uint_as_float(sv[0].x), m1 = -__uint_as_float(sv[0].z), h0 = blo(pack(m0, 0.f)), h1 = blo(pack(m1, 0.f));
        r0 = __uint_as_float(sv[0].y); r1 = __uint_as_float(sv[0].w);
        fa = q == 2 ? pack(0.f, h0) : q == 3 ? pack(m0 - h0, h0) : 0u; fb = q == 2 ? pack(0.f, h1) : q == 3 ? pack(m1 - h1, h1) : 0u;
      } else {
        asm volatile("bar.sync 3, 320;" ::: "memory");
      }
      wg_fence();
      wgmma_rs56(ak, fa, fb, 0u, 0u, mkdesc(d16, OFF_CB + 1024, 512, 0, 2), 1);
      wgmma_rs56(av, fa, fb, 0u, 0u, mkdesc(d16, OFF_CB + 2048, 512, 0, 2), 1);
      wg_commit();
      wg_wait<0>(); REL(3) regfence(ak); regfence(av);
      MARK(3 + L * 19);
      phi_gemm(ak, pp, d16 + (OFF_WPHI >> 4), r0, r1);
#pragma unroll
      for (int j = 0; j < 7; j++) {
        const int n = 8 * j + 2 * q, n2 = n < 28 ? n : n + 4;
        sts32(sV + sw128(row0, n2), pack(av[4 * j] * r0, av[4 * j + 1] * r0)); sts32(sV + sw128(row0 + 8, n2), pack(av[4 * j + 2] * r1, av[4 * j + 3] * r1));
      }
      { const int n2 = 28 + 2 * (q & 1) + 32 * (q >> 1); const uint32_t v = (q & 1) ? 0u : 0x3F80u; sts32(sV + sw128(row0, n2), v); sts32(sV + sw128(row0 + 8, n2), v); }
      wg_wait<0>(); regfence(pp);
      hedgehog(pp, [&](int r, int h, int p, uint32_t v) { sts32(sPK + h * 16384 + sw128(row0 + 8 * r, 8 * p + 2 * q), v); }, [] {});
      fence_async();
      bar_cons();
      MARK(4 + L * 19);
      float kv[16];
      wg_fence();
#pragma unroll
      for (int ks = 0; ks < 8; ks++) wgmma_ss32(kv, mkdesc(d16 + wg * 1024, OFF_PHIK + ks * 2048, 1024, 1024, 1), mkdesc(d16 + wg * 4, OFF_V + ks * 2048, 1024, 1024, 1), ks);
      wg_commit(); wg_wait<0>(); regfence(kv);
      const int ln2 = laneid();
#pragma unroll
      for (int u = 0; u < 4; u++) {
        float e[4];
#pragma unroll
        for (int i = 0; i < 4; i++) e[i] = kv[4 * u + i];
        stll(g_KVP + (c * 16 + t) * 1024 + wg * 512 + u * 128 + (warp & 3) * 32 + ln2, tg(__float_as_uint(e[0]), tag), __float_as_uint(e[1]), __float_as_uint(e[2]), __float_as_uint(e[3]));
      }
      MARK(5 + L * 19);
      uint4 k4[4];
      const uint4* pk = g_KVP + (c * 16 + 4 * (ln2 & 3)) * 1024 + 64 * t + warp * 8 + (ln2 >> 2);
#pragma unroll
      for (int i = 0; i < 2; i++) {
        const uint32_t st = ACQ(4 + i); wg_fence();
#pragma unroll
        for (int ks = 0; ks < 14; ks++) { const uint4 f = a[14 * i + ks]; wgmma_rs56(aq, f.x, f.y, f.z, f.w, mkdesc(st, ks * 2048, 1024, 1024, 1), i | ks); }
        if (i == 1) wgmma_rs56(aq, fa, fb, 0u, 0u, mkdesc(d16, OFF_CB, 512, 0, 2), 1);
        wg_commit();
        if (i == 1) ll_issue<0, 4>(k4, pk, 1024);
      }
      ll_check<0, 4, false>(k4, pk, 1024, tag);
      float s0 = 0, s1 = 0, s2 = 0, s3 = 0;
#pragma unroll
      for (int i = 0; i < 4; i++) { s0 += __uint_as_float(k4[i].x); s1 += __uint_as_float(k4[i].y); s2 += __uint_as_float(k4[i].z); s3 += __uint_as_float(k4[i].w); }
      s0 = qsum(s0); s1 = qsum(s1); s2 = qsum(s2); s3 = qsum(s3);
      if (q == 0) stll2(g_KVR + c * 1024 + 64 * t + warp * 8 + (ln2 >> 2), tg(pack(s0, s1), tag), pack(s2, s3));
      MARK(6 + L * 19);
      wg_wait<0>(); REL(4) REL(5) regfence(aq);
      phi_gemm(aq, pp, d16 + (OFF_WPHI >> 4), r0, r1);
      bar_cons();
#pragma unroll
      for (int i = 0; i < 4; i++) sts128(sV + warp * 2048 + (lane + i * 32) * 16, 0, 0, 0, 0);
      wg_wait<0>(); regfence(pp);
      uint2 r[4];
      const uint2* pr = g_KVR + c * 1024 + wg * 512 + (warp & 3) * 32 + ln2;
      hedgehog(pp, [&](int r, int h, int p, uint32_t v) { phq[r][h][p] = v; }, [&] {
#pragma unroll
        for (int u = 0; u < 4; u++) r[u] = ldll2(pr + u * 128); });
      MARK(7 + L * 19);
#pragma unroll 1
      for (int it = 0; it < SPIN; it++) {
        if (!__any_sync(~0u, ((r[0].x ^ tag) | (r[1].x ^ tag) | (r[2].x ^ tag) | (r[3].x ^ tag)) & 1)) break;
#pragma unroll
        for (int u = 0; u < 4; u++) r[u] = ldll2(pr + u * 128);
      }
#pragma unroll
      for (int u = 0; u < 4; u++) {
        const int d = 8 * u + 2 * q;
        if (d < 28) { sts32(sV + sw128(row0, 28 * wg + d), r[u].x); sts32(sV + sw128(row0 + 8, 28 * wg + d), r[u].y); }
        else if (d == 28) {
#pragma unroll
          for (int j = 0; j < 4; j++) { sts16(sV + sw128(row0, 56 + 2 * j + wg), r[u].x); sts16(sV + sw128(row0 + 8, 56 + 2 * j + wg), r[u].y); }
        }
      }
      fence_async();
      bar_cons();
      MARK(8 + L * 19);
      float o[32];
      wg_fence();
#pragma unroll
      for (int ks = 0; ks < 8; ks++) {
        const int h = ks >> 2, p = 2 * (ks & 3);
        wgmma_rs64(o, phq[0][h][p], phq[1][h][p], p < 6 ? phq[0][h][p < 6 ? p + 1 : 0] : 0u, p < 6 ? phq[1][h][p < 6 ? p + 1 : 0] : 0u, mkdesc(d16, OFF_V + ks * 2048, 1024, 1024, 1), ks);
      }
      wg_commit(); wg_wait<0>(); regfence(o);
      const float iA0 = rcp(o[28] + 1e-6f), iB0 = rcp(o[29] + 1e-6f), iA1 = rcp(o[30] + 1e-6f), iB1 = rcp(o[31] + 1e-6f);
      uint32_t w[14];
      { PTRS
#pragma unroll
      for (int j = 0; j < 7; j++) {
        const bool hb = 8 * j + 2 * q >= 28; const float i0 = hb ? iB0 : iA0, i1 = hb ? iB1 : iA1;
        w[2 * j] = pack(o[4 * j] * i0, o[4 * j + 1] * i0); w[2 * j + 1] = pack(o[4 * j + 2] * i1, o[4 * j + 3] * i1);
        if (j == 0 || ((j ^ c) & 1) == 0) w[2 * j] = tg(w[2 * j], tag);
      }
      slice_store(sf + OO, sh + 2 * OO, w, c & 1);
      hint_post(hme, hs + 2, lane); }
    }
    MARK(9 + L * 19);
    uint4 xr[4];
    if (c < 7) {
      PTRS
      ll_issue<0, 4>(xr, fm + XR + 128 * c, 32);
      uint4 a[28];
      const uint4* pa = fm + OO;
      hint_wait(hrow, hs + 2);
      MARK(10 + L * 19);
      ll_issue<0, 28, true>(a, pa, 32, f2 + 2 * OO);
      float y[32];
      uint32_t st;
#define WOSTEP(i) { ll_check<7 * i, 7, true>(a, pa, 32, tag, f2 + 2 * OO); if (!(i & 1)) st = ACQ(6 + i / 2); wg_fence(); \
      _Pragma("unroll") for (int ks = 0; ks < 7; ks++) { const uint4 f = a[7 * i + ks]; \
        wgmma_rs64(y, f.x, f.y, f.z, f.w, mkdesc(st, ((i & 1) * 7 + ks) * 2048, 1024, 1024, 1), i | ks); } wg_commit(); }
      WOSTEP(0) WOSTEP(1) WOSTEP(2) WOSTEP(3)
      ll_check<0, 4, false>(xr, fm + XR + 128 * c, 32, tag);
      wg_wait<0>(); regfence(y);
      MARK(11 + L * 19);
#pragma unroll
      for (int u = 0; u < 4; u++) {
        xr[u].x = tg(pack(blo(xr[u].x) + y[8 * u], bhi(xr[u].x) + y[8 * u + 1]), tag); xr[u].y = pack(blo(xr[u].y) + y[8 * u + 2], bhi(xr[u].y) + y[8 * u + 3]);
        xr[u].z = pack(blo(xr[u].z) + y[8 * u + 4], bhi(xr[u].z) + y[8 * u + 5]); xr[u].w = pack(blo(xr[u].w) + y[8 * u + 6], bhi(xr[u].w) + y[8 * u + 7]);
        stll(fm + X1 + 128 * c + u * 32, xr[u].x, xr[u].y, xr[u].z, xr[u].w);
      }
      hint_post(hme, hs + 3, lane);
    } else {
      PTRS
      hint_post(hme, hs + 3, lane);
      (void)ACQ(6); (void)ACQ(7);
      hint_wait(hrow, hs + 3);
      ll_issue<0, 4>(xr, fm + X1, 32);
      MARK(10 + L * 19); MARK(11 + L * 19);
    }
    uint32_t hf[56];
    float rr0, rr1;
    {
      PTRS
      uint4 a[28];
      const uint4* pa = fm + X1;
      auto grp = [&](int i) -> const uint4* { const int k = i + c; return pa + ((k >= 7 ? k - 7 : k) - i) * 128; };
      if (c == 7) { ll_issue<4, 12>(a, pa, 32); ll_check<0, 4, false>(xr, pa, 32, tag); }
      else {
#pragma unroll
        for (int u = 4; u < 16; u++) a[u] = make_uint4(0, 0, 0, 0);
      }
#pragma unroll
      for (int u = 0; u < 4; u++) a[u] = xr[u];
      float y[96], z[16];
#define F1STAGE(i) { if (i > 0) ll_check<4 * i, 4, false>(a, grp(i), 32, tag); const uint32_t st = ACQ(8 + i); wg_fence(); \
      _Pragma("unroll") for (int ks = 0; ks < 4; ks++) { const uint4 f = a[4 * i + ks]; \
        wgmma_rs192(y, f.x, f.y, f.z, f.w, mkdesc(st, (ks >> 1) * 12288 + (ks & 1) * 2048, 4096, 1024, 1), i | ks); \
        wgmma_rs32(z, f.x, f.y, f.z, f.w, mkdesc(st, 24576 + ks * 1024, 512, 512, 2), i | ks); } \
      wg_commit(); if (i > 0) { wg_wait<1>(); REL(6 + i) if (i < 4) ll_issue<(i < 4 ? 4 * i + 12 : 0), 4>(a, grp(i + 3), 32); } }
      F1STAGE(0)
      MARK(12 + L * 19);
      if (c < 7) {
        hint_wait(hrow, hs + 3);
        ll_issue<4, 4>(a, grp(1), 32); ll_issue<8, 4>(a, grp(2), 32); ll_issue<12, 4>(a, grp(3), 32);
        float s0 = 0.f, s1 = 0.f, v0 = 0.f, v1 = 0.f;
#pragma unroll
        for (int u = 0; u < 4; u++) { s0 += (blo(xr[u].x) + bhi(xr[u].x)) + (blo(xr[u].z) + bhi(xr[u].z)); s1 += (blo(xr[u].y) + bhi(xr[u].y)) + (blo(xr[u].w) + bhi(xr[u].w)); }
        s0 = qsum(s0) * (1.f / 64); s1 = qsum(s1) * (1.f / 64);
#pragma unroll
        for (int u = 0; u < 4; u++) {
          const float d0 = blo(xr[u].x) - s0, d1 = bhi(xr[u].x) - s0, d2 = blo(xr[u].z) - s0, d3 = bhi(xr[u].z) - s0;
          const float d4 = blo(xr[u].y) - s1, d5 = bhi(xr[u].y) - s1, d6 = blo(xr[u].w) - s1, d7 = bhi(xr[u].w) - s1;
          v0 += (d0 * d0 + d1 * d1) + (d2 * d2 + d3 * d3); v1 += (d4 * d4 + d5 * d5) + (d6 * d6 + d7 * d7);
        }
        v0 = qsum(v0); v1 = qsum(v1);
        if (q == 0) stll(g_ST + ((t * 8 + warp) * 8 + c) * 8 + (ln_ >> 2), tg(__float_as_uint(s0), tag), __float_as_uint(v0), __float_as_uint(s1), __float_as_uint(v1));
      }
      REL(6)
      F1STAGE(1) MARK(13 + L * 19); F1STAGE(2) F1STAGE(3)
      uint4 sv[2];
      const uint4* ps = g_ST + ((t * 8 + warp) * 8 + 2 * (laneid() & 3)) * 8 + (laneid() >> 2);
      ll_issue<0, 2>(sv, ps, q < 3 ? 8 : 0);
      F1STAGE(4)
      ll_check<0, 2, false>(sv, ps, q < 3 ? 8 : 0, tag);
      const float wb = q < 3 ? 1.f : 0.f;
      const float ma = __uint_as_float(sv[0].x), mb = __uint_as_float(sv[1].x), mc = __uint_as_float(sv[0].z), md = __uint_as_float(sv[1].z);
      const float m0 = qsum(ma + wb * mb) * (1.f / 7), m1 = qsum(mc + wb * md) * (1.f / 7);
      const float v0 = qsum(__uint_as_float(sv[0].y) + 64.f * (ma - m0) * (ma - m0) + wb * (__uint_as_float(sv[1].y) + 64.f * (mb - m0) * (mb - m0)));
      const float v1 = qsum(__uint_as_float(sv[0].w) + 64.f * (mc - m1) * (mc - m1) + wb * (__uint_as_float(sv[1].w) + 64.f * (md - m1) * (md - m1)));
      const float e0 = v0 * (1.f / 448) + 1e-5f, e1 = v1 * (1.f / 448) + 1e-5f;
      rr0 = 1.f / e0; rr1 = 1.f / e1;
      auto fold = [&](float m, float sd) -> uint32_t {
        const float mh = blo(pack(-m, 0.f)), sh_ = blo(pack(sd, 0.f));
        return q == 0 ? pack(mh, -m - mh) : q == 1 ? pack(mh, sh_) : q == 2 ? pack(sd - sh_, 0.f) : 0u;
      };
      const uint32_t fa = fold(m0, sqrtf(e0)), fb = fold(m1, sqrtf(e1));
      if (L == 0) asm volatile("bar.sync 4, 288;" ::: "memory");
      wg_fence();
      wgmma_rs192(y, fa, fb, 0u, 0u, mkdesc(d16, OFF_CB, 512, 0, 2), 1);
      wgmma_rs32(z, fa, fb, 0u, 0u, mkdesc(d16, OFF_CB + 3072, 512, 0, 2), 1);
      F1STAGE(5) F1STAGE(6)
      wg_wait<0>(); REL(13) REL(14) regfence(y); regfence(z);
      MARK(14 + L * 19);
#pragma unroll
      for (int j = 0; j < 56; j++) {
        uint32_t r; asm("cvt.rn.relu.bf16x2.f32 %0, %1, %2;" : "=r"(r) : "f"(j < 48 ? y[j < 48 ? 2 * j + 1 : 0] : z[j < 48 ? 0 : 2 * j - 95]), "f"(j < 48 ? y[j < 48 ? 2 * j : 0] : z[j < 48 ? 0 : 2 * j - 96]));
        asm("mul.bf16x2 %0, %1, %1;" : "=r"(hf[j]) : "r"(r));
      }
    }
    MARK(15 + L * 19);
    {
      PTRS
      float ya[32], yb[32];
      uint4* pp = g_P + ((t * 8 + warp) * 8 + c) * 28 * 32 + ln_;
#define F2STORE(j, Y) { regfence(Y); _Pragma("unroll") for (int u = 0; u < 4; u++) \
      stll(pp + (4 * (j) + u) * 32, tg(pack(Y[8 * u] * rr0, Y[8 * u + 1] * rr0), tag), pack(Y[8 * u + 2] * rr1, Y[8 * u + 3] * rr1), \
           pack(Y[8 * u + 4] * rr0, Y[8 * u + 5] * rr0), pack(Y[8 * u + 6] * rr1, Y[8 * u + 7] * rr1)); if ((j) >= 5) hint_post(hme, hs + (4 + (j)), lane); }
#define F2PASS(j, Y, Z) { const uint32_t st = ACQ(15 + j); wg_fence(); \
      _Pragma("unroll") for (int ks = 0; ks < 14; ks++) wgmma_rs64(Y, hf[4 * ks], hf[4 * ks + 1], hf[4 * ks + 2], hf[4 * ks + 3], mkdesc(st, ks * 2048, 1024, 1024, 1), ks); \
      wg_commit(); if (j > 0) { wg_wait<1>(); REL(14 + j) F2STORE(j - 1, Z) } }
      const uint4* pr = g_P + ((t * 8 + c) * 8 * 28 + warp) * 32 + ln_;
      uint4 p[8], p2[8]; uint2 xa, xb, xc, xd; uint32_t ba, bb, bc, bd;
      const uint32_t ptag = tag;
      const uint32_t* hred = g_H + (t * 8 + c) * 8 + (ln_ & 7);
      F2PASS(0, ya, yb) F2PASS(1, yb, ya) F2PASS(2, ya, yb) F2PASS(3, yb, ya)
      F2PASS(4, ya, yb)
      RISSUE(0, p, xa, xb, ba, bb)
      F2PASS(5, yb, ya)
      REDU(0, p, xa, xb, ba, bb)
      if (L == 0) { xw[0][0] = tg(xw[0][0], 0); RPUB(0) }
      F2PASS(6, ya, yb)
      RISSUE(1, p, xa, xb, ba, bb)
      wg_wait<0>(); REL(21) F2STORE(6, ya)
      MARK(16 + L * 19);
      if (wg) hint_wait(hred, hs + 9);
      RISSUE(2, p2, xc, xd, bc, bd)
      REDU(1, p, xa, xb, ba, bb)
      if (L == 0) { xw[1][0] = tg(xw[1][0], 0); RPUB(1) }
      MARK(17 + L * 19);
      REDU(2, p2, xc, xd, bc, bd)
      if (L == 0) { xw[2][0] = tg(xw[2][0], 0); RPUB(2) }
    }
    MARK(18 + L * 19);
  }
  {
    PTRS
    uint32_t* op = (uint32_t*)(out + XOFF(ln_));
#define OUT(u) { op[u * 64] = xw[u][0]; op[u * 64 + 1792] = xw[u][1]; op[u * 64 + 4] = xw[u][2]; op[u * 64 + 1796] = xw[u][3]; }
    OUT(0) OUT(1) OUT(2)
    if (wg == 0) { RLAST(0u, 20u) OUT(3) }
    else if (warp == 7) {
      if (t == 0 && lane == 0) g_WQF[c] = 0;
      if (lane < 8) stll(g_S2 + (t * 8 + c) * 8 + lane, 0, 0, 0, 0);
      if (lane < 4) { stll(g_CS + blockIdx.x * 4 + lane, 0, 0, 0, 0); if (blockIdx.x < 68) stll(g_CS + 512 + blockIdx.x * 4 + lane, 0, 0, 0, 0); }
    }
  }
  MARK(38); GT(39);
  }
}

typedef CUresult (*EncFn)(CUtensorMap*, CUtensorMapDataType, cuuint32_t, void*, const cuuint64_t*, const cuuint64_t*, const cuuint32_t*, const cuuint32_t*,
                          CUtensorMapInterleave, CUtensorMapSwizzle, CUtensorMapL2promotion, CUtensorMapFloatOOBfill);

extern "C" void kernel_launch(void* const* d_in, const int* in_sizes, int n_in, void* d_out, int out_size) {
  static EncFn enc = nullptr;
  if (!enc) {
    void* fn = nullptr; cudaDriverEntryPointQueryResult qr;
    cudaGetDriverEntryPoint("cuTensorMapEncodeTiled", &fn, cudaEnableDefault, &qr);
    enc = (EncFn)fn;
    cudaFuncSetAttribute(fused_kernel, cudaFuncAttributeMaxDynamicSharedMemorySize, SMEM_BYTES);
  }
  CUtensorMap mQKV, mWO, mW1, mW1b, mW2, mW2b, mX;
  const cuuint32_t es[3] = {1, 1, 1};
  auto enc2 = [&](CUtensorMap* m, void* p, cuuint64_t cols, cuuint64_t rows, cuuint32_t bc, cuuint32_t br) {
    const cuuint64_t dims[2] = {cols, rows}, str[1] = {cols * 2}; const cuuint32_t box[2] = {bc, br};
    enc(m, CU_TENSOR_MAP_DATA_TYPE_BFLOAT16, 2, p, dims, str, box, es, CU_TENSOR_MAP_INTERLEAVE_NONE,
        bc == 64 ? CU_TENSOR_MAP_SWIZZLE_128B : CU_TENSOR_MAP_SWIZZLE_64B, CU_TENSOR_MAP_L2_PROMOTION_L2_128B, CU_TENSOR_MAP_FLOAT_OOB_FILL_NONE);
  };
  enc2(&mQKV, d_in[1], 1344, 448, 64, 112); enc2(&mWO, d_in[3], 448, 448, 64, 112); enc2(&mW1b, d_in[5], 1792, 448, 32, 32);
  enc2(&mX, d_in[0], 448, 2048, 64, 128);
  enc2(&mW2, d_in[7], 448, 1792, 64, 96); enc2(&mW2b, d_in[7], 448, 1792, 64, 16);
  {
    const cuuint64_t dims[3] = {64, 448, 28}, str[2] = {3584, 128}; const cuuint32_t box[3] = {64, 32, 3};
    enc(&mW1, CU_TENSOR_MAP_DATA_TYPE_BFLOAT16, 3, d_in[5], dims, str, box, es, CU_TENSOR_MAP_INTERLEAVE_NONE, CU_TENSOR_MAP_SWIZZLE_128B,
        CU_TENSOR_MAP_L2_PROMOTION_L2_128B, CU_TENSOR_MAP_FLOAT_OOB_FILL_NONE);
  }
  typedef const __nv_bfloat16* BP;
  fused_kernel<<<128, 384, SMEM_BYTES>>>(mQKV, mWO, mW1, mW1b, mW2, mW2b, mX, (BP)d_in[1], (BP)d_in[2], (BP)d_in[3], (BP)d_in[5], (BP)d_in[6], (BP)d_in[7], (BP)d_in[8],
                                         (__nv_bfloat16*)d_out);
}
```

```cpp
#include <cuda_runtime.h>
#include <cuda_bf16.h>
#include <cuda.h>
#include <stdint.h>

constexpr int NST = 6, STAGE = 28672;
constexpr int OFF_PHIK = NST * STAGE;
constexpr int OFF_V = OFF_PHIK + 32768;
constexpr int OFF_WPHI = OFF_V + 16384;
constexpr int OFF_CB = OFF_WPHI + 7168;
constexpr int OFF_BAR = OFF_CB + 3584;
constexpr int SMEM_BYTES = OFF_BAR + 16 * NST + 8;
constexpr int FR = 16 * 8 * 28 * 32;
constexpr int SPIN = 1 << 18;

__device__ uint4 g_F[3 * FR];
constexpr int XR = 0, OO = FR, X1 = 2 * FR;
__device__ uint4 g_P[8 * FR];
__device__ uint4 g_ST[16 * 8 * 8 * 8];
__device__ uint4 g_KVP[8 * 16 * 1024];
__device__ uint2 g_KVR[8 * 1024];
__device__ uint4 g_CS[784];
__device__ uint4 g_S2[16 * 8 * 8];
__device__ uint4 g_WQ[8 * 6 * (STAGE / 16)];
__device__ uint32_t g_WQF[8];
__device__ uint32_t g_H[16 * 8 * 8];
#define MARK(i)
#define GT(i)

__device__ __forceinline__ uint32_t s2u(const void* p) { return (uint32_t)__cvta_generic_to_shared(p); }
__device__ __forceinline__ void mbar_init(uint32_t b, uint32_t c) { asm volatile("mbarrier.init.shared::cta.b64 [%0], %1;" ::"r"(b), "r"(c)); }
__device__ __forceinline__ void mbar_expect(uint32_t b, uint32_t tx) { asm volatile("mbarrier.arrive.expect_tx.shared::cta.b64 _, [%0], %1;" ::"r"(b), "r"(tx) : "memory"); }
__device__ __forceinline__ void mbar_arrive(uint32_t b) { asm volatile("mbarrier.arrive.shared::cta.b64 _, [%0];" ::"r"(b) : "memory"); }
__device__ __forceinline__ void mbar_wait(uint32_t b, uint32_t ph) {
  uint32_t ok = 0;
#pragma unroll 1
  for (int it = 0; it < SPIN && !ok; it++)
    asm volatile("{.reg .pred p; mbarrier.try_wait.parity.shared::cta.b64 p,[%1],%2; selp.u32 %0,1,0,p;}" : "=r"(ok) : "r"(b), "r"(ph) : "memory");
}
__device__ __forceinline__ void tma2d(uint32_t dst, const CUtensorMap* m, int c0, int c1, uint32_t bar) {
  asm volatile("cp.async.bulk.tensor.2d.shared::cluster.global.mbarrier::complete_tx::bytes [%0], [%1, {%3, %4}], [%2];"
               ::"r"(dst), "l"(m), "r"(bar), "r"(c0), "r"(c1) : "memory");
}
__device__ __forceinline__ void tma3d(uint32_t dst, const CUtensorMap* m, int c0, int c1, int c2, uint32_t bar) {
  asm volatile("cp.async.bulk.tensor.3d.shared::cluster.global.mbarrier::complete_tx::bytes [%0], [%1, {%3, %4, %5}], [%2];"
               ::"r"(dst), "l"(m), "r"(bar), "r"(c0), "r"(c1), "r"(c2) : "memory");
}
__device__ __forceinline__ void l2pf(const void* p, uint32_t bytes) { asm volatile("cp.async.bulk.prefetch.L2.global [%0], %1;" ::"l"(p), "r"(bytes) : "memory"); }
__device__ __forceinline__ void wg_fence() { asm volatile("wgmma.fence.sync.aligned;" ::: "memory"); }
__device__ __forceinline__ void wg_commit() { asm volatile("wgmma.commit_group.sync.aligned;" ::: "memory"); }
template <int N> __device__ __forceinline__ void wg_wait() { asm volatile("wgmma.wait_group.sync.aligned %0;" ::"n"(N) : "memory"); }
template <int N> __device__ __forceinline__ void regfence(float (&d)[N]) {
#pragma unroll
  for (int i = 0; i < N; i++) asm volatile("" : "+f"(d[i])::"memory");
}
__device__ __forceinline__ void bar_cons() { asm volatile("bar.sync 1, 256;" ::: "memory"); }
__device__ __forceinline__ void fence_async() { asm volatile("fence.proxy.async.shared::cta;" ::: "memory"); }
struct Desc { uint32_t lo, hi; };
__device__ __forceinline__ Desc mkdesc(uint32_t base16, uint32_t off, uint32_t lbo, uint32_t sbo, uint32_t swz) {
  return Desc{base16 + ((off >> 4) | ((lbo >> 4) << 16)), (sbo >> 4) | (swz << 30)};
}
__device__ __forceinline__ uint4 ldll(const uint4* p) {
  uint4 v; asm volatile("ld.relaxed.gpu.global.v4.u32 {%0,%1,%2,%3}, [%4];" : "=r"(v.x), "=r"(v.y), "=r"(v.z), "=r"(v.w) : "l"(p) : "memory"); return v;
}
__device__ __forceinline__ uint2 ldll2(const uint2* p) {
  uint2 v; asm volatile("ld.relaxed.gpu.global.v2.u32 {%0,%1}, [%2];" : "=r"(v.x), "=r"(v.y) : "l"(p) : "memory"); return v;
}
__device__ __forceinline__ void stll(uint4* p, uint32_t x, uint32_t y, uint32_t z, uint32_t w) {
  asm volatile("st.relaxed.gpu.global.v4.u32 [%0], {%1,%2,%3,%4};" ::"l"(p), "r"(x), "r"(y), "r"(z), "r"(w) : "memory");
}
__device__ __forceinline__ void stll2(void* p, uint32_t x, uint32_t y) {
  asm volatile("st.relaxed.gpu.global.v2.u32 [%0], {%1,%2};" ::"l"(p), "r"(x), "r"(y) : "memory");
}
__device__ __forceinline__ int laneid() { int l; asm volatile("mov.u32 %0, %%laneid;" : "=r"(l)); return l; }
__device__ __forceinline__ uint32_t tg(uint32_t w, uint32_t tag) { return (w & ~1u) | tag; }
__device__ __forceinline__ uint32_t pack(float lo, float hi) {
  uint32_t r; asm("cvt.rn.bf16x2.f32 %0, %1, %2;" : "=r"(r) : "f"(hi), "f"(lo)); return r;
}
__device__ __forceinline__ float blo(uint32_t w) { return __uint_as_float(w << 16); }
__device__ __forceinline__ float bhi(uint32_t w) { return __uint_as_float(w & 0xffff0000u); }
__device__ __forceinline__ float ex2(float x) { float r; asm("ex2.approx.ftz.f32 %0, %1;" : "=f"(r) : "f"(x)); return r; }
__device__ __forceinline__ float rcp(float x) { float r; asm("rcp.approx.ftz.f32 %0, %1;" : "=f"(r) : "f"(x)); return r; }
__device__ __forceinline__ float qsum(float v) { v += __shfl_xor_sync(~0u, v, 1); v += __shfl_xor_sync(~0u, v, 2); return v; }
__device__ __forceinline__ void sts32(uint32_t a, uint32_t v) { asm volatile("st.shared.u32 [%0], %1;" ::"r"(a), "r"(v) : "memory"); }
__device__ __forceinline__ void sts16(uint32_t a, uint32_t v) { asm volatile("st.shared.u16 [%0], %1;" ::"r"(a), "h"((uint16_t)v) : "memory"); }
__device__ __forceinline__ void sts128(uint32_t a, uint32_t x, uint32_t y, uint32_t z, uint32_t w) {
  asm volatile("st.shared.v4.u32 [%0], {%1,%2,%3,%4};" ::"r"(a), "r"(x), "r"(y), "r"(z), "r"(w) : "memory");
}
__device__ __forceinline__ uint32_t sw128(int row, int col) { return row * 128 + ((((col >> 3) ^ row) & 7) << 4) + (col & 7) * 2; }

__device__ __forceinline__ void wgmma_rs56(float (&d)[28], const uint32_t a0, const uint32_t a1, const uint32_t a2, const uint32_t a3, Desc db, int sd) {
  asm volatile("{.reg .pred p; .reg .b64 da, db; setp.ne.b32 p, %33, 0; mov.b64 db, {%32, %34};\n wgmma.mma_async.sync.aligned.m64n56k16.f32.bf16.bf16 {%0,%1,%2,%3,%4,%5,%6,%7,%8,%9,%10,%11,%12,%13,%14,%15,%16,%17,%18,%19,%20,%21,%22,%23,%24,%25,%26,%27}, {%28,%29,%30,%31}, db, p, 1, 1, 1;}"
   : "+f"(d[0]),"+f"(d[1]),"+f"(d[2]),"+f"(d[3]),"+f"(d[4]),"+f"(d[5]),"+f"(d[6]),"+f"(d[7]),"+f"(d[8]),"+f"(d[9]),"+f"(d[10]),"+f"(d[11]),"+f"(d[12]),"+f"(d[13]),"+f"(d[14]),"+f"(d[15]),"+f"(d[16]),"+f"(d[17]),"+f"(d[18]),"+f"(d[19]),"+f"(d[20]),"+f"(d[21]),"+f"(d[22]),"+f"(d[23]),"+f"(d[24]),"+f"(d[25]),"+f"(d[26]),"+f"(d[27])
   : "r"(a0),"r"(a1),"r"(a2),"r"(a3),"r"(db.lo),"r"(sd),"r"(db.hi));
}
__device__ __forceinline__ void wgmma_rs64(float (&d)[32], const uint32_t a0, const uint32_t a1, const uint32_t a2, const uint32_t a3, Desc db, int sd) {
  asm volatile("{.reg .pred p; .reg .b64 da, db; setp.ne.b32 p, %37, 0; mov.b64 db, {%36, %38};\n wgmma.mma_async.sync.aligned.m64n64k16.f32.bf16.bf16 {%0,%1,%2,%3,%4,%5,%6,%7,%8,%9,%10,%11,%12,%13,%14,%15,%16,%17,%18,%19,%20,%21,%22,%23,%24,%25,%26,%27,%28,%29,%30,%31}, {%32,%33,%34,%35}, db, p, 1, 1, 1;}"
   : "+f"(d[0]),"+f"(d[1]),"+f"(d[2]),"+f"(d[3]),"+f"(d[4]),"+f"(d[5]),"+f"(d[6]),"+f"(d[7]),"+f"(d[8]),"+f"(d[9]),"+f"(d[10]),"+f"(d[11]),"+f"(d[12]),"+f"(d[13]),"+f"(d[14]),"+f"(d[15]),"+f"(d[16]),"+f"(d[17]),"+f"(d[18]),"+f"(d[19]),"+f"(d[20]),"+f"(d[21]),"+f"(d[22]),"+f"(d[23]),"+f"(d[24]),"+f"(d[25]),"+f"(d[26]),"+f"(d[27]),"+f"(d[28]),"+f"(d[29]),"+f"(d[30]),"+f"(d[31])
   : "r"(a0),"r"(a1),"r"(a2),"r"(a3),"r"(db.lo),"r"(sd),"r"(db.hi));
}
__device__ __forceinline__ void wgmma_rs192(float (&d)[96], const uint32_t a0, const uint32_t a1, const uint32_t a2, const uint32_t a3, Desc db, int sd) {
  asm volatile("{.reg .pred p; .reg .b64 db; setp.ne.b32 p, %101, 0; mov.b64 db, {%100, %102};\n wgmma.mma_async.sync.aligned.m64n192k16.f32.bf16.bf16 {%0,%1,%2,%3,%4,%5,%6,%7,%8,%9,%10,%11,%12,%13,%14,%15,%16,%17,%18,%19,%20,%21,%22,%23,%24,%25,%26,%27,%28,%29,%30,%31,%32,%33,%34,%35,%36,%37,%38,%39,%40,%41,%42,%43,%44,%45,%46,%47,%48,%49,%50,%51,%52,%53,%54,%55,%56,%57,%58,%59,%60,%61,%62,%63,%64,%65,%66,%67,%68,%69,%70,%71,%72,%73,%74,%75,%76,%77,%78,%79,%80,%81,%82,%83,%84,%85,%86,%87,%88,%89,%90,%91,%92,%93,%94,%95}, {%96,%97,%98,%99}, db, p, 1, 1, 1;}"
   : "+f"(d[0]),"+f"(d[1]),"+f"(d[2]),"+f"(d[3]),"+f"(d[4]),"+f"(d[5]),"+f"(d[6]),"+f"(d[7]),"+f"(d[8]),"+f"(d[9]),"+f"(d[10]),"+f"(d[11]),"+f"(d[12]),"+f"(d[13]),"+f"(d[14]),"+f"(d[15]),"+f"(d[16]),"+f"(d[17]),"+f"(d[18]),"+f"(d[19]),"+f"(d[20]),"+f"(d[21]),"+f"(d[22]),"+f"(d[23]),"+f"(d[24]),"+f"(d[25]),"+f"(d[26]),"+f"(d[27]),"+f"(d[28]),"+f"(d[29]),"+f"(d[30]),"+f"(d[31]),"+f"(d[32]),"+f"(d[33]),"+f"(d[34]),"+f"(d[35]),"+f"(d[36]),"+f"(d[37]),"+f"(d[38]),"+f"(d[39]),"+f"(d[40]),"+f"(d[41]),"+f"(d[42]),"+f"(d[43]),"+f"(d[44]),"+f"(d[45]),"+f"(d[46]),"+f"(d[47]),"+f"(d[48]),"+f"(d[49]),"+f"(d[50]),"+f"(d[51]),"+f"(d[52]),"+f"(d[53]),"+f"(d[54]),"+f"(d[55]),"+f"(d[56]),"+f"(d[57]),"+f"(d[58]),"+f"(d[59]),"+f"(d[60]),"+f"(d[61]),"+f"(d[62]),"+f"(d[63]),"+f"(d[64]),"+f"(d[65]),"+f"(d[66]),"+f"(d[67]),"+f"(d[68]),"+f"(d[69]),"+f"(d[70]),"+f"(d[71]),"+f"(d[72]),"+f"(d[73]),"+f"(d[74]),"+f"(d[75]),"+f"(d[76]),"+f"(d[77]),"+f"(d[78]),"+f"(d[79]),"+f"(d[80]),"+f"(d[81]),"+f"(d[82]),"+f"(d[83]),"+f"(d[84]),"+f"(d[85]),"+f"(d[86]),"+f"(d[87]),"+f"(d[88]),"+f"(d[89]),"+f"(d[90]),"+f"(d[91]),"+f"(d[92]),"+f"(d[93]),"+f"(d[94]),"+f"(d[95])
   : "r"(a0),"r"(a1),"r"(a2),"r"(a3),"r"(db.lo),"r"(sd),"r"(db.hi));
}
__device__ __forceinline__ void wgmma_rs32(float (&d)[16], const uint32_t a0, const uint32_t a1, const uint32_t a2, const uint32_t a3, Desc db, int sd) {
  asm volatile("{.reg .pred p; .reg .b64 db; setp.ne.b32 p, %21, 0; mov.b64 db, {%20, %22};\n wgmma.mma_async.sync.aligned.m64n32k16.f32.bf16.bf16 {%0,%1,%2,%3,%4,%5,%6,%7,%8,%9,%10,%11,%12,%13,%14,%15}, {%16,%17,%18,%19}, db, p, 1, 1, 1;}"
   : "+f"(d[0]),"+f"(d[1]),"+f"(d[2]),"+f"(d[3]),"+f"(d[4]),"+f"(d[5]),"+f"(d[6]),"+f"(d[7]),"+f"(d[8]),"+f"(d[9]),"+f"(d[10]),"+f"(d[11]),"+f"(d[12]),"+f"(d[13]),"+f"(d[14]),"+f"(d[15])
   : "r"(a0),"r"(a1),"r"(a2),"r"(a3),"r"(db.lo),"r"(sd),"r"(db.hi));
}
__device__ __forceinline__ void wgmma_ss32(float (&d)[16], Desc da, Desc db, int sd) {
  asm volatile("{.reg .pred p; .reg .b64 da, db; setp.ne.b32 p, %18, 0; mov.b64 da, {%16, %19}; mov.b64 db, {%17, %19};\n wgmma.mma_async.sync.aligned.m64n32k16.f32.bf16.bf16 {%0,%1,%2,%3,%4,%5,%6,%7,%8,%9,%10,%11,%12,%13,%14,%15}, da, db, p, 1, 1, 1, 1;}"
   : "+f"(d[0]),"+f"(d[1]),"+f"(d[2]),"+f"(d[3]),"+f"(d[4]),"+f"(d[5]),"+f"(d[6]),"+f"(d[7]),"+f"(d[8]),"+f"(d[9]),"+f"(d[10]),"+f"(d[11]),"+f"(d[12]),"+f"(d[13]),"+f"(d[14]),"+f"(d[15])
   : "r"(da.lo),"r"(db.lo),"r"(sd),"r"(db.hi));
}

__device__ __forceinline__ uint4 ldsm4(uint32_t a) {
  uint4 v; asm volatile("ldmatrix.sync.aligned.m8n8.x4.shared.b16 {%0,%1,%2,%3}, [%4];" : "=r"(v.x), "=r"(v.y), "=r"(v.z), "=r"(v.w) : "r"(a) : "memory"); return v;
}
__device__ __forceinline__ void mma16816(float (&d)[4], const uint4& a, uint32_t b0, uint32_t b1) {
  asm("mma.sync.aligned.m16n8k16.row.col.f32.bf16.bf16.f32 {%0,%1,%2,%3}, {%4,%5,%6,%7}, {%8,%9}, {%0,%1,%2,%3};"
      : "+f"(d[0]), "+f"(d[1]), "+f"(d[2]), "+f"(d[3]) : "r"(a.x), "r"(a.y), "r"(a.z), "r"(a.w), "r"(b0), "r"(b1));
}
__device__ __forceinline__ uint32_t bsub(uint32_t a, uint32_t b) { uint32_t r; asm("sub.bf16x2 %0, %1, %2;" : "=r"(r) : "r"(a), "r"(b)); return r; }
__device__ __forceinline__ uint32_t hint_ld(const uint32_t* p) { uint32_t v; asm volatile("ld.relaxed.gpu.global.u32 %0, [%1];" : "=r"(v) : "l"(p) : "memory"); return v; }
template <int S, int N, bool SPL = false, int T> __device__ __forceinline__ void ll_issue(uint4 (&v)[T], const uint4* p, int stride, const uint2* p2 = nullptr) {
#pragma unroll
  for (int i = S; i < S + N; i++) {
    if (SPL && i % 7 == 3) { const uint2 lo = ldll2(p2 + i * 64), hi = ldll2(p2 + i * 64 + 32); v[i] = make_uint4(lo.x, lo.y, hi.x, hi.y); }
    else v[i] = ldll(p + i * stride);
  }
}
template <int S, int N, bool SPL, int T> __device__ __forceinline__ void ll_check(uint4 (&v)[T], const uint4* p, int stride, uint32_t tag, const uint2* p2 = nullptr) {
#pragma unroll 1
  for (int it = 0; it < SPIN; it++) {
    uint32_t bad = 0;
#pragma unroll
    for (int i = S; i < S + N; i++) bad |= (v[i].x ^ tag) | ((SPL && i % 7 == 3) ? (v[i].z ^ tag) : 0u);
    if (!__any_sync(~0u, bad & 1)) break;
    ll_issue<S, N, SPL>(v, p, stride, p2);
  }
}
__device__ __forceinline__ void hint_post(uint32_t* p, uint32_t v, int lane) {
  if (lane == 0) asm volatile("st.relaxed.gpu.global.u32 [%0], %1;" ::"l"(p), "r"(v) : "memory");
}
__device__ __forceinline__ void hint_wait(const uint32_t* p, uint32_t s, uint32_t v = 0xffffu) {
#pragma unroll 1
  for (int it = 0; it < SPIN; it++) {
    if (__all_sync(~0u, v - s < 10u)) break;
    v = hint_ld(p);
  }
}
__device__ __forceinline__ void slice_store(uint4* pf, uint2* ph, const uint32_t (&w)[14], bool odd) {
#pragma unroll
  for (int u = 0; u < 3; u++)
    stll(pf + u * 32, odd ? w[4 * u + 2] : w[4 * u], odd ? w[4 * u + 3] : w[4 * u + 1], odd ? w[4 * u + 4] : w[4 * u + 2], odd ? w[4 * u + 5] : w[4 * u + 3]);
  stll2(ph, odd ? w[0] : w[12], odd ? w[1] : w[13]);
}
template <class F, class M> __device__ __forceinline__ void hedgehog(const float (&d)[28], F sink, M mid) {
  const float L2E = 1.4426950408889634f;
#define HX(G, p) ((p) < 6 ? d[((G) & 1) * 16 + ((p) >> 1) * 4 + ((p) & 1) + ((G) & 2)] : d[12 + (G)])
  float mx[4], mn[4], sp[4], sn[4], ep[4][7], en[4][7];
#pragma unroll
  for (int G = 0; G < 4; G++) {
    mx[G] = mn[G] = HX(G, 0);
#pragma unroll
    for (int p = 1; p < 7; p++) { mx[G] = fmaxf(mx[G], HX(G, p)); mn[G] = fminf(mn[G], HX(G, p)); }
  }
#pragma unroll
  for (int o = 1; o < 4; o <<= 1)
#pragma unroll
    for (int G = 0; G < 4; G++) { mx[G] = fmaxf(mx[G], __shfl_xor_sync(~0u, mx[G], o)); mn[G] = fminf(mn[G], __shfl_xor_sync(~0u, mn[G], o)); }
#pragma unroll
  for (int G = 0; G < 4; G++) {
    const float a = -mx[G] * L2E, b = mn[G] * L2E;
#pragma unroll
    for (int p = 0; p < 7; p++) { ep[G][p] = ex2(fmaf(HX(G, p), L2E, a)); en[G][p] = ex2(fmaf(HX(G, p), -L2E, b)); }
    sp[G] = ((ep[G][0] + ep[G][1]) + (ep[G][2] + ep[G][3])) + ((ep[G][4] + ep[G][5]) + ep[G][6]);
    sn[G] = ((en[G][0] + en[G][1]) + (en[G][2] + en[G][3])) + ((en[G][4] + en[G][5]) + en[G][6]);
    if (G == 1) mid();
  }
#pragma unroll
  for (int o = 1; o < 4; o <<= 1)
#pragma unroll
    for (int G = 0; G < 4; G++) { sp[G] += __shfl_xor_sync(~0u, sp[G], o); sn[G] += __shfl_xor_sync(~0u, sn[G], o); }
#pragma unroll
  for (int G = 0; G < 4; G++) {
    const float a = rcp(sp[G]), b = rcp(sn[G]);
#pragma unroll
    for (int p = 0; p < 7; p++) sink(G >> 1, G & 1, p, pack(ep[G][p] * a, en[G][p] * b));
  }
}
__device__ __forceinline__ void phi_gemm(const float (&x)[28], float (&y)[28], uint32_t wphi, float r0, float r1) {
  uint32_t f[14];
#pragma unroll
  for (int j = 0; j < 14; j++) f[j] = pack(x[2 * j] * (j & 1 ? r1 : r0), x[2 * j + 1] * (j & 1 ? r1 : r0));
  wg_fence();
#pragma unroll
  for (int ks = 0; ks < 3; ks++) wgmma_rs56(y, f[4 * ks], f[4 * ks + 1], f[4 * ks + 2], f[4 * ks + 3], mkdesc(wphi, ks * 2048, 1024, 1024, 1), ks);
  wgmma_rs56(y, f[12], f[13], 0u, 0u, mkdesc(wphi, 3 * 2048, 1024, 1024, 1), 1);
  wg_commit();
}
__device__ __forceinline__ void ln_stats(uint32_t (&xw)[4][4], float* sLN, int warp, int lane, uint4* dst) {
  const int g = lane >> 2; const bool full = warp < 4;
  float s0 = 0.f, s1 = 0.f;
#pragma unroll
  for (int u = 0; u < 4; u++) {
    s0 += (blo(xw[u][0]) + bhi(xw[u][0])) + (blo(xw[u][2]) + bhi(xw[u][2]));
    s1 += (blo(xw[u][1]) + bhi(xw[u][1])) + (blo(xw[u][3]) + bhi(xw[u][3]));
  }
  const float rc = full ? 1.f / 64 : 1.f / 48;
  s0 = qsum(s0); s1 = qsum(s1);
  const float a0 = s0 * rc, a1 = s1 * rc;
  float v0 = 0.f, v1 = 0.f;
#pragma unroll
  for (int u = 0; u < 4; u++)
    if (u < 3 || full) {
#pragma unroll
      for (int k = 0; k < 4; k += 2) {
        float a = blo(xw[u][k]) - a0, b = bhi(xw[u][k]) - a0, c2 = blo(xw[u][k + 1]) - a1, d2 = bhi(xw[u][k + 1]) - a1;
        v0 += a * a + b * b; v1 += c2 * c2 + d2 * d2;
      }
    }
  v0 = qsum(v0); v1 = qsum(v1);
  if ((lane & 3) == 0) *(float4*)(sLN + (g * 8 + warp) * 4) = make_float4(s0, v0, s1, v1);
  if (warp) { asm volatile("bar.arrive 7, 256;" ::: "memory"); return; }
  asm volatile("bar.sync 7, 256;" ::: "memory");
  const float4 ea = *(const float4*)(sLN + (g * 8 + (lane & 3)) * 4), eb = *(const float4*)(sLN + (g * 8 + 4 + (lane & 3)) * 4);
  const float m0 = qsum(ea.x + eb.x) * (1.f / 448), m1 = qsum(ea.z + eb.z) * (1.f / 448);
  const float d0 = ea.x * (1.f / 64) - m0, d1 = eb.x * (1.f / 48) - m0, d2 = ea.z * (1.f / 64) - m1, d3 = eb.z * (1.f / 48) - m1;
  v0 = qsum(ea.y + eb.y + 64.f * d0 * d0 + 48.f * d1 * d1); v1 = qsum(ea.w + eb.w + 64.f * d2 * d2 + 48.f * d3 * d3);
  if ((lane & 3) == 0) stll(dst + g, tg(__float_as_uint(m0), 1), __float_as_uint(rsqrtf(v0 * (1.f / 448) + 1e-5f)), __float_as_uint(m1), __float_as_uint(rsqrtf(v1 * (1.f / 448) + 1e-5f)));
}

__global__ void __launch_bounds__(384, 1)
fused_kernel(const __grid_constant__ CUtensorMap mQKV, const __grid_constant__ CUtensorMap mWO, const __grid_constant__ CUtensorMap mW1,
             const __grid_constant__ CUtensorMap mW1b, const __grid_constant__ CUtensorMap mW2, const __grid_constant__ CUtensorMap mW2b,
             const __grid_constant__ CUtensorMap mX, const __nv_bfloat16* __restrict__ wqkv, const __nv_bfloat16* __restrict__ wphi,
             const __nv_bfloat16* __restrict__ wo, const __nv_bfloat16* __restrict__ w1, const __nv_bfloat16* __restrict__ b1,
             const __nv_bfloat16* __restrict__ w2, const __nv_bfloat16* __restrict__ b2, __nv_bfloat16* __restrict__ out) {
  extern __shared__ __align__(1024) uint8_t sm[];
  constexpr uint32_t sb = 1024;
  if (s2u(sm) != sb) __trap();
  const int tid = threadIdx.x, warp = __shfl_sync(~0u, tid >> 5, 0), lane = tid & 31,
            t = blockIdx.x >> 3, c = blockIdx.x & 7;
  const uint32_t bfull = sb + OFF_BAR, bempty = bfull + 8 * NST;

#define XOFF(l) ((t * 128 + c * 16 + ((l) >> 2)) * 448 + warp * 16 + 2 * ((l) & 3))
  if (warp < 8) { MARK(0); GT(19); }
  if (tid == 256) {
    for (int s = 0; s < NST; s++) { mbar_init(bfull + 8 * s, 1); mbar_init(bempty + 8 * s, 8); }
    mbar_init(bempty + 8 * NST, 1);
    asm volatile("fence.mbarrier_init.release.cluster;" ::: "memory");
    fence_async();
    mbar_expect(bempty + 8 * NST, 114688);
    for (int i = 0; i < 7; i++)
      asm volatile("cp.async.bulk.tensor.2d.shared::cluster.global.mbarrier::complete_tx::bytes [%0], [%1, {%3, %4}], [%2];"
                   ::"r"(sb + 2 * STAGE + i * 16384), "l"(&mX), "r"(bempty + 8 * NST), "r"(64 * i), "r"(128 * t) : "memory");
  }
  __syncthreads();
  if (warp >= 8) {
    asm volatile("setmaxnreg.dec.sync.aligned.u32 24;");
    auto issue = [&](int i, int s) {
      const uint32_t dst = sb + s * STAGE, bar = bfull + 8 * s;
      mbar_expect(bar, STAGE);
#pragma unroll 1
      for (int rk = 0; rk < 2; rk++)
      if (i < 4) tma2d(dst + rk * 14336, &mQKV, 448 + 448 * rk + 56 * c, 112 * i, bar);
      else if (i < 8) tma2d(dst + rk * 14336, i < 6 ? &mQKV : &mWO, (i < 6 ? 56 : 64) * c, 224 * (i & 1) + 112 * rk, bar);
      else if (i < 15) { const int k0 = 64 * ((i - 8 + c) % 7) + 32 * rk;
        tma3d(dst + rk * 12288, &mW1, 0, k0, 3 * c, bar); tma2d(dst + 24576 + rk * 2048, &mW1b, 1536 + 32 * c, k0, bar); }
      else { tma2d(dst + rk * 12288, &mW2, 64 * (i - 15), 192 * c + 96 * rk, bar); tma2d(dst + 24576 + rk * 2048, &mW2b, 64 * (i - 15), 1536 + 32 * c + 16 * rk, bar); }
    };
    auto colsum = [&](int job) {
        const int ld4 = job < 112 ? 448 : 336;
        const uint2* wp = (job < 112 ? (const uint2*)w1 + job * 4 : (const uint2*)wqkv + (job - 112) * 4) + (lane >> 2) * ld4 + (lane & 3);
        float s0 = 0.f, s1 = 0.f, s2 = 0.f, s3 = 0.f;
#pragma unroll 8
        for (int i = 0; i < 56; i++) { const uint2 v = __ldg(wp + i * 8 * ld4); s0 += blo(v.x); s1 += bhi(v.x); s2 += blo(v.y); s3 += bhi(v.y); }
#pragma unroll 1
        for (int o = 4; o < 32; o <<= 1) { s0 += __shfl_xor_sync(~0u, s0, o); s1 += __shfl_xor_sync(~0u, s1, o); s2 += __shfl_xor_sync(~0u, s2, o); s3 += __shfl_xor_sync(~0u, s3, o); }
        if (lane < 4) stll(g_CS + job * 4 + lane, tg(__float_as_uint(s0), 1), __float_as_uint(s1), __float_as_uint(s2), __float_as_uint(s3));
      };
    if (warp == 8) {
#pragma unroll 1
      for (int n = 0; n < 44; n++) {
        const int L = n >= 22, i = L ? (n < 28 ? (n - 18) % 6 : n - 22) : n, s = i % 6;
        if (n == 2) asm volatile("bar.sync 2, 288;" ::: "memory");
        mbar_wait(bempty + 8 * s, (i / 6 + (s >= 4 ? L : 0) + 1) & 1);
        if (n == 22) {
          uint32_t v = 0;
#pragma unroll 1
          for (int it = 0; it < SPIN && v < 32; it++) asm volatile("ld.acquire.gpu.global.u32 %0, [%1];" : "=r"(v) : "l"(g_WQF + c) : "memory");
          asm volatile("fence.proxy.async.global;" ::: "memory");
        }
        if (lane == 0) {
          if (n >= 22 && n < 28) {
            mbar_expect(bfull + 8 * s, STAGE);
            asm volatile("cp.async.bulk.shared::cluster.global.mbarrier::complete_tx::bytes [%0], [%1], %2, [%3];"
                         ::"r"(sb + s * STAGE), "l"(g_WQ + c * 10752 + i * (STAGE / 16)), "r"(STAGE), "r"(bfull + 8 * s) : "memory");
          } else issue(i, s);
        }
        __syncwarp();
      }
    } else if (warp == 9) {
      mbar_wait(bfull + 8 * 3, 0);
      if (lane == 0) {
        l2pf((const uint8_t*)wo + blockIdx.x * 3136, 3136);
        l2pf((const uint8_t*)w1 + blockIdx.x * 12544, 12544);
        l2pf((const uint8_t*)w2 + blockIdx.x * 12544, 12544);
      }
      if (blockIdx.x < 112) colsum(blockIdx.x);
      asm volatile("bar.sync 6, 96;" ::: "memory");
#pragma unroll 1
      for (int i = 0; i < 4; i++) {
        const int e = lane < 28 ? lane + 28 * (i & 1) : 0;
        const bool ok = i < 2 || (e < 48 && (e & 15) < 14);
        const int e4 = i < 2 ? (e < 48 ? 48 * c + e : 336 + 8 * c + e) : ok ? 448 + 112 * (e >> 4) + 14 * c + (e & 15) : 448;
        uint4 cv[1];
        ll_issue<0, 1>(cv, g_CS + e4, 0); ll_check<0, 1, false>(cv, g_CS + e4, 0, 1u);
        const uint2 bb = __ldg((const uint2*)b1 + (i < 2 ? e4 : 0));
        const uint32_t h0 = pack(__uint_as_float(cv[0].x), __uint_as_float(cv[0].y)), h1 = pack(__uint_as_float(cv[0].z), __uint_as_float(cv[0].w));
        const uint32_t l0 = pack(__uint_as_float(cv[0].x) - blo(h0), __uint_as_float(cv[0].y) - bhi(h0)), l1 = pack(__uint_as_float(cv[0].z) - blo(h1), __uint_as_float(cv[0].w) - bhi(h1));
#pragma unroll 1
        for (int j = 0; j < (i < 2 ? 5 : 3); j++) {
          const int r = i < 2 ? j : j + 5;
          const uint32_t ad = sb + OFF_CB + (e >> 3) * 512 + r * 64 + ((((e >> 1) ^ (r >> 1)) & 3) << 4) + (e & 1) * 8;
          sts32(ad, j < 2 ? h0 : j == 2 ? l0 : bb.x); sts32(ad + 4, j < 2 ? h1 : j == 2 ? l1 : bb.y);
        }
        if (i & 1) { fence_async(); if (i == 1) asm volatile("bar.arrive 4, 288;" ::: "memory"); else asm volatile("bar.arrive 8, 160; bar.arrive 9, 160;" ::: "memory"); }
      }
    } else if (warp >= 10) {
      const int h = warp - 10;
      uint4 wv[4];
#pragma unroll
      for (int i = 0; i < 4; i++) wv[i] = __ldg((const uint4*)wphi + (2 * c + h) * 98 + min(lane + 32 * i, 97));
#pragma unroll 1
      for (int e = h * 32 + lane; e < 672; e += 64) sts128(sb + OFF_WPHI + e * 16, 0, 0, 0, 0);
      asm volatile("bar.arrive 6, 96;" ::: "memory");
#pragma unroll 1
      for (int i = 0; i < 4; i++) sts128(sb + OFF_PHIK + sw128(h * 128 + i * 32 + lane, 56), 0, 0, 0, 0);
      asm volatile("bar.sync 5, 64;" ::: "memory");
#pragma unroll
      for (int i = 0; i < 4; i++) sts128(sb + OFF_V + h * 2048 + (lane + 32 * i) * 16, wv[i].x, wv[i].y, wv[i].z, wv[i].w);
      __syncwarp();
#pragma unroll 1
      for (int e = lane; e < 392; e += 32) {
        const int d = e / 14, f2 = 2 * (e - 14 * d), k = 28 * h + d;
        const uint32_t v = *(volatile uint32_t*)(sm + OFF_V + h * 2048 + e * 4);
        if (f2 < 24) sts32(sb + OFF_WPHI + sw128(k, 32 * h + f2), v);
        else { sts16(sb + OFF_WPHI + sw128(k, 2 * f2 - 24 + h), v); sts16(sb + OFF_WPHI + sw128(k, 2 * f2 - 22 + h), v >> 16); }
      }
      fence_async();
      asm volatile("bar.arrive 3, 320;" ::: "memory");
      mbar_wait(bfull + 8 * 5, 0);
#pragma unroll 2
      for (int e = t * 672 + h * 32 + lane; e < t * 672 + 672; e += 64) {
        const int r = e >> 3, st = r / 224, rr = r - st * 224, ch = (e & 7) ^ (rr & 7);
        const int k = st < 4 ? 112 * st + (rr >= 112 ? rr - 112 : rr) : 224 * (st - 4) + rr, col = (st < 4 ? (rr >= 112 ? 896 : 448) : 0) + 56 * c + 8 * ch;
        g_WQ[c * 10752 + e] = ch < 7 ? __ldg((const uint4*)(wqkv + k * 1344 + col)) : make_uint4(0, 0, 0, 0);
      }
      __syncwarp();
      if (lane == 0) asm volatile("red.release.gpu.global.add.u32 [%0], 1;" ::"l"(g_WQF + c) : "memory");
      if (h == 0 && blockIdx.x < 84) colsum(112 + blockIdx.x);
    }
  } else {
  asm volatile("setmaxnreg.inc.sync.aligned.u32 240;");

  const int wg = warp >> 2, g = lane >> 2, q = lane & 3;
  const int row0 = warp * 16 + g;
#define PTRS const int ln_ = laneid(); \
  uint4* const fm = g_F + ((t * 8 + warp) * 28) * 32 + ln_;            \
  uint4* const fr = g_F + ((t * 8 + c) * 28 + warp) * 32 + ln_;        \
  uint4* const sf = fm + (7 * (c >> 1) + 4 * (c & 1)) * 32;             \
  uint2* const f2 = (uint2*)(fm - ln_) + ln_;                           \
  uint2* const sh = f2 + (7 * (c >> 1) + 3) * 64 + 32 * (c & 1);        \
  uint32_t* const hme = g_H + (t * 8 + warp) * 8 + c; \
  const uint32_t* const hrow = g_H + (t * 8 + warp) * 8 + (ln_ & 7); \
  (void)fm; (void)fr; (void)sf; (void)f2; (void)sh; (void)hme; (void)hrow;
  float* sLN = (float*)(sm + OFF_V);
  const uint32_t sPK = sb + OFF_PHIK, sV = sb + OFF_V, d16 = (sb & 0x3FFFF) >> 4;
    uint32_t xw[4][4];
#pragma unroll
  for (int i = 0; i < 16; i++) xw[i >> 2][i & 3] = 0;
#define ACQ(I) (mbar_wait(bfull + 8 * ((I) % 6), ((I) / 6 + ((I) % 6 >= 4 ? L : 0)) & 1), d16 + ((I) % 6) * (STAGE >> 4))
#define REL(I) { if (lane == 0) mbar_arrive(bempty + 8 * ((I) % 6)); }
#define RISSUE(m, P, XA, XB, BA, BB) { ll_issue<0, 8>(P, pr + (m) * 256, 896); \
      { const uint4 v_ = ldll(fr + X1 + (m) * 256); XA = make_uint2(v_.x, v_.y); XB = make_uint2(v_.z, v_.w); } \
      const uint32_t* bp = (const uint32_t*)(b2 + 128 * (m) + 16 * warp) + (ln_ & 3); BA = __ldg(bp); BB = __ldg(bp + 4); }
#define REDU(m, P, XA, XB, BA, BB) { ll_check<0, 8, false>(P, pr + (m) * 256, 896, ptag); \
      float e[8] = {blo(XA.x) + blo(BA), bhi(XA.x) + bhi(BA), blo(XA.y) + blo(BA), bhi(XA.y) + bhi(BA), blo(XB.x) + blo(BB), bhi(XB.x) + bhi(BB), blo(XB.y) + blo(BB), bhi(XB.y) + bhi(BB)}; \
      _Pragma("unroll") for (int i = 0; i < 8; i++) { e[0] += blo(P[i].x); e[1] += bhi(P[i].x); e[2] += blo(P[i].y); e[3] += bhi(P[i].y); \
        e[4] += blo(P[i].z); e[5] += bhi(P[i].z); e[6] += blo(P[i].w); e[7] += bhi(P[i].w); } \
      xw[m][0] = pack(e[0], e[1]); xw[m][1] = pack(e[2], e[3]); xw[m][2] = pack(e[4], e[5]); xw[m][3] = pack(e[6], e[7]); }
#define RPUB(m) stll(fr + XR + (m) * 256, tg(xw[m][0], 0), xw[m][1], xw[m][2], xw[m][3]);
#define RLAST(ptag_, hv) { const uint32_t ptag = ptag_; const uint4* pr = g_P + ((t * 8 + c) * 8 * 28 + warp) * 32 + ln_; uint4 p[8]; uint2 xa, xb; uint32_t ba, bb; \
      if (ptag_) hint_wait(g_H + (t * 8 + c) * 8 + (ln_ & 7), hv); RISSUE(3, p, xa, xb, ba, bb) REDU(3, p, xa, xb, ba, bb) }
#pragma unroll 1
  for (int L = 0; L < 2; L++) {
    const uint32_t tag = 1 - L;
    uint32_t phq[2][2][7];
    const uint32_t hs = 10 * L;
    {
      PTRS
      uint4 a[28];
      const uint4* pa = fm + XR;
      uint32_t fa = 0, fb = 0;
      float r0 = 1.f, r1 = 1.f;
      if (L == 0) {
        hint_post(hme, 1, lane);
        mbar_wait(bempty + 8 * NST, 0);
        MARK(1);
        const int row = warp * 16 + (ln_ & 15);
        const uint32_t xb = sb + 2 * STAGE + row * 128;
        float cs_[4][4] = {};
#pragma unroll
        for (int ks = 0; ks < 28; ks++) { a[ks] = ldsm4(xb + (ks >> 2) * 16384 + (((2 * (ks & 3) + (ln_ >> 4)) ^ (row & 7)) << 4)); mma16816(cs_[ks & 3], a[ks], 0x3F803F80u, 0x3F803F80u); }
        if (c < 7) {
#pragma unroll
          for (int u = 0; u < 4; u++) { const uint4 v = ldsm4(xb + c * 16384 + (((2 * u + (ln_ >> 4)) ^ (row & 7)) << 4)); stll(fm + XR + 128 * c + u * 32, tg(v.x, tag), v.y, v.z, v.w); }
        }
        const float m0 = ((cs_[0][0] + cs_[1][0]) + (cs_[2][0] + cs_[3][0])) * (1.f / 448), m1 = ((cs_[0][2] + cs_[1][2]) + (cs_[2][2] + cs_[3][2])) * (1.f / 448);
        const uint32_t mb0 = pack(m0, m0), mb1 = pack(m1, m1);
        asm volatile("bar.arrive 2, 288;" ::"r"(mb0) : "memory");
#pragma unroll
        for (int ks = 0; ks < 28; ks++) {
          a[ks].x = bsub(a[ks].x, mb0); a[ks].y = bsub(a[ks].y, mb1); a[ks].z = bsub(a[ks].z, mb0); a[ks].w = bsub(a[ks].w, mb1);
        }
        r0 = m0 - blo(mb0); r1 = m1 - blo(mb1);
      } else {
        ll_issue<0, 14>(a, pa, 32);
        if (wg == 0) { RLAST(1u, 10u) xw[3][0] = tg(xw[3][0], 0); RPUB(3) } else { xw[3][0] = xw[3][1] = xw[3][2] = xw[3][3] = 0; }
        MARK(20);
        ll_issue<14, 7>(a, pa, 32);
        ln_stats(xw, sLN, warp, lane, g_S2 + (t * 8 + c) * 8);
      }
      MARK(2 + L * 19);
      float ak[28], av[28], aq[28], pp[28];
#define KVSTAGE(i) { if (L) ll_check<7 * i, 7, false>(a, pa, 32, tag); const uint32_t st = ACQ(i); wg_fence(); \
      _Pragma("unroll") for (int ks = 0; ks < 7; ks++) { const uint4 f = a[7 * i + ks]; \
        wgmma_rs56(ak, f.x, f.y, f.z, f.w, mkdesc(st, ks * 2048, 1024, 1024, 1), i | ks); \
        wgmma_rs56(av, f.x, f.y, f.z, f.w, mkdesc(st, 14336 + ks * 2048, 1024, 1024, 1), i | ks); } \
      wg_commit(); if (i > 0) { wg_wait<1>(); REL(i + 5) } }
      KVSTAGE(0) KVSTAGE(1)
      uint4 sv[1] = {make_uint4(0, 0, 0, 0)};
      const uint4* ps = g_S2 + (t * 8 + warp) * 8 + (ln_ >> 2);
      if (L) { ll_issue<21, 7>(a, pa, 32); ll_issue<0, 1>(sv, ps, 0); }
      else {
        float c0[2][4] = {}, c1[2][4] = {};
#pragma unroll
        for (int ks = 0; ks < 28; ks++) { mma16816(c0[ks & 1], a[ks], a[ks].x, a[ks].z); mma16816(c1[ks & 1], a[ks], a[ks].y, a[ks].w); }
        const int src = (ln_ & 28) | (g >> 1);
        const float q0 = __shfl_sync(~0u, (g & 1) ? c0[0][1] + c0[1][1] : c0[0][0] + c0[1][0], src), q1 = __shfl_sync(~0u, (g & 1) ? c1[0][3] + c1[1][3] : c1[0][2] + c1[1][2], src);
        r0 = rsqrtf(fmaxf(q0 * (1.f / 448) - r0 * r0, 0.f) + 1e-5f); r1 = rsqrtf(fmaxf(q1 * (1.f / 448) - r1 * r1, 0.f) + 1e-5f);
      }
      KVSTAGE(2) KVSTAGE(3)
      if (L) {
        if (wg) asm volatile("bar.sync 9, 160;" ::: "memory"); else asm volatile("bar.sync 8, 160;" ::: "memory");
        ll_check<0, 1, false>(sv, ps, 0, 1u);
        const float m0 = -__uint_as_float(sv[0].x), m1 = -__uint_as_float(sv[0].z), h0 = blo(pack(m0, 0.f)), h1 = blo(pack(m1, 0.f));
        r0 = __uint_as_float(sv[0].y); r1 = __uint_as_float(sv[0].w);
        fa = q == 2 ? pack(0.f, h0) : q == 3 ? pack(m0 - h0, h0) : 0u; fb = q == 2 ? pack(0.f, h1) : q == 3 ? pack(m1 - h1, h1) : 0u;
      } else {
        asm volatile("bar.sync 3, 320;" ::: "memory");
      }
      wg_fence();
      wgmma_rs56(ak, fa, fb, 0u, 0u, mkdesc(d16, OFF_CB + 1024, 512, 0, 2), 1);
      wgmma_rs56(av, fa, fb, 0u, 0u, mkdesc(d16, OFF_CB + 2048, 512, 0, 2), 1);
      wg_commit();
      wg_wait<0>(); REL(3) regfence(ak); regfence(av);
      MARK(3 + L * 19);
      phi_gemm(ak, pp, d16 + (OFF_WPHI >> 4), r0, r1);
#pragma unroll
      for (int j = 0; j < 7; j++) {
        const int n = 8 * j + 2 * q, n2 = n < 28 ? n : n + 4;
        sts32(sV + sw128(row0, n2), pack(av[4 * j] * r0, av[4 * j + 1] * r0)); sts32(sV + sw128(row0 + 8, n2), pack(av[4 * j + 2] * r1, av[4 * j + 3] * r1));
      }
      { const int n2 = 28 + 2 * (q & 1) + 32 * (q >> 1); const uint32_t v = (q & 1) ? 0u : 0x3F80u; sts32(sV + sw128(row0, n2), v); sts32(sV + sw128(row0 + 8, n2), v); }
      wg_wait<0>(); regfence(pp);
      hedgehog(pp, [&](int r, int h, int p, uint32_t v) { sts32(sPK + h * 16384 + sw128(row0 + 8 * r, 8 * p + 2 * q), v); }, [] {});
      fence_async();
      bar_cons();
      MARK(4 + L * 19);
      float kv[16];
      wg_fence();
#pragma unroll
      for (int ks = 0; ks < 8; ks++) wgmma_ss32(kv, mkdesc(d16 + wg * 1024, OFF_PHIK + ks * 2048, 1024, 1024, 1), mkdesc(d16 + wg * 4, OFF_V + ks * 2048, 1024, 1024, 1), ks);
      wg_commit(); wg_wait<0>(); regfence(kv);
      const int ln2 = laneid();
#pragma unroll
      for (int u = 0; u < 4; u++) {
        float e[4];
#pragma unroll
        for (int i = 0; i < 4; i++) e[i] = kv[4 * u + i];
        stll(g_KVP + (c * 16 + t) * 1024 + wg * 512 + u * 128 + (warp & 3) * 32 + ln2, tg(__float_as_uint(e[0]), tag), __float_as_uint(e[1]), __float_as_uint(e[2]), __float_as_uint(e[3]));
      }
      MARK(5 + L * 19);
      uint4 k4[4];
      const uint4* pk = g_KVP + (c * 16 + 4 * (ln2 & 3)) * 1024 + 64 * t + warp * 8 + (ln2 >> 2);
#pragma unroll
      for (int i = 0; i < 2; i++) {
        const uint32_t st = ACQ(4 + i); wg_fence();
#pragma unroll
        for (int ks = 0; ks < 14; ks++) { const uint4 f = a[14 * i + ks]; wgmma_rs56(aq, f.x, f.y, f.z, f.w, mkdesc(st, ks * 2048, 1024, 1024, 1), i | ks); }
        if (i == 1) wgmma_rs56(aq, fa, fb, 0u, 0u, mkdesc(d16, OFF_CB, 512, 0, 2), 1);
        wg_commit();
        if (i == 1) ll_issue<0, 4>(k4, pk, 1024);
      }
      ll_check<0, 4, false>(k4, pk, 1024, tag);
      float s0 = 0, s1 = 0, s2 = 0, s3 = 0;
#pragma unroll
      for (int i = 0; i < 4; i++) { s0 += __uint_as_float(k4[i].x); s1 += __uint_as_float(k4[i].y); s2 += __uint_as_float(k4[i].z); s3 += __uint_as_float(k4[i].w); }
      s0 = qsum(s0); s1 = qsum(s1); s2 = qsum(s2); s3 = qsum(s3);
      if (q == 0) stll2(g_KVR + c * 1024 + 64 * t + warp * 8 + (ln2 >> 2), tg(pack(s0, s1), tag), pack(s2, s3));
      MARK(6 + L * 19);
      wg_wait<0>(); REL(4) REL(5) regfence(aq);
      phi_gemm(aq, pp, d16 + (OFF_WPHI >> 4), r0, r1);
      bar_cons();
#pragma unroll
      for (int i = 0; i < 4; i++) sts128(sV + warp * 2048 + (lane + i * 32) * 16, 0, 0, 0, 0);
      wg_wait<0>(); regfence(pp);
      uint2 r[4];
      const uint2* pr = g_KVR + c * 1024 + wg * 512 + (warp & 3) * 32 + ln2;
      hedgehog(pp, [&](int r, int h, int p, uint32_t v) { phq[r][h][p] = v; }, [&] {
#pragma unroll
        for (int u = 0; u < 4; u++) r[u] = ldll2(pr + u * 128); });
      MARK(7 + L * 19);
#pragma unroll 1
      for (int it = 0; it < SPIN; it++) {
        if (!__any_sync(~0u, ((r[0].x ^ tag) | (r[1].x ^ tag) | (r[2].x ^ tag) | (r[3].x ^ tag)) & 1)) break;
#pragma unroll
        for (int u = 0; u < 4; u++) r[u] = ldll2(pr + u * 128);
      }
#pragma unroll
      for (int u = 0; u < 4; u++) {
        const int d = 8 * u + 2 * q;
        if (d < 28) { sts32(sV + sw128(row0, 28 * wg + d), r[u].x); sts32(sV + sw128(row0 + 8, 28 * wg + d), r[u].y); }
        else if (d == 28) {
#pragma unroll
          for (int j = 0; j < 4; j++) { sts16(sV + sw128(row0, 56 + 2 * j + wg), r[u].x); sts16(sV + sw128(row0 + 8, 56 + 2 * j + wg), r[u].y); }
        }
      }
      fence_async();
      bar_cons();
      MARK(8 + L * 19);
      float o[32];
      wg_fence();
#pragma unroll
      for (int ks = 0; ks < 8; ks++) {
        const int h = ks >> 2, p = 2 * (ks & 3);
        wgmma_rs64(o, phq[0][h][p], phq[1][h][p], p < 6 ? phq[0][h][p < 6 ? p + 1 : 0] : 0u, p < 6 ? phq[1][h][p < 6 ? p + 1 : 0] : 0u, mkdesc(d16, OFF_V + ks * 2048, 1024, 1024, 1), ks);
      }
      wg_commit(); wg_wait<0>(); regfence(o);
      const float iA0 = rcp(o[28] + 1e-6f), iB0 = rcp(o[29] + 1e-6f), iA1 = rcp(o[30] + 1e-6f), iB1 = rcp(o[31] + 1e-6f);
      uint32_t w[14];
      { PTRS
#pragma unroll
      for (int j = 0; j < 7; j++) {
        const bool hb = 8 * j + 2 * q >= 28; const float i0 = hb ? iB0 : iA0, i1 = hb ? iB1 : iA1;
        w[2 * j] = pack(o[4 * j] * i0, o[4 * j + 1] * i0); w[2 * j + 1] = pack(o[4 * j + 2] * i1, o[4 * j + 3] * i1);
        if (j == 0 || ((j ^ c) & 1) == 0) w[2 * j] = tg(w[2 * j], tag);
      }
      slice_store(sf + OO, sh + 2 * OO, w, c & 1);
      hint_post(hme, hs + 2, lane); }
    }
    MARK(9 + L * 19);
    uint4 xr[4];
    if (c < 7) {
      PTRS
      ll_issue<0, 4>(xr, fm + XR + 128 * c, 32);
      uint4 a[28];
      const uint4* pa = fm + OO;
      hint_wait(hrow, hs + 2);
      MARK(10 + L * 19);
      ll_issue<0, 28, true>(a, pa, 32, f2 + 2 * OO);
      float y[32];
      uint32_t st;
#define WOSTEP(i) { ll_check<7 * i, 7, true>(a, pa, 32, tag, f2 + 2 * OO); if (!(i & 1)) st = ACQ(6 + i / 2); wg_fence(); \
      _Pragma("unroll") for (int ks = 0; ks < 7; ks++) { const uint4 f = a[7 * i + ks]; \
        wgmma_rs64(y, f.x, f.y, f.z, f.w, mkdesc(st, ((i & 1) * 7 + ks) * 2048, 1024, 1024, 1), i | ks); } wg_commit(); }
      WOSTEP(0) WOSTEP(1) WOSTEP(2) WOSTEP(3)
      ll_check<0, 4, false>(xr, fm + XR + 128 * c, 32, tag);
      wg_wait<0>(); regfence(y);
      MARK(11 + L * 19);
#pragma unroll
      for (int u = 0; u < 4; u++) {
        xr[u].x = tg(pack(blo(xr[u].x) + y[8 * u], bhi(xr[u].x) + y[8 * u + 1]), tag); xr[u].y = pack(blo(xr[u].y) + y[8 * u + 2], bhi(xr[u].y) + y[8 * u + 3]);
        xr[u].z = pack(blo(xr[u].z) + y[8 * u + 4], bhi(xr[u].z) + y[8 * u + 5]); xr[u].w = pack(blo(xr[u].w) + y[8 * u + 6], bhi(xr[u].w) + y[8 * u + 7]);
        stll(fm + X1 + 128 * c + u * 32, xr[u].x, xr[u].y, xr[u].z, xr[u].w);
      }
      hint_post(hme, hs + 3, lane);
    } else {
      PTRS
      hint_post(hme, hs + 3, lane);
      (void)ACQ(6); (void)ACQ(7);
      hint_wait(hrow, hs + 3);
      ll_issue<0, 4>(xr, fm + X1, 32);
      MARK(10 + L * 19); MARK(11 + L * 19);
    }
    uint32_t hf[56];
    float rr0, rr1;
    {
      PTRS
      uint4 a[28];
      const uint4* pa = fm + X1;
      auto grp = [&](int i) -> const uint4* { const int k = i + c; return pa + ((k >= 7 ? k - 7 : k) - i) * 128; };
      if (c == 7) { ll_issue<4, 12>(a, pa, 32); ll_check<0, 4, false>(xr, pa, 32, tag); }
      else {
#pragma unroll
        for (int u = 4; u < 16; u++) a[u] = make_uint4(0, 0, 0, 0);
      }
#pragma unroll
      for (int u = 0; u < 4; u++) a[u] = xr[u];
      float y[96], z[16];
#define F1STAGE(i) { if (i > 0) ll_check<4 * i, 4, false>(a, grp(i), 32, tag); const uint32_t st = ACQ(8 + i); wg_fence(); \
      _Pragma("unroll") for (int ks = 0; ks < 4; ks++) { const uint4 f = a[4 * i + ks]; \
        wgmma_rs192(y, f.x, f.y, f.z, f.w, mkdesc(st, (ks >> 1) * 12288 + (ks & 1) * 2048, 4096, 1024, 1), i | ks); \
        wgmma_rs32(z, f.x, f.y, f.z, f.w, mkdesc(st, 24576 + ks * 1024, 512, 512, 2), i | ks); } \
      wg_commit(); if (i > 0) { wg_wait<1>(); REL(6 + i) if (i < 4) ll_issue<(i < 4 ? 4 * i + 12 : 0), 4>(a, grp(i + 3), 32); } }
      F1STAGE(0)
      MARK(12 + L * 19);
      if (c < 7) {
        hint_wait(hrow, hs + 3);
        ll_issue<4, 4>(a, grp(1), 32); ll_issue<8, 4>(a, grp(2), 32); ll_issue<12, 4>(a, grp(3), 32);
        float s0 = 0.f, s1 = 0.f, v0 = 0.f, v1 = 0.f;
#pragma unroll
        for (int u = 0; u < 4; u++) { s0 += (blo(xr[u].x) + bhi(xr[u].x)) + (blo(xr[u].z) + bhi(xr[u].z)); s1 += (blo(xr[u].y) + bhi(xr[u].y)) + (blo(xr[u].w) + bhi(xr[u].w)); }
        s0 = qsum(s0) * (1.f / 64); s1 = qsum(s1) * (1.f / 64);
#pragma unroll
        for (int u = 0; u < 4; u++) {
          const float d0 = blo(xr[u].x) - s0, d1 = bhi(xr[u].x) - s0, d2 = blo(xr[u].z) - s0, d3 = bhi(xr[u].z) - s0;
          const float d4 = blo(xr[u].y) - s1, d5 = bhi(xr[u].y) - s1, d6 = blo(xr[u].w) - s1, d7 = bhi(xr[u].w) - s1;
          v0 += (d0 * d0 + d1 * d1) + (d2 * d2 + d3 * d3); v1 += (d4 * d4 + d5 * d5) + (d6 * d6 + d7 * d7);
        }
        v0 = qsum(v0); v1 = qsum(v1);
        if (q == 0) stll(g_ST + ((t * 8 + warp) * 8 + c) * 8 + (ln_ >> 2), tg(__float_as_uint(s0), tag), __float_as_uint(v0), __float_as_uint(s1), __float_as_uint(v1));
      }
      REL(6)
      F1STAGE(1) MARK(13 + L * 19); F1STAGE(2) F1STAGE(3)
      uint4 sv[2];
      const uint4* ps = g_ST + ((t * 8 + warp) * 8 + 2 * (laneid() & 3)) * 8 + (laneid() >> 2);
      ll_issue<0, 2>(sv, ps, q < 3 ? 8 : 0);
      F1STAGE(4)
      ll_check<0, 2, false>(sv, ps, q < 3 ? 8 : 0, tag);
      const float wb = q < 3 ? 1.f : 0.f;
      const float ma = __uint_as_float(sv[0].x), mb = __uint_as_float(sv[1].x), mc = __uint_as_float(sv[0].z), md = __uint_as_float(sv[1].z);
      const float m0 = qsum(ma + wb * mb) * (1.f / 7), m1 = qsum(mc + wb * md) * (1.f / 7);
      const float v0 = qsum(__uint_as_float(sv[0].y) + 64.f * (ma - m0) * (ma - m0) + wb * (__uint_as_float(sv[1].y) + 64.f * (mb - m0) * (mb - m0)));
      const float v1 = qsum(__uint_as_float(sv[0].w) + 64.f * (mc - m1) * (mc - m1) + wb * (__uint_as_float(sv[1].w) + 64.f * (md - m1) * (md - m1)));
      const float e0 = v0 * (1.f / 448) + 1e-5f, e1 = v1 * (1.f / 448) + 1e-5f;
      rr0 = 1.f / e0; rr1 = 1.f / e1;
      auto fold = [&](float m, float sd) -> uint32_t {
        const float mh = blo(pack(-m, 0.f)), sh_ = blo(pack(sd, 0.f));
        return q == 0 ? pack(mh, -m - mh) : q == 1 ? pack(mh, sh_) : q == 2 ? pack(sd - sh_, 0.f) : 0u;
      };
      const uint32_t fa = fold(m0, sqrtf(e0)), fb = fold(m1, sqrtf(e1));
      if (L == 0) asm volatile("bar.sync 4, 288;" ::: "memory");
      wg_fence();
      wgmma_rs192(y, fa, fb, 0u, 0u, mkdesc(d16, OFF_CB, 512, 0, 2), 1);
      wgmma_rs32(z, fa, fb, 0u, 0u, mkdesc(d16, OFF_CB + 3072, 512, 0, 2), 1);
      F1STAGE(5) F1STAGE(6)
      wg_wait<0>(); REL(13) REL(14) regfence(y); regfence(z);
      MARK(14 + L * 19);
#pragma unroll
      for (int j = 0; j < 56; j++) {
        uint32_t r; asm("cvt.rn.relu.bf16x2.f32 %0, %1, %2;" : "=r"(r) : "f"(j < 48 ? y[j < 48 ? 2 * j + 1 : 0] : z[j < 48 ? 0 : 2 * j - 95]), "f"(j < 48 ? y[j < 48 ? 2 * j : 0] : z[j < 48 ? 0 : 2 * j - 96]));
        asm("mul.bf16x2 %0, %1, %1;" : "=r"(hf[j]) : "r"(r));
      }
    }
    MARK(15 + L * 19);
    {
      PTRS
      float ya[32], yb[32];
      uint4* pp = g_P + ((t * 8 + warp) * 8 + c) * 28 * 32 + ln_;
#define F2STORE(j, Y) { regfence(Y); _Pragma("unroll") for (int u = 0; u < 4; u++) \
      stll(pp + (4 * (j) + u) * 32, tg(pack(Y[8 * u] * rr0, Y[8 * u + 1] * rr0), tag), pack(Y[8 * u + 2] * rr1, Y[8 * u + 3] * rr1), \
           pack(Y[8 * u + 4] * rr0, Y[8 * u + 5] * rr0), pack(Y[8 * u + 6] * rr1, Y[8 * u + 7] * rr1)); if ((j) >= 5) hint_post(hme, hs + (4 + (j)), lane); }
#define F2PASS(j, Y, Z) { const uint32_t st = ACQ(15 + j); wg_fence(); \
      _Pragma("unroll") for (int ks = 0; ks < 14; ks++) wgmma_rs64(Y, hf[4 * ks], hf[4 * ks + 1], hf[4 * ks + 2], hf[4 * ks + 3], mkdesc(st, ks * 2048, 1024, 1024, 1), ks); \
      wg_commit(); if (j > 0) { wg_wait<1>(); REL(14 + j) F2STORE(j - 1, Z) } }
      const uint4* pr = g_P + ((t * 8 + c) * 8 * 28 + warp) * 32 + ln_;
      uint4 p[8], p2[8]; uint2 xa, xb, xc, xd; uint32_t ba, bb, bc, bd;
      const uint32_t ptag = tag;
      const uint32_t* hred = g_H + (t * 8 + c) * 8 + (ln_ & 7);
      F2PASS(0, ya, yb) F2PASS(1, yb, ya) F2PASS(2, ya, yb) F2PASS(3, yb, ya)
      F2PASS(4, ya, yb)
      RISSUE(0, p, xa, xb, ba, bb)
      F2PASS(5, yb, ya)
      REDU(0, p, xa, xb, ba, bb)
      if (L == 0) { xw[0][0] = tg(xw[0][0], 0); RPUB(0) }
      F2PASS(6, ya, yb)
      RISSUE(1, p, xa, xb, ba, bb)
      wg_wait<0>(); REL(21) F2STORE(6, ya)
      MARK(16 + L * 19);
      if (wg) hint_wait(hred, hs + 9);
      RISSUE(2, p2, xc, xd, bc, bd)
      REDU(1, p, xa, xb, ba, bb)
      if (L == 0) { xw[1][0] = tg(xw[1][0], 0); RPUB(1) }
      MARK(17 + L * 19);
      REDU(2, p2, xc, xd, bc, bd)
      if (L == 0) { xw[2][0] = tg(xw[2][0], 0); RPUB(2) }
    }
    MARK(18 + L * 19);
  }
  {
    PTRS
    uint32_t* op = (uint32_t*)(out + XOFF(ln_));
#define OUT(u) { op[u * 64] = xw[u][0]; op[u * 64 + 1792] = xw[u][1]; op[u * 64 + 4] = xw[u][2]; op[u * 64 + 1796] = xw[u][3]; }
    OUT(0) OUT(1) OUT(2)
    if (wg == 0) { RLAST(0u, 20u) OUT(3) }
    else if (warp == 7) {
      if (t == 0 && lane == 0) g_WQF[c] = 0;
      if (lane < 8) stll(g_S2 + (t * 8 + c) * 8 + lane, 0, 0, 0, 0);
      if (lane < 4) { stll(g_CS + blockIdx.x * 4 + lane, 0, 0, 0, 0); if (blockIdx.x < 68) stll(g_CS + 512 + blockIdx.x * 4 + lane, 0, 0, 0, 0); }
    }
  }
  MARK(38); GT(39);
  }
}

typedef CUresult (*EncFn)(CUtensorMap*, CUtensorMapDataType, cuuint32_t, void*, const cuuint64_t*, const cuuint64_t*, const cuuint32_t*, const cuuint32_t*,
                          CUtensorMapInterleave, CUtensorMapSwizzle, CUtensorMapL2promotion, CUtensorMapFloatOOBfill);

extern "C" void kernel_launch(void* const* d_in, const int* in_sizes, int n_in, void* d_out, int out_size) {
  static EncFn enc = nullptr;
  if (!enc) {
    void* fn = nullptr; cudaDriverEntryPointQueryResult qr;
    cudaGetDriverEntryPoint("cuTensorMapEncodeTiled", &fn, cudaEnableDefault, &qr);
    enc = (EncFn)fn;
    cudaFuncSetAttribute(fused_kernel, cudaFuncAttributeMaxDynamicSharedMemorySize, SMEM_BYTES);
  }
  CUtensorMap mQKV, mWO, mW1, mW1b, mW2, mW2b, mX;
  const cuuint32_t es[3] = {1, 1, 1};
  auto enc2 = [&](CUtensorMap* m, void* p, cuuint64_t cols, cuuint64_t rows, cuuint32_t bc, cuuint32_t br) {
    const cuuint64_t dims[2] = {cols, rows}, str[1] = {cols * 2}; const cuuint32_t box[2] = {bc, br};
    enc(m, CU_TENSOR_MAP_DATA_TYPE_BFLOAT16, 2, p, dims, str, box, es, CU_TENSOR_MAP_INTERLEAVE_NONE,
        bc == 64 ? CU_TENSOR_MAP_SWIZZLE_128B : CU_TENSOR_MAP_SWIZZLE_64B, CU_TENSOR_MAP_L2_PROMOTION_L2_128B, CU_TENSOR_MAP_FLOAT_OOB_FILL_NONE);
  };
  enc2(&mQKV, d_in[1], 1344, 448, 64, 112); enc2(&mWO, d_in[3], 448, 448, 64, 112); enc2(&mW1b, d_in[5], 1792, 448, 32, 32);
  enc2(&mX, d_in[0], 448, 2048, 64, 128);
  enc2(&mW2, d_in[7], 448, 1792, 64, 96); enc2(&mW2b, d_in[7], 448, 1792, 64, 16);
  {
    const cuuint64_t dims[3] = {64, 448, 28}, str[2] = {3584, 128}; const cuuint32_t box[3] = {64, 32, 3};
    enc(&mW1, CU_TENSOR_MAP_DATA_TYPE_BFLOAT16, 3, d_in[5], dims, str, box, es, CU_TENSOR_MAP_INTERLEAVE_NONE, CU_TENSOR_MAP_SWIZZLE_128B,
        CU_TENSOR_MAP_L2_PROMOTION_L2_128B, CU_TENSOR_MAP_FLOAT_OOB_FILL_NONE);
  }
  typedef const __nv_bfloat16* BP;
  fused_kernel<<<128, 384, SMEM_BYTES>>>(mQKV, mWO, mW1, mW1b, mW2, mW2b, mX, (BP)d_in[1], (BP)d_in[2], (BP)d_in[3], (BP)d_in[5], (BP)d_in[6], (BP)d_in[7], (BP)d_in[8],
                                         (__nv_bfloat16*)d_out);
}
```

```cpp
#include <cuda_runtime.h>
#include <cuda_bf16.h>
#include <cuda.h>
#include <stdint.h>

constexpr int NST = 6, STAGE = 28672;
constexpr int OFF_PHIK = NST * STAGE;
constexpr int OFF_V = OFF_PHIK + 32768;
constexpr int OFF_WPHI = OFF_V + 16384;
constexpr int OFF_CB = OFF_WPHI + 7168;
constexpr int OFF_BAR = OFF_CB + 3584;
constexpr int SMEM_BYTES = OFF_BAR + 16 * NST + 8;
constexpr int FR = 16 * 8 * 28 * 32;
constexpr int SPIN = 1 << 18;

__device__ uint4 g_F[3 * FR];
constexpr int XR = 0, OO = FR, X1 = 2 * FR;
__device__ uint4 g_P[8 * FR];
__device__ uint4 g_ST[16 * 8 * 8 * 8];
__device__ uint4 g_KVP[8 * 16 * 1024];
__device__ uint2 g_KVR[8 * 1024];
__device__ uint4 g_CS[784];
__device__ uint4 g_S2[16 * 8 * 8];
__device__ uint4 g_WQ[8 * 6 * (STAGE / 16)];
__device__ uint32_t g_WQF[8];
__device__ uint32_t g_H[16 * 8 * 8];
#define MARK(i)
#define GT(i)

__device__ __forceinline__ uint32_t s2u(const void* p) { return (uint32_t)__cvta_generic_to_shared(p); }
__device__ __forceinline__ void mbar_init(uint32_t b, uint32_t c) { asm volatile("mbarrier.init.shared::cta.b64 [%0], %1;" ::"r"(b), "r"(c)); }
__device__ __forceinline__ void mbar_expect(uint32_t b, uint32_t tx) { asm volatile("mbarrier.arrive.expect_tx.shared::cta.b64 _, [%0], %1;" ::"r"(b), "r"(tx) : "memory"); }
__device__ __forceinline__ void mbar_arrive(uint32_t b) { asm volatile("mbarrier.arrive.shared::cta.b64 _, [%0];" ::"r"(b) : "memory"); }
__device__ __forceinline__ void mbar_wait(uint32_t b, uint32_t ph) {
  uint32_t ok = 0;
#pragma unroll 1
  for (int it = 0; it < SPIN && !ok; it++)
    asm volatile("{.reg .pred p; mbarrier.try_wait.parity.shared::cta.b64 p,[%1],%2; selp.u32 %0,1,0,p;}" : "=r"(ok) : "r"(b), "r"(ph) : "memory");
}
__device__ __forceinline__ void tma2d(uint32_t dst, const CUtensorMap* m, int c0, int c1, uint32_t bar) {
  asm volatile("cp.async.bulk.tensor.2d.shared::cluster.global.mbarrier::complete_tx::bytes [%0], [%1, {%3, %4}], [%2];"
               ::"r"(dst), "l"(m), "r"(bar), "r"(c0), "r"(c1) : "memory");
}
__device__ __forceinline__ void tma3d(uint32_t dst, const CUtensorMap* m, int c0, int c1, int c2, uint32_t bar) {
  asm volatile("cp.async.bulk.tensor.3d.shared::cluster.global.mbarrier::complete_tx::bytes [%0], [%1, {%3, %4, %5}], [%2];"
               ::"r"(dst), "l"(m), "r"(bar), "r"(c0), "r"(c1), "r"(c2) : "memory");
}
__device__ __forceinline__ void l2pf(const void* p, uint32_t bytes) { asm volatile("cp.async.bulk.prefetch.L2.global [%0], %1;" ::"l"(p), "r"(bytes) : "memory"); }
__device__ __forceinline__ void wg_fence() { asm volatile("wgmma.fence.sync.aligned;" ::: "memory"); }
__device__ __forceinline__ void wg_commit() { asm volatile("wgmma.commit_group.sync.aligned;" ::: "memory"); }
template <int N> __device__ __forceinline__ void wg_wait() { asm volatile("wgmma.wait_group.sync.aligned %0;" ::"n"(N) : "memory"); }
template <int N> __device__ __forceinline__ void regfence(float (&d)[N]) {
#pragma unroll
  for (int i = 0; i < N; i++) asm volatile("" : "+f"(d[i])::"memory");
}
__device__ __forceinline__ void bar_cons() { asm volatile("bar.sync 1, 256;" ::: "memory"); }
__device__ __forceinline__ void fence_async() { asm volatile("fence.proxy.async.shared::cta;" ::: "memory"); }
struct Desc { uint32_t lo, hi; };
__device__ __forceinline__ Desc mkdesc(uint32_t base16, uint32_t off, uint32_t lbo, uint32_t sbo, uint32_t swz) {
  return Desc{base16 + ((off >> 4) | ((lbo >> 4) << 16)), (sbo >> 4) | (swz << 30)};
}
__device__ __forceinline__ uint4 ldll(const uint4* p) {
  uint4 v; asm volatile("ld.relaxed.gpu.global.v4.u32 {%0,%1,%2,%3}, [%4];" : "=r"(v.x), "=r"(v.y), "=r"(v.z), "=r"(v.w) : "l"(p) : "memory"); return v;
}
__device__ __forceinline__ uint2 ldll2(const uint2* p) {
  uint2 v; asm volatile("ld.relaxed.gpu.global.v2.u32 {%0,%1}, [%2];" : "=r"(v.x), "=r"(v.y) : "l"(p) : "memory"); return v;
}
__device__ __forceinline__ void stll(uint4* p, uint32_t x, uint32_t y, uint32_t z, uint32_t w) {
  asm volatile("st.relaxed.gpu.global.v4.u32 [%0], {%1,%2,%3,%4};" ::"l"(p), "r"(x), "r"(y), "r"(z), "r"(w) : "memory");
}
__device__ __forceinline__ void stll2(void* p, uint32_t x, uint32_t y) {
  asm volatile("st.relaxed.gpu.global.v2.u32 [%0], {%1,%2};" ::"l"(p), "r"(x), "r"(y) : "memory");
}
__device__ __forceinline__ int laneid() { int l; asm volatile("mov.u32 %0, %%laneid;" : "=r"(l)); return l; }
__device__ __forceinline__ uint32_t tg(uint32_t w, uint32_t tag) { return (w & ~1u) | tag; }
__device__ __forceinline__ uint32_t pack(float lo, float hi) {
  uint32_t r; asm("cvt.rn.bf16x2.f32 %0, %1, %2;" : "=r"(r) : "f"(hi), "f"(lo)); return r;
}
__device__ __forceinline__ float blo(uint32_t w) { return __uint_as_float(w << 16); }
__device__ __forceinline__ float bhi(uint32_t w) { return __uint_as_float(w & 0xffff0000u); }
__device__ __forceinline__ float ex2(float x) { float r; asm("ex2.approx.ftz.f32 %0, %1;" : "=f"(r) : "f"(x)); return r; }
__device__ __forceinline__ float rcp(float x) { float r; asm("rcp.approx.ftz.f32 %0, %1;" : "=f"(r) : "f"(x)); return r; }
__device__ __forceinline__ float qsum(float v) { v += __shfl_xor_sync(~0u, v, 1); v += __shfl_xor_sync(~0u, v, 2); return v; }
__device__ __forceinline__ void sts32(uint32_t a, uint32_t v) { asm volatile("st.shared.u32 [%0], %1;" ::"r"(a), "r"(v) : "memory"); }
__device__ __forceinline__ void sts16(uint32_t a, uint32_t v) { asm volatile("st.shared.u16 [%0], %1;" ::"r"(a), "h"((uint16_t)v) : "memory"); }
__device__ __forceinline__ void sts128(uint32_t a, uint32_t x, uint32_t y, uint32_t z, uint32_t w) {
  asm volatile("st.shared.v4.u32 [%0], {%1,%2,%3,%4};" ::"r"(a), "r"(x), "r"(y), "r"(z), "r"(w) : "memory");
}
__device__ __forceinline__ uint32_t sw128(int row, int col) { return row * 128 + ((((col >> 3) ^ row) & 7) << 4) + (col & 7) * 2; }

__device__ __forceinline__ void wgmma_rs56(float (&d)[28], const uint32_t a0, const uint32_t a1, const uint32_t a2, const uint32_t a3, Desc db, int sd) {
  asm volatile("{.reg .pred p; .reg .b64 da, db; setp.ne.b32 p, %33, 0; mov.b64 db, {%32, %34};\n wgmma.mma_async.sync.aligned.m64n56k16.f32.bf16.bf16 {%0,%1,%2,%3,%4,%5,%6,%7,%8,%9,%10,%11,%12,%13,%14,%15,%16,%17,%18,%19,%20,%21,%22,%23,%24,%25,%26,%27}, {%28,%29,%30,%31}, db, p, 1, 1, 1;}"
   : "+f"(d[0]),"+f"(d[1]),"+f"(d[2]),"+f"(d[3]),"+f"(d[4]),"+f"(d[5]),"+f"(d[6]),"+f"(d[7]),"+f"(d[8]),"+f"(d[9]),"+f"(d[10]),"+f"(d[11]),"+f"(d[12]),"+f"(d[13]),"+f"(d[14]),"+f"(d[15]),"+f"(d[16]),"+f"(d[17]),"+f"(d[18]),"+f"(d[19]),"+f"(d[20]),"+f"(d[21]),"+f"(d[22]),"+f"(d[23]),"+f"(d[24]),"+f"(d[25]),"+f"(d[26]),"+f"(d[27])
   : "r"(a0),"r"(a1),"r"(a2),"r"(a3),"r"(db.lo),"r"(sd),"r"(db.hi));
}
__device__ __forceinline__ void wgmma_rs64(float (&d)[32], const uint32_t a0, const uint32_t a1, const uint32_t a2, const uint32_t a3, Desc db, int sd) {
  asm volatile("{.reg .pred p; .reg .b64 da, db; setp.ne.b32 p, %37, 0; mov.b64 db, {%36, %38};\n wgmma.mma_async.sync.aligned.m64n64k16.f32.bf16.bf16 {%0,%1,%2,%3,%4,%5,%6,%7,%8,%9,%10,%11,%12,%13,%14,%15,%16,%17,%18,%19,%20,%21,%22,%23,%24,%25,%26,%27,%28,%29,%30,%31}, {%32,%33,%34,%35}, db, p, 1, 1, 1;}"
   : "+f"(d[0]),"+f"(d[1]),"+f"(d[2]),"+f"(d[3]),"+f"(d[4]),"+f"(d[5]),"+f"(d[6]),"+f"(d[7]),"+f"(d[8]),"+f"(d[9]),"+f"(d[10]),"+f"(d[11]),"+f"(d[12]),"+f"(d[13]),"+f"(d[14]),"+f"(d[15]),"+f"(d[16]),"+f"(d[17]),"+f"(d[18]),"+f"(d[19]),"+f"(d[20]),"+f"(d[21]),"+f"(d[22]),"+f"(d[23]),"+f"(d[24]),"+f"(d[25]),"+f"(d[26]),"+f"(d[27]),"+f"(d[28]),"+f"(d[29]),"+f"(d[30]),"+f"(d[31])
   : "r"(a0),"r"(a1),"r"(a2),"r"(a3),"r"(db.lo),"r"(sd),"r"(db.hi));
}
__device__ __forceinline__ void wgmma_rs192(float (&d)[96], const uint32_t a0, const uint32_t a1, const uint32_t a2, const uint32_t a3, Desc db, int sd) {
  asm volatile("{.reg .pred p; .reg .b64 db; setp.ne.b32 p, %101, 0; mov.b64 db, {%100, %102};\n wgmma.mma_async.sync.aligned.m64n192k16.f32.bf16.bf16 {%0,%1,%2,%3,%4,%5,%6,%7,%8,%9,%10,%11,%12,%13,%14,%15,%16,%17,%18,%19,%20,%21,%22,%23,%24,%25,%26,%27,%28,%29,%30,%31,%32,%33,%34,%35,%36,%37,%38,%39,%40,%41,%42,%43,%44,%45,%46,%47,%48,%49,%50,%51,%52,%53,%54,%55,%56,%57,%58,%59,%60,%61,%62,%63,%64,%65,%66,%67,%68,%69,%70,%71,%72,%73,%74,%75,%76,%77,%78,%79,%80,%81,%82,%83,%84,%85,%86,%87,%88,%89,%90,%91,%92,%93,%94,%95}, {%96,%97,%98,%99}, db, p, 1, 1, 1;}"
   : "+f"(d[0]),"+f"(d[1]),"+f"(d[2]),"+f"(d[3]),"+f"(d[4]),"+f"(d[5]),"+f"(d[6]),"+f"(d[7]),"+f"(d[8]),"+f"(d[9]),"+f"(d[10]),"+f"(d[11]),"+f"(d[12]),"+f"(d[13]),"+f"(d[14]),"+f"(d[15]),"+f"(d[16]),"+f"(d[17]),"+f"(d[18]),"+f"(d[19]),"+f"(d[20]),"+f"(d[21]),"+f"(d[22]),"+f"(d[23]),"+f"(d[24]),"+f"(d[25]),"+f"(d[26]),"+f"(d[27]),"+f"(d[28]),"+f"(d[29]),"+f"(d[30]),"+f"(d[31]),"+f"(d[32]),"+f"(d[33]),"+f"(d[34]),"+f"(d[35]),"+f"(d[36]),"+f"(d[37]),"+f"(d[38]),"+f"(d[39]),"+f"(d[40]),"+f"(d[41]),"+f"(d[42]),"+f"(d[43]),"+f"(d[44]),"+f"(d[45]),"+f"(d[46]),"+f"(d[47]),"+f"(d[48]),"+f"(d[49]),"+f"(d[50]),"+f"(d[51]),"+f"(d[52]),"+f"(d[53]),"+f"(d[54]),"+f"(d[55]),"+f"(d[56]),"+f"(d[57]),"+f"(d[58]),"+f"(d[59]),"+f"(d[60]),"+f"(d[61]),"+f"(d[62]),"+f"(d[63]),"+f"(d[64]),"+f"(d[65]),"+f"(d[66]),"+f"(d[67]),"+f"(d[68]),"+f"(d[69]),"+f"(d[70]),"+f"(d[71]),"+f"(d[72]),"+f"(d[73]),"+f"(d[74]),"+f"(d[75]),"+f"(d[76]),"+f"(d[77]),"+f"(d[78]),"+f"(d[79]),"+f"(d[80]),"+f"(d[81]),"+f"(d[82]),"+f"(d[83]),"+f"(d[84]),"+f"(d[85]),"+f"(d[86]),"+f"(d[87]),"+f"(d[88]),"+f"(d[89]),"+f"(d[90]),"+f"(d[91]),"+f"(d[92]),"+f"(d[93]),"+f"(d[94]),"+f"(d[95])
   : "r"(a0),"r"(a1),"r"(a2),"r"(a3),"r"(db.lo),"r"(sd),"r"(db.hi));
}
__device__ __forceinline__ void wgmma_rs32(float (&d)[16], const uint32_t a0, const uint32_t a1, const uint32_t a2, const uint32_t a3, Desc db, int sd) {
  asm volatile("{.reg .pred p; .reg .b64 db; setp.ne.b32 p, %21, 0; mov.b64 db, {%20, %22};\n wgmma.mma_async.sync.aligned.m64n32k16.f32.bf16.bf16 {%0,%1,%2,%3,%4,%5,%6,%7,%8,%9,%10,%11,%12,%13,%14,%15}, {%16,%17,%18,%19}, db, p, 1, 1, 1;}"
   : "+f"(d[0]),"+f"(d[1]),"+f"(d[2]),"+f"(d[3]),"+f"(d[4]),"+f"(d[5]),"+f"(d[6]),"+f"(d[7]),"+f"(d[8]),"+f"(d[9]),"+f"(d[10]),"+f"(d[11]),"+f"(d[12]),"+f"(d[13]),"+f"(d[14]),"+f"(d[15])
   : "r"(a0),"r"(a1),"r"(a2),"r"(a3),"r"(db.lo),"r"(sd),"r"(db.hi));
}
__device__ __forceinline__ void wgmma_ss32(float (&d)[16], Desc da, Desc db, int sd) {
  asm volatile("{.reg .pred p; .reg .b64 da, db; setp.ne.b32 p, %18, 0; mov.b64 da, {%16, %19}; mov.b64 db, {%17, %19};\n wgmma.mma_async.sync.aligned.m64n32k16.f32.bf16.bf16 {%0,%1,%2,%3,%4,%5,%6,%7,%8,%9,%10,%11,%12,%13,%14,%15}, da, db, p, 1, 1, 1, 1;}"
   : "+f"(d[0]),"+f"(d[1]),"+f"(d[2]),"+f"(d[3]),"+f"(d[4]),"+f"(d[5]),"+f"(d[6]),"+f"(d[7]),"+f"(d[8]),"+f"(d[9]),"+f"(d[10]),"+f"(d[11]),"+f"(d[12]),"+f"(d[13]),"+f"(d[14]),"+f"(d[15])
   : "r"(da.lo),"r"(db.lo),"r"(sd),"r"(db.hi));
}

__device__ __forceinline__ uint4 ldsm4(uint32_t a) {
  uint4 v; asm volatile("ldmatrix.sync.aligned.m8n8.x4.shared.b16 {%0,%1,%2,%3}, [%4];" : "=r"(v.x), "=r"(v.y), "=r"(v.z), "=r"(v.w) : "r"(a) : "memory"); return v;
}
__device__ __forceinline__ void mma16816(float (&d)[4], const uint4& a, uint32_t b0, uint32_t b1) {
  asm("mma.sync.aligned.m16n8k16.row.col.f32.bf16.bf16.f32 {%0,%1,%2,%3}, {%4,%5,%6,%7}, {%8,%9}, {%0,%1,%2,%3};"
      : "+f"(d[0]), "+f"(d[1]), "+f"(d[2]), "+f"(d[3]) : "r"(a.x), "r"(a.y), "r"(a.z), "r"(a.w), "r"(b0), "r"(b1));
}
__device__ __forceinline__ uint32_t bsub(uint32_t a, uint32_t b) { uint32_t r; asm("sub.bf16x2 %0, %1, %2;" : "=r"(r) : "r"(a), "r"(b)); return r; }
__device__ __forceinline__ uint32_t hint_ld(const uint32_t* p) { uint32_t v; asm volatile("ld.relaxed.gpu.global.u32 %0, [%1];" : "=r"(v) : "l"(p) : "memory"); return v; }
template <int S, int N, bool SPL = false, int T> __device__ __forceinline__ void ll_issue(uint4 (&v)[T], const uint4* p, int stride, const uint2* p2 = nullptr) {
#pragma unroll
  for (int i = S; i < S + N; i++) {
    if (SPL && i % 7 == 3) { const uint2 lo = ldll2(p2 + i * 64), hi = ldll2(p2 + i * 64 + 32); v[i] = make_uint4(lo.x, lo.y, hi.x, hi.y); }
    else v[i] = ldll(p + i * stride);
  }
}
template <int S, int N, bool SPL, int T> __device__ __forceinline__ void ll_check(uint4 (&v)[T], const uint4* p, int stride, uint32_t tag, const uint2* p2 = nullptr) {
#pragma unroll 1
  for (int it = 0; it < SPIN; it++) {
    uint32_t bad = 0;
#pragma unroll
    for (int i = S; i < S + N; i++) bad |= (v[i].x ^ tag) | ((SPL && i % 7 == 3) ? (v[i].z ^ tag) : 0u);
    if (!__any_sync(~0u, bad & 1)) break;
    ll_issue<S, N, SPL>(v, p, stride, p2);
  }
}
__device__ __forceinline__ void hint_post(uint32_t* p, uint32_t v, int lane) {
  if (lane == 0) asm volatile("st.relaxed.gpu.global.u32 [%0], %1;" ::"l"(p), "r"(v) : "memory");
}
__device__ __forceinline__ void hint_wait(const uint32_t* p, uint32_t s, uint32_t v = 0xffffu) {
#pragma unroll 1
  for (int it = 0; it < SPIN; it++) {
    if (__all_sync(~0u, v - s < 10u)) break;
    v = hint_ld(p);
  }
}
__device__ __forceinline__ void probe_wait(const uint4* p, uint32_t tag) {
#pragma unroll 1
  for (int it = 0; it < SPIN; it++) if (!__any_sync(~0u, (hint_ld((const uint32_t*)p) ^ tag) & 1)) break;
}
template <int N> __device__ __forceinline__ void bulk_wait_read(int lane) {
  if (lane == 0) asm volatile("cp.async.bulk.wait_group.read %0;" ::"n"(N) : "memory");
  __syncwarp();
}
__device__ __forceinline__ void slice_store(uint4* pf, uint2* ph, const uint32_t (&w)[14], bool odd) {
#pragma unroll
  for (int u = 0; u < 3; u++)
    stll(pf + u * 32, odd ? w[4 * u + 2] : w[4 * u], odd ? w[4 * u + 3] : w[4 * u + 1], odd ? w[4 * u + 4] : w[4 * u + 2], odd ? w[4 * u + 5] : w[4 * u + 3]);
  stll2(ph, odd ? w[0] : w[12], odd ? w[1] : w[13]);
}
template <class F, class M> __device__ __forceinline__ void hedgehog(const float (&d)[28], F sink, M mid) {
  const float L2E = 1.4426950408889634f;
#define HX(G, p) ((p) < 6 ? d[((G) & 1) * 16 + ((p) >> 1) * 4 + ((p) & 1) + ((G) & 2)] : d[12 + (G)])
  float mx[4], mn[4], sp[4], sn[4], ep[4][7], en[4][7];
#pragma unroll
  for (int G = 0; G < 4; G++) {
    mx[G] = mn[G] = HX(G, 0);
#pragma unroll
    for (int p = 1; p < 7; p++) { mx[G] = fmaxf(mx[G], HX(G, p)); mn[G] = fminf(mn[G], HX(G, p)); }
  }
#pragma unroll
  for (int o = 1; o < 4; o <<= 1)
#pragma unroll
    for (int G = 0; G < 4; G++) { mx[G] = fmaxf(mx[G], __shfl_xor_sync(~0u, mx[G], o)); mn[G] = fminf(mn[G], __shfl_xor_sync(~0u, mn[G], o)); }
#pragma unroll
  for (int G = 0; G < 4; G++) {
    const float a = -mx[G] * L2E, b = mn[G] * L2E;
#pragma unroll
    for (int p = 0; p < 7; p++) { ep[G][p] = ex2(fmaf(HX(G, p), L2E, a)); en[G][p] = ex2(fmaf(HX(G, p), -L2E, b)); }
    sp[G] = ((ep[G][0] + ep[G][1]) + (ep[G][2] + ep[G][3])) + ((ep[G][4] + ep[G][5]) + ep[G][6]);
    sn[G] = ((en[G][0] + en[G][1]) + (en[G][2] + en[G][3])) + ((en[G][4] + en[G][5]) + en[G][6]);
    if (G == 1) mid();
  }
#pragma unroll
  for (int o = 1; o < 4; o <<= 1)
#pragma unroll
    for (int G = 0; G < 4; G++) { sp[G] += __shfl_xor_sync(~0u, sp[G], o); sn[G] += __shfl_xor_sync(~0u, sn[G], o); }
#pragma unroll
  for (int G = 0; G < 4; G++) {
    const float a = rcp(sp[G]), b = rcp(sn[G]);
#pragma unroll
    for (int p = 0; p < 7; p++) sink(G >> 1, G & 1, p, pack(ep[G][p] * a, en[G][p] * b));
  }
}
__device__ __forceinline__ void phi_gemm(const float (&x)[28], float (&y)[28], uint32_t wphi, float r0, float r1) {
  uint32_t f[14];
#pragma unroll
  for (int j = 0; j < 14; j++) f[j] = pack(x[2 * j] * (j & 1 ? r1 : r0), x[2 * j + 1] * (j & 1 ? r1 : r0));
  wg_fence();
#pragma unroll
  for (int ks = 0; ks < 3; ks++) wgmma_rs56(y, f[4 * ks], f[4 * ks + 1], f[4 * ks + 2], f[4 * ks + 3], mkdesc(wphi, ks * 2048, 1024, 1024, 1), ks);
  wgmma_rs56(y, f[12], f[13], 0u, 0u, mkdesc(wphi, 3 * 2048, 1024, 1024, 1), 1);
  wg_commit();
}
__device__ __forceinline__ void ln_stats(uint32_t (&xw)[4][4], float* sLN, int warp, int lane, uint4* dst) {
  const int g = lane >> 2; const bool full = warp < 4;
  float s0 = 0.f, s1 = 0.f;
#pragma unroll
  for (int u = 0; u < 4; u++) {
    s0 += (blo(xw[u][0]) + bhi(xw[u][0])) + (blo(xw[u][2]) + bhi(xw[u][2]));
    s1 += (blo(xw[u][1]) + bhi(xw[u][1])) + (blo(xw[u][3]) + bhi(xw[u][3]));
  }
  const float rc = full ? 1.f / 64 : 1.f / 48;
  s0 = qsum(s0); s1 = qsum(s1);
  const float a0 = s0 * rc, a1 = s1 * rc;
  float v0 = 0.f, v1 = 0.f;
#pragma unroll
  for (int u = 0; u < 4; u++)
    if (u < 3 || full) {
#pragma unroll
      for (int k = 0; k < 4; k += 2) {
        float a = blo(xw[u][k]) - a0, b = bhi(xw[u][k]) - a0, c2 = blo(xw[u][k + 1]) - a1, d2 = bhi(xw[u][k + 1]) - a1;
        v0 += a * a + b * b; v1 += c2 * c2 + d2 * d2;
      }
    }
  v0 = qsum(v0); v1 = qsum(v1);
  if ((lane & 3) == 0) *(float4*)(sLN + (g * 8 + warp) * 4) = make_float4(s0, v0, s1, v1);
  if (warp) { asm volatile("bar.arrive 7, 256;" ::: "memory"); return; }
  asm volatile("bar.sync 7, 256;" ::: "memory");
  const float4 ea = *(const float4*)(sLN + (g * 8 + (lane & 3)) * 4), eb = *(const float4*)(sLN + (g * 8 + 4 + (lane & 3)) * 4);
  const float m0 = qsum(ea.x + eb.x) * (1.f / 448), m1 = qsum(ea.z + eb.z) * (1.f / 448);
  const float d0 = ea.x * (1.f / 64) - m0, d1 = eb.x * (1.f / 48) - m0, d2 = ea.z * (1.f / 64) - m1, d3 = eb.z * (1.f / 48) - m1;
  v0 = qsum(ea.y + eb.y + 64.f * d0 * d0 + 48.f * d1 * d1); v1 = qsum(ea.w + eb.w + 64.f * d2 * d2 + 48.f * d3 * d3);
  if ((lane & 3) == 0) stll(dst + g, tg(__float_as_uint(m0), 1), __float_as_uint(rsqrtf(v0 * (1.f / 448) + 1e-5f)), __float_as_uint(m1), __float_as_uint(rsqrtf(v1 * (1.f / 448) + 1e-5f)));
}

__global__ void __launch_bounds__(384, 1)
fused_kernel(const __grid_constant__ CUtensorMap mQKV, const __grid_constant__ CUtensorMap mWO, const __grid_constant__ CUtensorMap mW1,
             const __grid_constant__ CUtensorMap mW1b, const __grid_constant__ CUtensorMap mW2, const __grid_constant__ CUtensorMap mW2b,
             const __grid_constant__ CUtensorMap mX, const __nv_bfloat16* __restrict__ wqkv, const __nv_bfloat16* __restrict__ wphi,
             const __nv_bfloat16* __restrict__ wo, const __nv_bfloat16* __restrict__ w1, const __nv_bfloat16* __restrict__ b1,
             const __nv_bfloat16* __restrict__ w2, const __nv_bfloat16* __restrict__ b2, __nv_bfloat16* __restrict__ out) {
  extern __shared__ __align__(1024) uint8_t sm[];
  constexpr uint32_t sb = 1024;
  if (s2u(sm) != sb) __trap();
  const int tid = threadIdx.x, warp = __shfl_sync(~0u, tid >> 5, 0), lane = tid & 31,
            t = blockIdx.x >> 3, c = blockIdx.x & 7;
  const uint32_t bfull = sb + OFF_BAR, bempty = bfull + 8 * NST;

#define XOFF(l) ((t * 128 + c * 16 + ((l) >> 2)) * 448 + warp * 16 + 2 * ((l) & 3))
  if (warp < 8) { MARK(0); GT(19); }
  if (tid == 256) {
    for (int s = 0; s < NST; s++) { mbar_init(bfull + 8 * s, 1); mbar_init(bempty + 8 * s, 8); }
    mbar_init(bempty + 8 * NST, 1);
    asm volatile("fence.mbarrier_init.release.cluster;" ::: "memory");
    fence_async();
    mbar_expect(bempty + 8 * NST, 114688);
    for (int i = 0; i < 7; i++)
      asm volatile("cp.async.bulk.tensor.2d.shared::cluster.global.mbarrier::complete_tx::bytes [%0], [%1, {%3, %4}], [%2];"
                   ::"r"(sb + 2 * STAGE + i * 16384), "l"(&mX), "r"(bempty + 8 * NST), "r"(64 * i), "r"(128 * t) : "memory");
  }
  __syncthreads();
  if (warp >= 8) {
    asm volatile("setmaxnreg.dec.sync.aligned.u32 24;");
    auto issue = [&](int i, int s) {
      const uint32_t dst = sb + s * STAGE, bar = bfull + 8 * s;
      mbar_expect(bar, STAGE);
#pragma unroll 1
      for (int rk = 0; rk < 2; rk++)
      if (i < 4) tma2d(dst + rk * 14336, &mQKV, 448 + 448 * rk + 56 * c, 112 * i, bar);
      else if (i < 8) tma2d(dst + rk * 14336, i < 6 ? &mQKV : &mWO, (i < 6 ? 56 : 64) * c, 224 * (i & 1) + 112 * rk, bar);
      else if (i < 15) { const int k0 = 64 * ((i - 8 + c) % 7) + 32 * rk;
        tma3d(dst + rk * 12288, &mW1, 0, k0, 3 * c, bar); tma2d(dst + 24576 + rk * 2048, &mW1b, 1536 + 32 * c, k0, bar); }
      else { tma2d(dst + rk * 12288, &mW2, 64 * (i - 15), 192 * c + 96 * rk, bar); tma2d(dst + 24576 + rk * 2048, &mW2b, 64 * (i - 15), 1536 + 32 * c + 16 * rk, bar); }
    };
    auto colsum = [&](int job) {
        const int ld4 = job < 112 ? 448 : 336;
        const uint2* wp = (job < 112 ? (const uint2*)w1 + job * 4 : (const uint2*)wqkv + (job - 112) * 4) + (lane >> 2) * ld4 + (lane & 3);
        float s0 = 0.f, s1 = 0.f, s2 = 0.f, s3 = 0.f;
#pragma unroll 8
        for (int i = 0; i < 56; i++) { const uint2 v = __ldg(wp + i * 8 * ld4); s0 += blo(v.x); s1 += bhi(v.x); s2 += blo(v.y); s3 += bhi(v.y); }
#pragma unroll 1
        for (int o = 4; o < 32; o <<= 1) { s0 += __shfl_xor_sync(~0u, s0, o); s1 += __shfl_xor_sync(~0u, s1, o); s2 += __shfl_xor_sync(~0u, s2, o); s3 += __shfl_xor_sync(~0u, s3, o); }
        if (lane < 4) stll(g_CS + job * 4 + lane, tg(__float_as_uint(s0), 1), __float_as_uint(s1), __float_as_uint(s2), __float_as_uint(s3));
      };
    if (warp == 8) {
#pragma unroll 1
      for (int n = 0; n < 44; n++) {
        const int L = n >= 22, i = L ? (n < 28 ? (n - 18) % 6 : n - 22) : n, s = i % 6;
        if (n == 2) asm volatile("bar.sync 2, 288;" ::: "memory");
        mbar_wait(bempty + 8 * s, (i / 6 + (s >= 4 ? L : 0) + 1) & 1);
        if (n == 22) {
          uint32_t v = 0;
#pragma unroll 1
          for (int it = 0; it < SPIN && v < 32; it++) asm volatile("ld.acquire.gpu.global.u32 %0, [%1];" : "=r"(v) : "l"(g_WQF + c) : "memory");
          asm volatile("fence.proxy.async.global;" ::: "memory");
        }
        if (lane == 0) {
          if (n >= 22 && n < 28) {
            mbar_expect(bfull + 8 * s, STAGE);
            asm volatile("cp.async.bulk.shared::cluster.global.mbarrier::complete_tx::bytes [%0], [%1], %2, [%3];"
                         ::"r"(sb + s * STAGE), "l"(g_WQ + c * 10752 + i * (STAGE / 16)), "r"(STAGE), "r"(bfull + 8 * s) : "memory");
          } else issue(i, s);
        }
        __syncwarp();
      }
    } else if (warp == 9) {
      mbar_wait(bfull + 8 * 3, 0);
      if (lane == 0) {
        l2pf((const uint8_t*)wo + blockIdx.x * 3136, 3136);
        l2pf((const uint8_t*)w1 + blockIdx.x * 12544, 12544);
        l2pf((const uint8_t*)w2 + blockIdx.x * 12544, 12544);
      }
      if (blockIdx.x < 112) colsum(blockIdx.x);
      asm volatile("bar.sync 6, 96;" ::: "memory");
#pragma unroll 1
      for (int i = 0; i < 4; i++) {
        const int e = lane < 28 ? lane + 28 * (i & 1) : 0;
        const bool ok = i < 2 || (e < 48 && (e & 15) < 14);
        const int e4 = i < 2 ? (e < 48 ? 48 * c + e : 336 + 8 * c + e) : ok ? 448 + 112 * (e >> 4) + 14 * c + (e & 15) : 448;
        uint4 cv[1];
        ll_issue<0, 1>(cv, g_CS + e4, 0); ll_check<0, 1, false>(cv, g_CS + e4, 0, 1u);
        const uint2 bb = __ldg((const uint2*)b1 + (i < 2 ? e4 : 0));
        const uint32_t h0 = pack(__uint_as_float(cv[0].x), __uint_as_float(cv[0].y)), h1 = pack(__uint_as_float(cv[0].z), __uint_as_float(cv[0].w));
        const uint32_t l0 = pack(__uint_as_float(cv[0].x) - blo(h0), __uint_as_float(cv[0].y) - bhi(h0)), l1 = pack(__uint_as_float(cv[0].z) - blo(h1), __uint_as_float(cv[0].w) - bhi(h1));
#pragma unroll 1
        for (int j = 0; j < (i < 2 ? 5 : 3); j++) {
          const int r = i < 2 ? j : j + 5;
          const uint32_t ad = sb + OFF_CB + (e >> 3) * 512 + r * 64 + ((((e >> 1) ^ (r >> 1)) & 3) << 4) + (e & 1) * 8;
          sts32(ad, j < 2 ? h0 : j == 2 ? l0 : bb.x); sts32(ad + 4, j < 2 ? h1 : j == 2 ? l1 : bb.y);
        }
        if (i & 1) { fence_async(); if (i == 1) asm volatile("bar.arrive 4, 288;" ::: "memory"); else asm volatile("bar.arrive 8, 160; bar.arrive 9, 160;" ::: "memory"); }
      }
    } else if (warp >= 10) {
      const int h = warp - 10;
      uint4 wv[4];
#pragma unroll
      for (int i = 0; i < 4; i++) wv[i] = __ldg((const uint4*)wphi + (2 * c + h) * 98 + min(lane + 32 * i, 97));
#pragma unroll 1
      for (int e = h * 32 + lane; e < 672; e += 64) sts128(sb + OFF_WPHI + e * 16, 0, 0, 0, 0);
      asm volatile("bar.arrive 6, 96;" ::: "memory");
      asm volatile("bar.sync 5, 64;" ::: "memory");
#pragma unroll
      for (int i = 0; i < 4; i++) sts128(sb + OFF_V + h * 2048 + (lane + 32 * i) * 16, wv[i].x, wv[i].y, wv[i].z, wv[i].w);
      __syncwarp();
#pragma unroll 1
      for (int e = lane; e < 392; e += 32) {
        const int d = e / 14, f2 = 2 * (e - 14 * d), k = 28 * h + d;
        const uint32_t v = *(volatile uint32_t*)(sm + OFF_V + h * 2048 + e * 4);
        if (f2 < 24) sts32(sb + OFF_WPHI + sw128(k, 32 * h + f2), v);
        else { sts16(sb + OFF_WPHI + sw128(k, 2 * f2 - 24 + h), v); sts16(sb + OFF_WPHI + sw128(k, 2 * f2 - 22 + h), v >> 16); }
      }
      fence_async();
      asm volatile("bar.arrive 3, 320;" ::: "memory");
      mbar_wait(bfull + 8 * 5, 0);
#pragma unroll 2
      for (int e = t * 672 + h * 32 + lane; e < t * 672 + 672; e += 64) {
        const int r = e >> 3, st = r / 224, rr = r - st * 224, ch = (e & 7) ^ (rr & 7);
        const int k = st < 4 ? 112 * st + (rr >= 112 ? rr - 112 : rr) : 224 * (st - 4) + rr, col = (st < 4 ? (rr >= 112 ? 896 : 448) : 0) + 56 * c + 8 * ch;
        g_WQ[c * 10752 + e] = ch < 7 ? __ldg((const uint4*)(wqkv + k * 1344 + col)) : make_uint4(0, 0, 0, 0);
      }
      __syncwarp();
      if (lane == 0) asm volatile("red.release.gpu.global.add.u32 [%0], 1;" ::"l"(g_WQF + c) : "memory");
      if (h == 0 && blockIdx.x < 84) colsum(112 + blockIdx.x);
    }
  } else {
  asm volatile("setmaxnreg.inc.sync.aligned.u32 240;");

  const int wg = warp >> 2, g = lane >> 2, q = lane & 3;
  const int row0 = warp * 16 + g;
#define PTRS const int ln_ = laneid(); \
  uint4* const fm = g_F + ((t * 8 + warp) * 28) * 32 + ln_;            \
  uint4* const fr = g_F + ((t * 8 + c) * 28 + warp) * 32 + ln_;        \
  uint4* const sf = fm + (7 * (c >> 1) + 4 * (c & 1)) * 32;             \
  uint2* const f2 = (uint2*)(fm - ln_) + ln_;                           \
  uint2* const sh = f2 + (7 * (c >> 1) + 3) * 64 + 32 * (c & 1);        \
  uint32_t* const hme = g_H + (t * 8 + warp) * 8 + c; \
  const uint32_t* const hrow = g_H + (t * 8 + warp) * 8 + (ln_ & 7); \
  (void)fm; (void)fr; (void)sf; (void)f2; (void)sh; (void)hme; (void)hrow;
  float* sLN = (float*)(sm + OFF_V);
  const uint32_t sPK = sb + OFF_PHIK, sV = sb + OFF_V, d16 = (sb & 0x3FFFF) >> 4;
    uint32_t xw[4][4];
#pragma unroll
  for (int i = 0; i < 16; i++) xw[i >> 2][i & 3] = 0;
#define ACQ(I) (mbar_wait(bfull + 8 * ((I) % 6), ((I) / 6 + ((I) % 6 >= 4 ? L : 0)) & 1), d16 + ((I) % 6) * (STAGE >> 4))
#define REL(I) { if (lane == 0) mbar_arrive(bempty + 8 * ((I) % 6)); }
#define RISSUE(m, P, XA, XB, BA, BB) { ll_issue<0, 8>(P, pr + (m) * 256, 896); \
      { const uint4 v_ = ldll(fr + X1 + (m) * 256); XA = make_uint2(v_.x, v_.y); XB = make_uint2(v_.z, v_.w); } \
      const uint32_t* bp = (const uint32_t*)(b2 + 128 * (m) + 16 * warp) + (ln_ & 3); BA = __ldg(bp); BB = __ldg(bp + 4); }
#define REDU(m, P, XA, XB, BA, BB) { ll_check<0, 8, false>(P, pr + (m) * 256, 896, ptag); \
      float e[8] = {blo(XA.x) + blo(BA), bhi(XA.x) + bhi(BA), blo(XA.y) + blo(BA), bhi(XA.y) + bhi(BA), blo(XB.x) + blo(BB), bhi(XB.x) + bhi(BB), blo(XB.y) + blo(BB), bhi(XB.y) + bhi(BB)}; \
      _Pragma("unroll") for (int i = 0; i < 8; i++) { e[0] += blo(P[i].x); e[1] += bhi(P[i].x); e[2] += blo(P[i].y); e[3] += bhi(P[i].y); \
        e[4] += blo(P[i].z); e[5] += bhi(P[i].z); e[6] += blo(P[i].w); e[7] += bhi(P[i].w); } \
      xw[m][0] = pack(e[0], e[1]); xw[m][1] = pack(e[2], e[3]); xw[m][2] = pack(e[4], e[5]); xw[m][3] = pack(e[6], e[7]); }
#define RPUB(m) stll(fr + XR + (m) * 256, tg(xw[m][0], 0), xw[m][1], xw[m][2], xw[m][3]);
#define RLAST(ptag_) { const uint32_t ptag = ptag_; const uint4* pr = g_P + ((t * 8 + c) * 8 * 28 + warp) * 32 + ln_; uint4 p[8]; uint2 xa, xb; uint32_t ba, bb; \
      if (ptag_) probe_wait(pr - ln_ + 31 + 3 * 256 + (ln_ & 7) * 896, ptag); RISSUE(3, p, xa, xb, ba, bb) REDU(3, p, xa, xb, ba, bb) }
#pragma unroll 1
  for (int L = 0; L < 2; L++) {
    const uint32_t tag = 1 - L;
    uint32_t phq[2][2][7];
    const uint32_t hs = 10 * L;
    {
      PTRS
      uint4 a[28];
      const uint4* pa = fm + XR;
      uint32_t fa = 0, fb = 0;
      float r0 = 1.f, r1 = 1.f;
      if (L == 0) {
        hint_post(hme, 1, lane);
        mbar_wait(bempty + 8 * NST, 0);
        MARK(1);
        const int row = warp * 16 + (ln_ & 15);
        const uint32_t xb = sb + 2 * STAGE + row * 128;
        float cs_[4][4] = {};
#pragma unroll
        for (int ks = 0; ks < 28; ks++) { a[ks] = ldsm4(xb + (ks >> 2) * 16384 + (((2 * (ks & 3) + (ln_ >> 4)) ^ (row & 7)) << 4)); mma16816(cs_[ks & 3], a[ks], 0x3F803F80u, 0x3F803F80u); }
        if (c < 7) {
#pragma unroll
          for (int u = 0; u < 4; u++) { const uint4 v = ldsm4(xb + c * 16384 + (((2 * u + (ln_ >> 4)) ^ (row & 7)) << 4)); stll(fm + XR + 128 * c + u * 32, tg(v.x, tag), v.y, v.z, v.w); }
        }
        const float m0 = ((cs_[0][0] + cs_[1][0]) + (cs_[2][0] + cs_[3][0])) * (1.f / 448), m1 = ((cs_[0][2] + cs_[1][2]) + (cs_[2][2] + cs_[3][2])) * (1.f / 448);
        const uint32_t mb0 = pack(m0, m0), mb1 = pack(m1, m1);
        asm volatile("bar.arrive 2, 288;" ::"r"(mb0) : "memory");
#pragma unroll
        for (int ks = 0; ks < 28; ks++) {
          a[ks].x = bsub(a[ks].x, mb0); a[ks].y = bsub(a[ks].y, mb1); a[ks].z = bsub(a[ks].z, mb0); a[ks].w = bsub(a[ks].w, mb1);
        }
        r0 = m0 - blo(mb0); r1 = m1 - blo(mb1);
      } else {
        ll_issue<0, 14>(a, pa, 32);
        if (wg == 0) { RLAST(1u) xw[3][0] = tg(xw[3][0], 0); RPUB(3) } else { xw[3][0] = xw[3][1] = xw[3][2] = xw[3][3] = 0; }
        MARK(20);
        ll_issue<14, 7>(a, pa, 32);
        ln_stats(xw, sLN, warp, lane, g_S2 + (t * 8 + c) * 8);
      }
      MARK(2 + L * 19);
      float ak[28], av[28], aq[28], pp[28];
#define KVSTAGE(i) { if (L) ll_check<7 * i, 7, false>(a, pa, 32, tag); const uint32_t st = ACQ(i); wg_fence(); \
      _Pragma("unroll") for (int ks = 0; ks < 7; ks++) { const uint4 f = a[7 * i + ks]; \
        wgmma_rs56(ak, f.x, f.y, f.z, f.w, mkdesc(st, ks * 2048, 1024, 1024, 1), i | ks); \
        wgmma_rs56(av, f.x, f.y, f.z, f.w, mkdesc(st, 14336 + ks * 2048, 1024, 1024, 1), i | ks); } \
      wg_commit(); if (i > 0) { wg_wait<1>(); REL(i + 5) } }
      KVSTAGE(0) KVSTAGE(1)
      uint4 sv[1] = {make_uint4(0, 0, 0, 0)};
      const uint4* ps = g_S2 + (t * 8 + warp) * 8 + (ln_ >> 2);
      if (L) { ll_issue<21, 7>(a, pa, 32); ll_issue<0, 1>(sv, ps, 0); }
      else {
        float c0[2][4] = {}, c1[2][4] = {};
#pragma unroll
        for (int ks = 0; ks < 28; ks++) { mma16816(c0[ks & 1], a[ks], a[ks].x, a[ks].z); mma16816(c1[ks & 1], a[ks], a[ks].y, a[ks].w); }
        const int src = (ln_ & 28) | (g >> 1);
        const float q0 = __shfl_sync(~0u, (g & 1) ? c0[0][1] + c0[1][1] : c0[0][0] + c0[1][0], src), q1 = __shfl_sync(~0u, (g & 1) ? c1[0][3] + c1[1][3] : c1[0][2] + c1[1][2], src);
        r0 = rsqrtf(fmaxf(q0 * (1.f / 448) - r0 * r0, 0.f) + 1e-5f); r1 = rsqrtf(fmaxf(q1 * (1.f / 448) - r1 * r1, 0.f) + 1e-5f);
      }
      KVSTAGE(2) KVSTAGE(3)
      if (L) {
        if (wg) asm volatile("bar.sync 9, 160;" ::: "memory"); else asm volatile("bar.sync 8, 160;" ::: "memory");
        ll_check<0, 1, false>(sv, ps, 0, 1u);
        const float m0 = -__uint_as_float(sv[0].x), m1 = -__uint_as_float(sv[0].z), h0 = blo(pack(m0, 0.f)), h1 = blo(pack(m1, 0.f));
        r0 = __uint_as_float(sv[0].y); r1 = __uint_as_float(sv[0].w);
        fa = q == 2 ? pack(0.f, h0) : q == 3 ? pack(m0 - h0, h0) : 0u; fb = q == 2 ? pack(0.f, h1) : q == 3 ? pack(m1 - h1, h1) : 0u;
      } else {
        asm volatile("bar.sync 3, 320;" ::: "memory");
      }
      wg_fence();
      wgmma_rs56(ak, fa, fb, 0u, 0u, mkdesc(d16, OFF_CB + 1024, 512, 0, 2), 1);
      wgmma_rs56(av, fa, fb, 0u, 0u, mkdesc(d16, OFF_CB + 2048, 512, 0, 2), 1);
      wg_commit();
      wg_wait<0>(); REL(3) regfence(ak); regfence(av);
      MARK(3 + L * 19);
      bulk_wait_read<0>(lane);
      phi_gemm(ak, pp, d16 + (OFF_WPHI >> 4), r0, r1);
#pragma unroll
      for (int j = 0; j < 7; j++) {
        const int n = 8 * j + 2 * q, n2 = n < 28 ? n : n + 4;
        sts32(sV + sw128(row0, n2), pack(av[4 * j] * r0, av[4 * j + 1] * r0)); sts32(sV + sw128(row0 + 8, n2), pack(av[4 * j + 2] * r1, av[4 * j + 3] * r1));
      }
      { const int n2 = 28 + 2 * (q & 1) + 32 * (q >> 1); const uint32_t v = (q & 1) ? 0u : 0x3F80u; sts32(sV + sw128(row0, n2), v); sts32(sV + sw128(row0 + 8, n2), v); }
      wg_wait<0>(); regfence(pp);
      hedgehog(pp, [&](int r, int h, int p, uint32_t v) { sts32(sPK + h * 16384 + sw128(row0 + 8 * r, 8 * p + 2 * q), v); }, [] {});
#pragma unroll
      for (int i = 0; i < 4; i++) sts32(sPK + (i & 1) * 16384 + sw128(row0 + 8 * (i >> 1), 56 + 2 * q), 0u);
      fence_async();
      bar_cons();
      MARK(4 + L * 19);
      float kv[16];
      wg_fence();
#pragma unroll
      for (int ks = 0; ks < 8; ks++) wgmma_ss32(kv, mkdesc(d16 + wg * 1024, OFF_PHIK + ks * 2048, 1024, 1024, 1), mkdesc(d16 + wg * 4, OFF_V + ks * 2048, 1024, 1024, 1), ks);
      wg_commit(); wg_wait<0>(); regfence(kv);
      const int ln2 = laneid();
#pragma unroll
      for (int u = 0; u < 4; u++) {
        float e[4];
#pragma unroll
        for (int i = 0; i < 4; i++) e[i] = kv[4 * u + i];
        stll(g_KVP + (c * 16 + t) * 1024 + wg * 512 + u * 128 + (warp & 3) * 32 + ln2, tg(__float_as_uint(e[0]), tag), __float_as_uint(e[1]), __float_as_uint(e[2]), __float_as_uint(e[3]));
      }
      MARK(5 + L * 19);
      uint4 k4[4];
      const uint4* pk = g_KVP + (c * 16 + 4 * (ln2 & 3)) * 1024 + 64 * t + warp * 8 + (ln2 >> 2);
#pragma unroll
      for (int i = 0; i < 2; i++) {
        const uint32_t st = ACQ(4 + i); wg_fence();
#pragma unroll
        for (int ks = 0; ks < 14; ks++) { const uint4 f = a[14 * i + ks]; wgmma_rs56(aq, f.x, f.y, f.z, f.w, mkdesc(st, ks * 2048, 1024, 1024, 1), i | ks); }
        if (i == 1) wgmma_rs56(aq, fa, fb, 0u, 0u, mkdesc(d16, OFF_CB, 512, 0, 2), 1);
        wg_commit();
        if (i == 1) ll_issue<0, 4>(k4, pk, 1024);
      }
      ll_check<0, 4, false>(k4, pk, 1024, tag);
      float s0 = 0, s1 = 0, s2 = 0, s3 = 0;
#pragma unroll
      for (int i = 0; i < 4; i++) { s0 += __uint_as_float(k4[i].x); s1 += __uint_as_float(k4[i].y); s2 += __uint_as_float(k4[i].z); s3 += __uint_as_float(k4[i].w); }
      s0 = qsum(s0); s1 = qsum(s1); s2 = qsum(s2); s3 = qsum(s3);
      if (q == 0) stll2(g_KVR + c * 1024 + 64 * t + warp * 8 + (ln2 >> 2), tg(pack(s0, s1), tag), pack(s2, s3));
      MARK(6 + L * 19);
      wg_wait<0>(); REL(4) REL(5) regfence(aq);
      phi_gemm(aq, pp, d16 + (OFF_WPHI >> 4), r0, r1);
      bar_cons();
#pragma unroll
      for (int i = 0; i < 4; i++) sts128(sV + warp * 2048 + (lane + i * 32) * 16, 0, 0, 0, 0);
      wg_wait<0>(); regfence(pp);
      uint2 r[4];
      const uint2* pr = g_KVR + c * 1024 + wg * 512 + (warp & 3) * 32 + ln2;
      hedgehog(pp, [&](int r, int h, int p, uint32_t v) { phq[r][h][p] = v; }, [&] {
#pragma unroll
        for (int u = 0; u < 4; u++) r[u] = ldll2(pr + u * 128); });
      MARK(7 + L * 19);
#pragma unroll 1
      for (int it = 0; it < SPIN; it++) {
        if (!__any_sync(~0u, ((r[0].x ^ tag) | (r[1].x ^ tag) | (r[2].x ^ tag) | (r[3].x ^ tag)) & 1)) break;
#pragma unroll
        for (int u = 0; u < 4; u++) r[u] = ldll2(pr + u * 128);
      }
#pragma unroll
      for (int u = 0; u < 4; u++) {
        const int d = 8 * u + 2 * q;
        if (d < 28) { sts32(sV + sw128(row0, 28 * wg + d), r[u].x); sts32(sV + sw128(row0 + 8, 28 * wg + d), r[u].y); }
        else if (d == 28) {
#pragma unroll
          for (int j = 0; j < 4; j++) { sts16(sV + sw128(row0, 56 + 2 * j + wg), r[u].x); sts16(sV + sw128(row0 + 8, 56 + 2 * j + wg), r[u].y); }
        }
      }
      fence_async();
      bar_cons();
      MARK(8 + L * 19);
      float o[32];
      wg_fence();
#pragma unroll
      for (int ks = 0; ks < 8; ks++) {
        const int h = ks >> 2, p = 2 * (ks & 3);
        wgmma_rs64(o, phq[0][h][p], phq[1][h][p], p < 6 ? phq[0][h][p < 6 ? p + 1 : 0] : 0u, p < 6 ? phq[1][h][p < 6 ? p + 1 : 0] : 0u, mkdesc(d16, OFF_V + ks * 2048, 1024, 1024, 1), ks);
      }
      wg_commit(); wg_wait<0>(); regfence(o);
      const float iA0 = rcp(o[28] + 1e-6f), iB0 = rcp(o[29] + 1e-6f), iA1 = rcp(o[30] + 1e-6f), iB1 = rcp(o[31] + 1e-6f);
      uint32_t w[14];
      { PTRS
#pragma unroll
      for (int j = 0; j < 7; j++) {
        const bool hb = 8 * j + 2 * q >= 28; const float i0 = hb ? iB0 : iA0, i1 = hb ? iB1 : iA1;
        w[2 * j] = pack(o[4 * j] * i0, o[4 * j + 1] * i0); w[2 * j + 1] = pack(o[4 * j + 2] * i1, o[4 * j + 3] * i1);
        if (j == 0 || ((j ^ c) & 1) == 0) w[2 * j] = tg(w[2 * j], tag);
      }
      slice_store(sf + OO, sh + 2 * OO, w, c & 1);
      hint_post(hme, hs + 2, lane); }
    }
    MARK(9 + L * 19);
    uint4 xr[4];
    if (c < 7) {
      PTRS
      ll_issue<0, 4>(xr, fm + XR + 128 * c, 32);
      uint4 a[28];
      const uint4* pa = fm + OO;
      hint_wait(hrow, hs + 2);
      MARK(10 + L * 19);
      ll_issue<0, 28, true>(a, pa, 32, f2 + 2 * OO);
      float y[32];
      uint32_t st;
#define WOSTEP(i) { ll_check<7 * i, 7, true>(a, pa, 32, tag, f2 + 2 * OO); if (!(i & 1)) st = ACQ(6 + i / 2); wg_fence(); \
      _Pragma("unroll") for (int ks = 0; ks < 7; ks++) { const uint4 f = a[7 * i + ks]; \
        wgmma_rs64(y, f.x, f.y, f.z, f.w, mkdesc(st, ((i & 1) * 7 + ks) * 2048, 1024, 1024, 1), i | ks); } wg_commit(); }
      WOSTEP(0) WOSTEP(1) WOSTEP(2) WOSTEP(3)
      ll_check<0, 4, false>(xr, fm + XR + 128 * c, 32, tag);
      wg_wait<0>(); regfence(y);
      MARK(11 + L * 19);
#pragma unroll
      for (int u = 0; u < 4; u++) {
        xr[u].x = tg(pack(blo(xr[u].x) + y[8 * u], bhi(xr[u].x) + y[8 * u + 1]), tag); xr[u].y = pack(blo(xr[u].y) + y[8 * u + 2], bhi(xr[u].y) + y[8 * u + 3]);
        xr[u].z = pack(blo(xr[u].z) + y[8 * u + 4], bhi(xr[u].z) + y[8 * u + 5]); xr[u].w = pack(blo(xr[u].w) + y[8 * u + 6], bhi(xr[u].w) + y[8 * u + 7]);
        stll(fm + X1 + 128 * c + u * 32, xr[u].x, xr[u].y, xr[u].z, xr[u].w);
      }
      hint_post(hme, hs + 3, lane);
    } else {
      PTRS
      hint_post(hme, hs + 3, lane);
      (void)ACQ(6); (void)ACQ(7);
      hint_wait(hrow, hs + 3);
      ll_issue<0, 4>(xr, fm + X1, 32);
      MARK(10 + L * 19); MARK(11 + L * 19);
    }
    uint32_t hf[56];
    float rr0, rr1;
    {
      PTRS
      uint4 a[28];
      const uint4* pa = fm + X1;
      auto grp = [&](int i) -> const uint4* { const int k = i + c; return pa + ((k >= 7 ? k - 7 : k) - i) * 128; };
      if (c == 7) { ll_issue<4, 12>(a, pa, 32); ll_check<0, 4, false>(xr, pa, 32, tag); }
      else {
#pragma unroll
        for (int u = 4; u < 16; u++) a[u] = make_uint4(0, 0, 0, 0);
      }
#pragma unroll
      for (int u = 0; u < 4; u++) a[u] = xr[u];
      float y[96], z[16];
#define F1STAGE(i) { if (i > 0) ll_check<4 * i, 4, false>(a, grp(i), 32, tag); const uint32_t st = ACQ(8 + i); wg_fence(); \
      _Pragma("unroll") for (int ks = 0; ks < 4; ks++) { const uint4 f = a[4 * i + ks]; \
        wgmma_rs192(y, f.x, f.y, f.z, f.w, mkdesc(st, (ks >> 1) * 12288 + (ks & 1) * 2048, 4096, 1024, 1), i | ks); \
        wgmma_rs32(z, f.x, f.y, f.z, f.w, mkdesc(st, 24576 + ks * 1024, 512, 512, 2), i | ks); } \
      wg_commit(); if (i > 0) { wg_wait<1>(); REL(6 + i) if (i < 4) ll_issue<(i < 4 ? 4 * i + 12 : 0), 4>(a, grp(i + 3), 32); } }
      F1STAGE(0)
      MARK(12 + L * 19);
      if (c < 7) {
        hint_wait(hrow, hs + 3);
        ll_issue<4, 4>(a, grp(1), 32); ll_issue<8, 4>(a, grp(2), 32); ll_issue<12, 4>(a, grp(3), 32);
        float s0 = 0.f, s1 = 0.f, v0 = 0.f, v1 = 0.f;
#pragma unroll
        for (int u = 0; u < 4; u++) { s0 += (blo(xr[u].x) + bhi(xr[u].x)) + (blo(xr[u].z) + bhi(xr[u].z)); s1 += (blo(xr[u].y) + bhi(xr[u].y)) + (blo(xr[u].w) + bhi(xr[u].w)); }
        s0 = qsum(s0) * (1.f / 64); s1 = qsum(s1) * (1.f / 64);
#pragma unroll
        for (int u = 0; u < 4; u++) {
          const float d0 = blo(xr[u].x) - s0, d1 = bhi(xr[u].x) - s0, d2 = blo(xr[u].z) - s0, d3 = bhi(xr[u].z) - s0;
          const float d4 = blo(xr[u].y) - s1, d5 = bhi(xr[u].y) - s1, d6 = blo(xr[u].w) - s1, d7 = bhi(xr[u].w) - s1;
          v0 += (d0 * d0 + d1 * d1) + (d2 * d2 + d3 * d3); v1 += (d4 * d4 + d5 * d5) + (d6 * d6 + d7 * d7);
        }
        v0 = qsum(v0); v1 = qsum(v1);
        if (q == 0) stll(g_ST + ((t * 8 + warp) * 8 + c) * 8 + (ln_ >> 2), tg(__float_as_uint(s0), tag), __float_as_uint(v0), __float_as_uint(s1), __float_as_uint(v1));
      }
      REL(6)
      F1STAGE(1) MARK(13 + L * 19); F1STAGE(2) F1STAGE(3)
      uint4 sv[2];
      const uint4* ps = g_ST + ((t * 8 + warp) * 8 + 2 * (laneid() & 3)) * 8 + (laneid() >> 2);
      ll_issue<0, 2>(sv, ps, q < 3 ? 8 : 0);
      F1STAGE(4)
      ll_check<0, 2, false>(sv, ps, q < 3 ? 8 : 0, tag);
      const float wb = q < 3 ? 1.f : 0.f;
      const float ma = __uint_as_float(sv[0].x), mb = __uint_as_float(sv[1].x), mc = __uint_as_float(sv[0].z), md = __uint_as_float(sv[1].z);
      const float m0 = qsum(ma + wb * mb) * (1.f / 7), m1 = qsum(mc + wb * md) * (1.f / 7);
      const float v0 = qsum(__uint_as_float(sv[0].y) + 64.f * (ma - m0) * (ma - m0) + wb * (__uint_as_float(sv[1].y) + 64.f * (mb - m0) * (mb - m0)));
      const float v1 = qsum(__uint_as_float(sv[0].w) + 64.f * (mc - m1) * (mc - m1) + wb * (__uint_as_float(sv[1].w) + 64.f * (md - m1) * (md - m1)));
      const float e0 = v0 * (1.f / 448) + 1e-5f, e1 = v1 * (1.f / 448) + 1e-5f;
      rr0 = 1.f / e0; rr1 = 1.f / e1;
      auto fold = [&](float m, float sd) -> uint32_t {
        const float mh = blo(pack(-m, 0.f)), sh_ = blo(pack(sd, 0.f));
        return q == 0 ? pack(mh, -m - mh) : q == 1 ? pack(mh, sh_) : q == 2 ? pack(sd - sh_, 0.f) : 0u;
      };
      const uint32_t fa = fold(m0, sqrtf(e0)), fb = fold(m1, sqrtf(e1));
      if (L == 0) asm volatile("bar.sync 4, 288;" ::: "memory");
      wg_fence();
      wgmma_rs192(y, fa, fb, 0u, 0u, mkdesc(d16, OFF_CB, 512, 0, 2), 1);
      wgmma_rs32(z, fa, fb, 0u, 0u, mkdesc(d16, OFF_CB + 3072, 512, 0, 2), 1);
      F1STAGE(5) F1STAGE(6)
      wg_wait<0>(); REL(13) REL(14) regfence(y); regfence(z);
      MARK(14 + L * 19);
#pragma unroll
      for (int j = 0; j < 56; j++) {
        uint32_t r; asm("cvt.rn.relu.bf16x2.f32 %0, %1, %2;" : "=r"(r) : "f"(j < 48 ? y[j < 48 ? 2 * j + 1 : 0] : z[j < 48 ? 0 : 2 * j - 95]), "f"(j < 48 ? y[j < 48 ? 2 * j : 0] : z[j < 48 ? 0 : 2 * j - 96]));
        asm("mul.bf16x2 %0, %1, %1;" : "=r"(hf[j]) : "r"(r));
      }
    }
    MARK(15 + L * 19);
    {
      PTRS
      float ya[32], yb[32];
      uint4* pp = g_P + ((t * 8 + warp) * 8 + c) * 28 * 32 + ln_;
#define F2STORE(j, Y) { regfence(Y); if ((j) >= 3) bulk_wait_read<2>(lane); \
      const uint32_t bf = sPK + (((j) + 1) % 3) * 16384 + warp * 2048; \
      _Pragma("unroll") for (int u = 0; u < 4; u++) \
      sts128(bf + u * 512 + ln_ * 16, tg(pack(Y[8 * u] * rr0, Y[8 * u + 1] * rr0), tag), pack(Y[8 * u + 2] * rr1, Y[8 * u + 3] * rr1), \
             pack(Y[8 * u + 4] * rr0, Y[8 * u + 5] * rr0), pack(Y[8 * u + 6] * rr1, Y[8 * u + 7] * rr1)); \
      fence_async(); __syncwarp(); \
      if (lane == 0) asm volatile("cp.async.bulk.global.shared::cta.bulk_group [%0], [%1], 2048; cp.async.bulk.commit_group;" ::"l"(pp + (j) * 128), "r"(bf) : "memory"); }
#define F2PASS(j, Y, Z) { const uint32_t st = ACQ(15 + j); wg_fence(); \
      _Pragma("unroll") for (int ks = 0; ks < 14; ks++) wgmma_rs64(Y, hf[4 * ks], hf[4 * ks + 1], hf[4 * ks + 2], hf[4 * ks + 3], mkdesc(st, ks * 2048, 1024, 1024, 1), ks); \
      wg_commit(); if (j > 0) { wg_wait<1>(); REL(14 + j) F2STORE(j - 1, Z) } }
      const uint4* pr = g_P + ((t * 8 + c) * 8 * 28 + warp) * 32 + ln_;
      uint4 p[8], p2[8]; uint2 xa, xb, xc, xd; uint32_t ba, bb, bc, bd;
      const uint32_t ptag = tag;
      F2PASS(0, ya, yb) F2PASS(1, yb, ya) F2PASS(2, ya, yb) F2PASS(3, yb, ya)
      F2PASS(4, ya, yb)
      RISSUE(0, p, xa, xb, ba, bb)
      F2PASS(5, yb, ya)
      REDU(0, p, xa, xb, ba, bb)
      if (L == 0) { xw[0][0] = tg(xw[0][0], 0); RPUB(0) }
      F2PASS(6, ya, yb)
      RISSUE(1, p, xa, xb, ba, bb)
      wg_wait<0>(); REL(21) F2STORE(6, ya)
      MARK(16 + L * 19);
      if (L == 0) { bulk_wait_read<2>(lane); bar_cons(); }
      if (wg) probe_wait(pr - ln_ + 31 + 2 * 256 + (ln_ & 7) * 896, tag);
      RISSUE(2, p2, xc, xd, bc, bd)
      REDU(1, p, xa, xb, ba, bb)
      if (L == 0) { xw[1][0] = tg(xw[1][0], 0); RPUB(1) }
      MARK(17 + L * 19);
      REDU(2, p2, xc, xd, bc, bd)
      if (L == 0) { xw[2][0] = tg(xw[2][0], 0); RPUB(2) }
    }
    MARK(18 + L * 19);
  }
  {
    PTRS
    uint32_t* op = (uint32_t*)(out + XOFF(ln_));
#define OUT(u) { op[u * 64] = xw[u][0]; op[u * 64 + 1792] = xw[u][1]; op[u * 64 + 4] = xw[u][2]; op[u * 64 + 1796] = xw[u][3]; }
    OUT(0) OUT(1) OUT(2)
    if (wg == 0) { RLAST(0u) OUT(3) }
    else if (warp == 7) {
      if (t == 0 && lane == 0) g_WQF[c] = 0;
      if (lane < 8) stll(g_S2 + (t * 8 + c) * 8 + lane, 0, 0, 0, 0);
      if (lane < 4) { stll(g_CS + blockIdx.x * 4 + lane, 0, 0, 0, 0); if (blockIdx.x < 68) stll(g_CS + 512 + blockIdx.x * 4 + lane, 0, 0, 0, 0); }
    }
  }
  if (lane == 0) asm volatile("cp.async.bulk.wait_group 0;" ::: "memory");
  MARK(38); GT(39);
  }
}

typedef CUresult (*EncFn)(CUtensorMap*, CUtensorMapDataType, cuuint32_t, void*, const cuuint64_t*, const cuuint64_t*, const cuuint32_t*, const cuuint32_t*,
                          CUtensorMapInterleave, CUtensorMapSwizzle, CUtensorMapL2promotion, CUtensorMapFloatOOBfill);

extern "C" void kernel_launch(void* const* d_in, const int* in_sizes, int n_in, void* d_out, int out_size) {
  static EncFn enc = nullptr;
  if (!enc) {
    void* fn = nullptr; cudaDriverEntryPointQueryResult qr;
    cudaGetDriverEntryPoint("cuTensorMapEncodeTiled", &fn, cudaEnableDefault, &qr);
    enc = (EncFn)fn;
    cudaFuncSetAttribute(fused_kernel, cudaFuncAttributeMaxDynamicSharedMemorySize, SMEM_BYTES);
  }
  CUtensorMap mQKV, mWO, mW1, mW1b, mW2, mW2b, mX;
  const cuuint32_t es[3] = {1, 1, 1};
  auto enc2 = [&](CUtensorMap* m, void* p, cuuint64_t cols, cuuint64_t rows, cuuint32_t bc, cuuint32_t br) {
    const cuuint64_t dims[2] = {cols, rows}, str[1] = {cols * 2}; const cuuint32_t box[2] = {bc, br};
    enc(m, CU_TENSOR_MAP_DATA_TYPE_BFLOAT16, 2, p, dims, str, box, es, CU_TENSOR_MAP_INTERLEAVE_NONE,
        bc == 64 ? CU_TENSOR_MAP_SWIZZLE_128B : CU_TENSOR_MAP_SWIZZLE_64B, CU_TENSOR_MAP_L2_PROMOTION_L2_128B, CU_TENSOR_MAP_FLOAT_OOB_FILL_NONE);
  };
  enc2(&mQKV, d_in[1], 1344, 448, 64, 112); enc2(&mWO, d_in[3], 448, 448, 64, 112); enc2(&mW1b, d_in[5], 1792, 448, 32, 32);
  enc2(&mX, d_in[0], 448, 2048, 64, 128);
  enc2(&mW2, d_in[7], 448, 1792, 64, 96); enc2(&mW2b, d_in[7], 448, 1792, 64, 16);
  {
    const cuuint64_t dims[3] = {64, 448, 28}, str[2] = {3584, 128}; const cuuint32_t box[3] = {64, 32, 3};
    enc(&mW1, CU_TENSOR_MAP_DATA_TYPE_BFLOAT16, 3, d_in[5], dims, str, box, es, CU_TENSOR_MAP_INTERLEAVE_NONE, CU_TENSOR_MAP_SWIZZLE_128B,
        CU_TENSOR_MAP_L2_PROMOTION_L2_128B, CU_TENSOR_MAP_FLOAT_OOB_FILL_NONE);
  }
  typedef const __nv_bfloat16* BP;
  fused_kernel<<<128, 384, SMEM_BYTES>>>(mQKV, mWO, mW1, mW1b, mW2, mW2b, mX, (BP)d_in[1], (BP)d_in[2], (BP)d_in[3], (BP)d_in[5], (BP)d_in[6], (BP)d_in[7], (BP)d_in[8],
                                         (__nv_bfloat16*)d_out);
}
```

```cpp
#include <cuda_runtime.h>
#include <cuda_bf16.h>
#include <cuda.h>
#include <stdint.h>

constexpr int NST = 6, STAGE = 28672;
constexpr int OFF_PHIK = NST * STAGE;
constexpr int OFF_V = OFF_PHIK + 32768;
constexpr int OFF_WPHI = OFF_V + 16384;
constexpr int OFF_CB = OFF_WPHI + 7168;
constexpr int OFF_BAR = OFF_CB + 3584;
constexpr int SMEM_BYTES = OFF_BAR + 16 * NST + 8;
constexpr int FR = 16 * 8 * 28 * 32;
constexpr int SPIN = 1 << 18;

__device__ uint4 g_F[3 * FR];
constexpr int XR = 0, OO = FR, X1 = 2 * FR;
__device__ uint4 g_P[8 * FR];
__device__ uint4 g_ST[16 * 8 * 8 * 8];
__device__ uint4 g_KVP[8 * 16 * 1024];
__device__ uint2 g_KVR[8 * 1024];
__device__ uint4 g_CS[784];
__device__ uint4 g_S2[16 * 8 * 8];
__device__ uint4 g_WQ[8 * 6 * (STAGE / 16)];
__device__ uint32_t g_WQF[8];
__device__ uint32_t g_H[16 * 8 * 8];
#define MARK(i)
#define GT(i)

__device__ __forceinline__ uint32_t s2u(const void* p) { return (uint32_t)__cvta_generic_to_shared(p); }
__device__ __forceinline__ void mbar_init(uint32_t b, uint32_t c) { asm volatile("mbarrier.init.shared::cta.b64 [%0], %1;" ::"r"(b), "r"(c)); }
__device__ __forceinline__ void mbar_expect(uint32_t b, uint32_t tx) { asm volatile("mbarrier.arrive.expect_tx.shared::cta.b64 _, [%0], %1;" ::"r"(b), "r"(tx) : "memory"); }
__device__ __forceinline__ void mbar_arrive(uint32_t b) { asm volatile("mbarrier.arrive.shared::cta.b64 _, [%0];" ::"r"(b) : "memory"); }
__device__ __forceinline__ void mbar_wait(uint32_t b, uint32_t ph) {
  uint32_t ok = 0;
#pragma unroll 1
  for (int it = 0; it < SPIN && !ok; it++)
    asm volatile("{.reg .pred p; mbarrier.try_wait.parity.shared::cta.b64 p,[%1],%2; selp.u32 %0,1,0,p;}" : "=r"(ok) : "r"(b), "r"(ph) : "memory");
}
__device__ __forceinline__ void tma2d(uint32_t dst, const CUtensorMap* m, int c0, int c1, uint32_t bar) {
  asm volatile("cp.async.bulk.tensor.2d.shared::cluster.global.mbarrier::complete_tx::bytes [%0], [%1, {%3, %4}], [%2];"
               ::"r"(dst), "l"(m), "r"(bar), "r"(c0), "r"(c1) : "memory");
}
__device__ __forceinline__ void tma3d(uint32_t dst, const CUtensorMap* m, int c0, int c1, int c2, uint32_t bar) {
  asm volatile("cp.async.bulk.tensor.3d.shared::cluster.global.mbarrier::complete_tx::bytes [%0], [%1, {%3, %4, %5}], [%2];"
               ::"r"(dst), "l"(m), "r"(bar), "r"(c0), "r"(c1), "r"(c2) : "memory");
}
__device__ __forceinline__ void l2pf(const void* p, uint32_t bytes) { asm volatile("cp.async.bulk.prefetch.L2.global [%0], %1;" ::"l"(p), "r"(bytes) : "memory"); }
__device__ __forceinline__ void wg_fence() { asm volatile("wgmma.fence.sync.aligned;" ::: "memory"); }
__device__ __forceinline__ void wg_commit() { asm volatile("wgmma.commit_group.sync.aligned;" ::: "memory"); }
template <int N> __device__ __forceinline__ void wg_wait() { asm volatile("wgmma.wait_group.sync.aligned %0;" ::"n"(N) : "memory"); }
template <int N> __device__ __forceinline__ void regfence(float (&d)[N]) {
#pragma unroll
  for (int i = 0; i < N; i++) asm volatile("" : "+f"(d[i])::"memory");
}
__device__ __forceinline__ void bar_cons() { asm volatile("bar.sync 1, 256;" ::: "memory"); }
__device__ __forceinline__ void fence_async() { asm volatile("fence.proxy.async.shared::cta;" ::: "memory"); }
struct Desc { uint32_t lo, hi; };
__device__ __forceinline__ Desc mkdesc(uint32_t base16, uint32_t off, uint32_t lbo, uint32_t sbo, uint32_t swz) {
  return Desc{base16 + ((off >> 4) | ((lbo >> 4) << 16)), (sbo >> 4) | (swz << 30)};
}
__device__ __forceinline__ uint4 ldll(const uint4* p) {
  uint4 v; asm volatile("ld.relaxed.gpu.global.v4.u32 {%0,%1,%2,%3}, [%4];" : "=r"(v.x), "=r"(v.y), "=r"(v.z), "=r"(v.w) : "l"(p) : "memory"); return v;
}
__device__ __forceinline__ uint2 ldll2(const uint2* p) {
  uint2 v; asm volatile("ld.relaxed.gpu.global.v2.u32 {%0,%1}, [%2];" : "=r"(v.x), "=r"(v.y) : "l"(p) : "memory"); return v;
}
__device__ __forceinline__ void stll(uint4* p, uint32_t x, uint32_t y, uint32_t z, uint32_t w) {
  asm volatile("st.relaxed.gpu.global.v4.u32 [%0], {%1,%2,%3,%4};" ::"l"(p), "r"(x), "r"(y), "r"(z), "r"(w) : "memory");
}
__device__ __forceinline__ void stll2(void* p, uint32_t x, uint32_t y) {
  asm volatile("st.relaxed.gpu.global.v2.u32 [%0], {%1,%2};" ::"l"(p), "r"(x), "r"(y) : "memory");
}
__device__ __forceinline__ int laneid() { int l; asm volatile("mov.u32 %0, %%laneid;" : "=r"(l)); return l; }
__device__ __forceinline__ uint32_t tg(uint32_t w, uint32_t tag) { return (w & ~1u) | tag; }
__device__ __forceinline__ uint32_t pack(float lo, float hi) {
  uint32_t r; asm("cvt.rn.bf16x2.f32 %0, %1, %2;" : "=r"(r) : "f"(hi), "f"(lo)); return r;
}
__device__ __forceinline__ float blo(uint32_t w) { return __uint_as_float(w << 16); }
__device__ __forceinline__ float bhi(uint32_t w) { return __uint_as_float(w & 0xffff0000u); }
__device__ __forceinline__ float ex2(float x) { float r; asm("ex2.approx.ftz.f32 %0, %1;" : "=f"(r) : "f"(x)); return r; }
__device__ __forceinline__ float rcp(float x) { float r; asm("rcp.approx.ftz.f32 %0, %1;" : "=f"(r) : "f"(x)); return r; }
__device__ __forceinline__ float qsum(float v) { v += __shfl_xor_sync(~0u, v, 1); v += __shfl_xor_sync(~0u, v, 2); return v; }
__device__ __forceinline__ void sts32(uint32_t a, uint32_t v) { asm volatile("st.shared.u32 [%0], %1;" ::"r"(a), "r"(v) : "memory"); }
__device__ __forceinline__ void sts16(uint32_t a, uint32_t v) { asm volatile("st.shared.u16 [%0], %1;" ::"r"(a), "h"((uint16_t)v) : "memory"); }
__device__ __forceinline__ void sts128(uint32_t a, uint32_t x, uint32_t y, uint32_t z, uint32_t w) {
  asm volatile("st.shared.v4.u32 [%0], {%1,%2,%3,%4};" ::"r"(a), "r"(x), "r"(y), "r"(z), "r"(w) : "memory");
}
__device__ __forceinline__ uint32_t sw128(int row, int col) { return row * 128 + ((((col >> 3) ^ row) & 7) << 4) + (col & 7) * 2; }

__device__ __forceinline__ void wgmma_rs56(float (&d)[28], const uint32_t a0, const uint32_t a1, const uint32_t a2, const uint32_t a3, Desc db, int sd) {
  asm volatile("{.reg .pred p; .reg .b64 da, db; setp.ne.b32 p, %33, 0; mov.b64 db, {%32, %34};\n wgmma.mma_async.sync.aligned.m64n56k16.f32.bf16.bf16 {%0,%1,%2,%3,%4,%5,%6,%7,%8,%9,%10,%11,%12,%13,%14,%15,%16,%17,%18,%19,%20,%21,%22,%23,%24,%25,%26,%27}, {%28,%29,%30,%31}, db, p, 1, 1, 1;}"
   : "+f"(d[0]),"+f"(d[1]),"+f"(d[2]),"+f"(d[3]),"+f"(d[4]),"+f"(d[5]),"+f"(d[6]),"+f"(d[7]),"+f"(d[8]),"+f"(d[9]),"+f"(d[10]),"+f"(d[11]),"+f"(d[12]),"+f"(d[13]),"+f"(d[14]),"+f"(d[15]),"+f"(d[16]),"+f"(d[17]),"+f"(d[18]),"+f"(d[19]),"+f"(d[20]),"+f"(d[21]),"+f"(d[22]),"+f"(d[23]),"+f"(d[24]),"+f"(d[25]),"+f"(d[26]),"+f"(d[27])
   : "r"(a0),"r"(a1),"r"(a2),"r"(a3),"r"(db.lo),"r"(sd),"r"(db.hi));
}
__device__ __forceinline__ void wgmma_rs64(float (&d)[32], const uint32_t a0, const uint32_t a1, const uint32_t a2, const uint32_t a3, Desc db, int sd) {
  asm volatile("{.reg .pred p; .reg .b64 da, db; setp.ne.b32 p, %37, 0; mov.b64 db, {%36, %38};\n wgmma.mma_async.sync.aligned.m64n64k16.f32.bf16.bf16 {%0,%1,%2,%3,%4,%5,%6,%7,%8,%9,%10,%11,%12,%13,%14,%15,%16,%17,%18,%19,%20,%21,%22,%23,%24,%25,%26,%27,%28,%29,%30,%31}, {%32,%33,%34,%35}, db, p, 1, 1, 1;}"
   : "+f"(d[0]),"+f"(d[1]),"+f"(d[2]),"+f"(d[3]),"+f"(d[4]),"+f"(d[5]),"+f"(d[6]),"+f"(d[7]),"+f"(d[8]),"+f"(d[9]),"+f"(d[10]),"+f"(d[11]),"+f"(d[12]),"+f"(d[13]),"+f"(d[14]),"+f"(d[15]),"+f"(d[16]),"+f"(d[17]),"+f"(d[18]),"+f"(d[19]),"+f"(d[20]),"+f"(d[21]),"+f"(d[22]),"+f"(d[23]),"+f"(d[24]),"+f"(d[25]),"+f"(d[26]),"+f"(d[27]),"+f"(d[28]),"+f"(d[29]),"+f"(d[30]),"+f"(d[31])
   : "r"(a0),"r"(a1),"r"(a2),"r"(a3),"r"(db.lo),"r"(sd),"r"(db.hi));
}
__device__ __forceinline__ void wgmma_rs192(float (&d)[96], const uint32_t a0, const uint32_t a1, const uint32_t a2, const uint32_t a3, Desc db, int sd) {
  asm volatile("{.reg .pred p; .reg .b64 db; setp.ne.b32 p, %101, 0; mov.b64 db, {%100, %102};\n wgmma.mma_async.sync.aligned.m64n192k16.f32.bf16.bf16 {%0,%1,%2,%3,%4,%5,%6,%7,%8,%9,%10,%11,%12,%13,%14,%15,%16,%17,%18,%19,%20,%21,%22,%23,%24,%25,%26,%27,%28,%29,%30,%31,%32,%33,%34,%35,%36,%37,%38,%39,%40,%41,%42,%43,%44,%45,%46,%47,%48,%49,%50,%51,%52,%53,%54,%55,%56,%57,%58,%59,%60,%61,%62,%63,%64,%65,%66,%67,%68,%69,%70,%71,%72,%73,%74,%75,%76,%77,%78,%79,%80,%81,%82,%83,%84,%85,%86,%87,%88,%89,%90,%91,%92,%93,%94,%95}, {%96,%97,%98,%99}, db, p, 1, 1, 1;}"
   : "+f"(d[0]),"+f"(d[1]),"+f"(d[2]),"+f"(d[3]),"+f"(d[4]),"+f"(d[5]),"+f"(d[6]),"+f"(d[7]),"+f"(d[8]),"+f"(d[9]),"+f"(d[10]),"+f"(d[11]),"+f"(d[12]),"+f"(d[13]),"+f"(d[14]),"+f"(d[15]),"+f"(d[16]),"+f"(d[17]),"+f"(d[18]),"+f"(d[19]),"+f"(d[20]),"+f"(d[21]),"+f"(d[22]),"+f"(d[23]),"+f"(d[24]),"+f"(d[25]),"+f"(d[26]),"+f"(d[27]),"+f"(d[28]),"+f"(d[29]),"+f"(d[30]),"+f"(d[31]),"+f"(d[32]),"+f"(d[33]),"+f"(d[34]),"+f"(d[35]),"+f"(d[36]),"+f"(d[37]),"+f"(d[38]),"+f"(d[39]),"+f"(d[40]),"+f"(d[41]),"+f"(d[42]),"+f"(d[43]),"+f"(d[44]),"+f"(d[45]),"+f"(d[46]),"+f"(d[47]),"+f"(d[48]),"+f"(d[49]),"+f"(d[50]),"+f"(d[51]),"+f"(d[52]),"+f"(d[53]),"+f"(d[54]),"+f"(d[55]),"+f"(d[56]),"+f"(d[57]),"+f"(d[58]),"+f"(d[59]),"+f"(d[60]),"+f"(d[61]),"+f"(d[62]),"+f"(d[63]),"+f"(d[64]),"+f"(d[65]),"+f"(d[66]),"+f"(d[67]),"+f"(d[68]),"+f"(d[69]),"+f"(d[70]),"+f"(d[71]),"+f"(d[72]),"+f"(d[73]),"+f"(d[74]),"+f"(d[75]),"+f"(d[76]),"+f"(d[77]),"+f"(d[78]),"+f"(d[79]),"+f"(d[80]),"+f"(d[81]),"+f"(d[82]),"+f"(d[83]),"+f"(d[84]),"+f"(d[85]),"+f"(d[86]),"+f"(d[87]),"+f"(d[88]),"+f"(d[89]),"+f"(d[90]),"+f"(d[91]),"+f"(d[92]),"+f"(d[93]),"+f"(d[94]),"+f"(d[95])
   : "r"(a0),"r"(a1),"r"(a2),"r"(a3),"r"(db.lo),"r"(sd),"r"(db.hi));
}
__device__ __forceinline__ void wgmma_rs32(float (&d)[16], const uint32_t a0, const uint32_t a1, const uint32_t a2, const uint32_t a3, Desc db, int sd) {
  asm volatile("{.reg .pred p; .reg .b64 db; setp.ne.b32 p, %21, 0; mov.b64 db, {%20, %22};\n wgmma.mma_async.sync.aligned.m64n32k16.f32.bf16.bf16 {%0,%1,%2,%3,%4,%5,%6,%7,%8,%9,%10,%11,%12,%13,%14,%15}, {%16,%17,%18,%19}, db, p, 1, 1, 1;}"
   : "+f"(d[0]),"+f"(d[1]),"+f"(d[2]),"+f"(d[3]),"+f"(d[4]),"+f"(d[5]),"+f"(d[6]),"+f"(d[7]),"+f"(d[8]),"+f"(d[9]),"+f"(d[10]),"+f"(d[11]),"+f"(d[12]),"+f"(d[13]),"+f"(d[14]),"+f"(d[15])
   : "r"(a0),"r"(a1),"r"(a2),"r"(a3),"r"(db.lo),"r"(sd),"r"(db.hi));
}
__device__ __forceinline__ void wgmma_ss32(float (&d)[16], Desc da, Desc db, int sd) {
  asm volatile("{.reg .pred p; .reg .b64 da, db; setp.ne.b32 p, %18, 0; mov.b64 da, {%16, %19}; mov.b64 db, {%17, %19};\n wgmma.mma_async.sync.aligned.m64n32k16.f32.bf16.bf16 {%0,%1,%2,%3,%4,%5,%6,%7,%8,%9,%10,%11,%12,%13,%14,%15}, da, db, p, 1, 1, 1, 1;}"
   : "+f"(d[0]),"+f"(d[1]),"+f"(d[2]),"+f"(d[3]),"+f"(d[4]),"+f"(d[5]),"+f"(d[6]),"+f"(d[7]),"+f"(d[8]),"+f"(d[9]),"+f"(d[10]),"+f"(d[11]),"+f"(d[12]),"+f"(d[13]),"+f"(d[14]),"+f"(d[15])
   : "r"(da.lo),"r"(db.lo),"r"(sd),"r"(db.hi));
}

__device__ __forceinline__ uint4 ldsm4(uint32_t a) {
  uint4 v; asm volatile("ldmatrix.sync.aligned.m8n8.x4.shared.b16 {%0,%1,%2,%3}, [%4];" : "=r"(v.x), "=r"(v.y), "=r"(v.z), "=r"(v.w) : "r"(a) : "memory"); return v;
}
__device__ __forceinline__ void mma16816(float (&d)[4], const uint4& a, uint32_t b0, uint32_t b1) {
  asm("mma.sync.aligned.m16n8k16.row.col.f32.bf16.bf16.f32 {%0,%1,%2,%3}, {%4,%5,%6,%7}, {%8,%9}, {%0,%1,%2,%3};"
      : "+f"(d[0]), "+f"(d[1]), "+f"(d[2]), "+f"(d[3]) : "r"(a.x), "r"(a.y), "r"(a.z), "r"(a.w), "r"(b0), "r"(b1));
}
__device__ __forceinline__ uint32_t bsub(uint32_t a, uint32_t b) { uint32_t r; asm("sub.bf16x2 %0, %1, %2;" : "=r"(r) : "r"(a), "r"(b)); return r; }
__device__ __forceinline__ uint32_t hint_ld(const uint32_t* p) { uint32_t v; asm volatile("ld.relaxed.gpu.global.u32 %0, [%1];" : "=r"(v) : "l"(p) : "memory"); return v; }
template <int S, int N, bool SPL = false, int T> __device__ __forceinline__ void ll_issue(uint4 (&v)[T], const uint4* p, int stride, const uint2* p2 = nullptr) {
#pragma unroll
  for (int i = S; i < S + N; i++) {
    if (SPL && i % 7 == 3) { const uint2 lo = ldll2(p2 + i * 64), hi = ldll2(p2 + i * 64 + 32); v[i] = make_uint4(lo.x, lo.y, hi.x, hi.y); }
    else v[i] = ldll(p + i * stride);
  }
}
template <int S, int N, bool SPL, int T> __device__ __forceinline__ void ll_check(uint4 (&v)[T], const uint4* p, int stride, uint32_t tag, const uint2* p2 = nullptr) {
#pragma unroll 1
  for (int it = 0; it < SPIN; it++) {
    uint32_t bad = 0;
#pragma unroll
    for (int i = S; i < S + N; i++) bad |= (v[i].x ^ tag) | ((SPL && i % 7 == 3) ? (v[i].z ^ tag) : 0u);
    if (!__any_sync(~0u, bad & 1)) break;
    ll_issue<S, N, SPL>(v, p, stride, p2);
  }
}
__device__ __forceinline__ void hint_post(uint32_t* p, uint32_t v, int lane) {
  if (lane == 0) asm volatile("st.relaxed.gpu.global.u32 [%0], %1;" ::"l"(p), "r"(v) : "memory");
}
__device__ __forceinline__ void hint_wait(const uint32_t* p, uint32_t s, uint32_t v = 0xffffu) {
#pragma unroll 1
  for (int it = 0; it < SPIN; it++) {
    if (__all_sync(~0u, v - s < 10u)) break;
    v = hint_ld(p);
  }
}
__device__ __forceinline__ void probe_wait(const uint4* p, uint32_t tag) {
#pragma unroll 1
  for (int it = 0; it < SPIN; it++) if (!__any_sync(~0u, (hint_ld((const uint32_t*)p) ^ tag) & 1)) break;
}
template <int N> __device__ __forceinline__ void bulk_wait_read(int lane) {
  if (lane == 0) asm volatile("cp.async.bulk.wait_group.read %0;" ::"n"(N) : "memory");
  __syncwarp();
}
__device__ __forceinline__ void slice_store(uint4* pf, uint2* ph, const uint32_t (&w)[14], bool odd) {
#pragma unroll
  for (int u = 0; u < 3; u++)
    stll(pf + u * 32, odd ? w[4 * u + 2] : w[4 * u], odd ? w[4 * u + 3] : w[4 * u + 1], odd ? w[4 * u + 4] : w[4 * u + 2], odd ? w[4 * u + 5] : w[4 * u + 3]);
  stll2(ph, odd ? w[0] : w[12], odd ? w[1] : w[13]);
}
template <class F, class M> __device__ __forceinline__ void hedgehog(const float (&d)[28], F sink, M mid) {
  const float L2E = 1.4426950408889634f;
#define HX(G, p) ((p) < 6 ? d[((G) & 1) * 16 + ((p) >> 1) * 4 + ((p) & 1) + ((G) & 2)] : d[12 + (G)])
  float mx[4], mn[4], sp[4], sn[4], ep[4][7], en[4][7];
#pragma unroll
  for (int G = 0; G < 4; G++) {
    mx[G] = mn[G] = HX(G, 0);
#pragma unroll
    for (int p = 1; p < 7; p++) { mx[G] = fmaxf(mx[G], HX(G, p)); mn[G] = fminf(mn[G], HX(G, p)); }
  }
#pragma unroll
  for (int o = 1; o < 4; o <<= 1)
#pragma unroll
    for (int G = 0; G < 4; G++) { mx[G] = fmaxf(mx[G], __shfl_xor_sync(~0u, mx[G], o)); mn[G] = fminf(mn[G], __shfl_xor_sync(~0u, mn[G], o)); }
#pragma unroll
  for (int G = 0; G < 4; G++) {
    const float a = -mx[G] * L2E, b = mn[G] * L2E;
#pragma unroll
    for (int p = 0; p < 7; p++) { ep[G][p] = ex2(fmaf(HX(G, p), L2E, a)); en[G][p] = ex2(fmaf(HX(G, p), -L2E, b)); }
    sp[G] = ((ep[G][0] + ep[G][1]) + (ep[G][2] + ep[G][3])) + ((ep[G][4] + ep[G][5]) + ep[G][6]);
    sn[G] = ((en[G][0] + en[G][1]) + (en[G][2] + en[G][3])) + ((en[G][4] + en[G][5]) + en[G][6]);
    if (G == 1) mid();
  }
#pragma unroll
  for (int o = 1; o < 4; o <<= 1)
#pragma unroll
    for (int G = 0; G < 4; G++) { sp[G] += __shfl_xor_sync(~0u, sp[G], o); sn[G] += __shfl_xor_sync(~0u, sn[G], o); }
#pragma unroll
  for (int G = 0; G < 4; G++) {
    const float a = rcp(sp[G]), b = rcp(sn[G]);
#pragma unroll
    for (int p = 0; p < 7; p++) sink(G >> 1, G & 1, p, pack(ep[G][p] * a, en[G][p] * b));
  }
}
__device__ __forceinline__ void phi_gemm(const float (&x)[28], float (&y)[28], uint32_t wphi, float r0, float r1) {
  uint32_t f[14];
#pragma unroll
  for (int j = 0; j < 14; j++) f[j] = pack(x[2 * j] * (j & 1 ? r1 : r0), x[2 * j + 1] * (j & 1 ? r1 : r0));
  wg_fence();
#pragma unroll
  for (int ks = 0; ks < 3; ks++) wgmma_rs56(y, f[4 * ks], f[4 * ks + 1], f[4 * ks + 2], f[4 * ks + 3], mkdesc(wphi, ks * 2048, 1024, 1024, 1), ks);
  wgmma_rs56(y, f[12], f[13], 0u, 0u, mkdesc(wphi, 3 * 2048, 1024, 1024, 1), 1);
  wg_commit();
}
__device__ __forceinline__ void ln_stats(uint32_t (&xw)[4][4], float* sLN, int warp, int lane, uint4* dst) {
  const int g = lane >> 2; const bool full = warp < 4;
  float s0 = 0.f, s1 = 0.f;
#pragma unroll
  for (int u = 0; u < 4; u++) {
    s0 += (blo(xw[u][0]) + bhi(xw[u][0])) + (blo(xw[u][2]) + bhi(xw[u][2]));
    s1 += (blo(xw[u][1]) + bhi(xw[u][1])) + (blo(xw[u][3]) + bhi(xw[u][3]));
  }
  const float rc = full ? 1.f / 64 : 1.f / 48;
  s0 = qsum(s0); s1 = qsum(s1);
  const float a0 = s0 * rc, a1 = s1 * rc;
  float v0 = 0.f, v1 = 0.f;
#pragma unroll
  for (int u = 0; u < 4; u++)
    if (u < 3 || full) {
#pragma unroll
      for (int k = 0; k < 4; k += 2) {
        float a = blo(xw[u][k]) - a0, b = bhi(xw[u][k]) - a0, c2 = blo(xw[u][k + 1]) - a1, d2 = bhi(xw[u][k + 1]) - a1;
        v0 += a * a + b * b; v1 += c2 * c2 + d2 * d2;
      }
    }
  v0 = qsum(v0); v1 = qsum(v1);
  if ((lane & 3) == 0) *(float4*)(sLN + (g * 8 + warp) * 4) = make_float4(s0, v0, s1, v1);
  if (warp) { asm volatile("bar.arrive 7, 256;" ::: "memory"); return; }
  asm volatile("bar.sync 7, 256;" ::: "memory");
  const float4 ea = *(const float4*)(sLN + (g * 8 + (lane & 3)) * 4), eb = *(const float4*)(sLN + (g * 8 + 4 + (lane & 3)) * 4);
  const float m0 = qsum(ea.x + eb.x) * (1.f / 448), m1 = qsum(ea.z + eb.z) * (1.f / 448);
  const float d0 = ea.x * (1.f / 64) - m0, d1 = eb.x * (1.f / 48) - m0, d2 = ea.z * (1.f / 64) - m1, d3 = eb.z * (1.f / 48) - m1;
  v0 = qsum(ea.y + eb.y + 64.f * d0 * d0 + 48.f * d1 * d1); v1 = qsum(ea.w + eb.w + 64.f * d2 * d2 + 48.f * d3 * d3);
  if ((lane & 3) == 0) stll(dst + g, tg(__float_as_uint(m0), 1), __float_as_uint(rsqrtf(v0 * (1.f / 448) + 1e-5f)), __float_as_uint(m1), __float_as_uint(rsqrtf(v1 * (1.f / 448) + 1e-5f)));
}

__global__ void __launch_bounds__(384, 1)
fused_kernel(const __grid_constant__ CUtensorMap mQKV, const __grid_constant__ CUtensorMap mWO, const __grid_constant__ CUtensorMap mW1,
             const __grid_constant__ CUtensorMap mW1b, const __grid_constant__ CUtensorMap mW2, const __grid_constant__ CUtensorMap mW2b,
             const __grid_constant__ CUtensorMap mX, const __nv_bfloat16* __restrict__ wqkv, const __nv_bfloat16* __restrict__ wphi,
             const __nv_bfloat16* __restrict__ wo, const __nv_bfloat16* __restrict__ w1, const __nv_bfloat16* __restrict__ b1,
             const __nv_bfloat16* __restrict__ w2, const __nv_bfloat16* __restrict__ b2, __nv_bfloat16* __restrict__ out) {
  extern __shared__ __align__(1024) uint8_t sm[];
  constexpr uint32_t sb = 1024;
  if (s2u(sm) != sb) __trap();
  const int tid = threadIdx.x, warp = __shfl_sync(~0u, tid >> 5, 0), lane = tid & 31,
            t = blockIdx.x >> 3, c = blockIdx.x & 7;
  const uint32_t bfull = sb + OFF_BAR, bempty = bfull + 8 * NST;

#define XOFF(l) ((t * 128 + c * 16 + ((l) >> 2)) * 448 + warp * 16 + 2 * ((l) & 3))
  if (warp < 8) { MARK(0); GT(19); }
  if (tid == 256) {
    for (int s = 0; s < NST; s++) { mbar_init(bfull + 8 * s, 1); mbar_init(bempty + 8 * s, 8); }
    mbar_init(bempty + 8 * NST, 1);
    asm volatile("fence.mbarrier_init.release.cluster;" ::: "memory");
    fence_async();
    mbar_expect(bempty + 8 * NST, 114688);
    for (int i = 0; i < 7; i++)
      asm volatile("cp.async.bulk.tensor.2d.shared::cluster.global.mbarrier::complete_tx::bytes [%0], [%1, {%3, %4}], [%2];"
                   ::"r"(sb + 2 * STAGE + i * 16384), "l"(&mX), "r"(bempty + 8 * NST), "r"(64 * i), "r"(128 * t) : "memory");
  }
  __syncthreads();
  if (warp >= 8) {
    asm volatile("setmaxnreg.dec.sync.aligned.u32 24;");
    auto issue = [&](int i, int s) {
      const uint32_t dst = sb + s * STAGE, bar = bfull + 8 * s;
      mbar_expect(bar, STAGE);
#pragma unroll 1
      for (int rk = 0; rk < 2; rk++)
      if (i < 4) tma2d(dst + rk * 14336, &mQKV, 448 + 448 * rk + 56 * c, 112 * i, bar);
      else if (i < 8) tma2d(dst + rk * 14336, i < 6 ? &mQKV : &mWO, (i < 6 ? 56 : 64) * c, 224 * (i & 1) + 112 * rk, bar);
      else if (i < 15) { const int k0 = 64 * ((i - 8 + c) % 7) + 32 * rk;
        tma3d(dst + rk * 12288, &mW1, 0, k0, 3 * c, bar); tma2d(dst + 24576 + rk * 2048, &mW1b, 1536 + 32 * c, k0, bar); }
      else { tma2d(dst + rk * 12288, &mW2, 64 * (i - 15), 192 * c + 96 * rk, bar); tma2d(dst + 24576 + rk * 2048, &mW2b, 64 * (i - 15), 1536 + 32 * c + 16 * rk, bar); }
    };
    auto colsum = [&](int job) {
        const int ld4 = job < 112 ? 448 : 336;
        const uint2* wp = (job < 112 ? (const uint2*)w1 + job * 4 : (const uint2*)wqkv + (job - 112) * 4) + (lane >> 2) * ld4 + (lane & 3);
        float s0 = 0.f, s1 = 0.f, s2 = 0.f, s3 = 0.f;
#pragma unroll 8
        for (int i = 0; i < 56; i++) { const uint2 v = __ldg(wp + i * 8 * ld4); s0 += blo(v.x); s1 += bhi(v.x); s2 += blo(v.y); s3 += bhi(v.y); }
#pragma unroll 1
        for (int o = 4; o < 32; o <<= 1) { s0 += __shfl_xor_sync(~0u, s0, o); s1 += __shfl_xor_sync(~0u, s1, o); s2 += __shfl_xor_sync(~0u, s2, o); s3 += __shfl_xor_sync(~0u, s3, o); }
        if (lane < 4) stll(g_CS + job * 4 + lane, tg(__float_as_uint(s0), 1), __float_as_uint(s1), __float_as_uint(s2), __float_as_uint(s3));
      };
    if (warp == 8) {
#pragma unroll 1
      for (int n = 0; n < 44; n++) {
        const int L = n >= 22, i = L ? (n < 28 ? (n - 18) % 6 : n - 22) : n, s = i % 6;
        if (n == 2) asm volatile("bar.sync 2, 288;" ::: "memory");
        mbar_wait(bempty + 8 * s, (i / 6 + (s >= 4 ? L : 0) + 1) & 1);
        if (n == 22) {
          uint32_t v = 0;
#pragma unroll 1
          for (int it = 0; it < SPIN && v < 32; it++) asm volatile("ld.acquire.gpu.global.u32 %0, [%1];" : "=r"(v) : "l"(g_WQF + c) : "memory");
          asm volatile("fence.proxy.async.global;" ::: "memory");
        }
        if (lane == 0) {
          if (n >= 22 && n < 28) {
            mbar_expect(bfull + 8 * s, STAGE);
            asm volatile("cp.async.bulk.shared::cluster.global.mbarrier::complete_tx::bytes [%0], [%1], %2, [%3];"
                         ::"r"(sb + s * STAGE), "l"(g_WQ + c * 10752 + i * (STAGE / 16)), "r"(STAGE), "r"(bfull + 8 * s) : "memory");
          } else issue(i, s);
        }
        __syncwarp();
      }
    } else if (warp == 9) {
      mbar_wait(bfull + 8 * 3, 0);
      if (lane == 0) {
        l2pf((const uint8_t*)wo + blockIdx.x * 3136, 3136);
        l2pf((const uint8_t*)w1 + blockIdx.x * 12544, 12544);
        l2pf((const uint8_t*)w2 + blockIdx.x * 12544, 12544);
      }
      if (blockIdx.x < 112) colsum(blockIdx.x);
      asm volatile("bar.sync 6, 96;" ::: "memory");
#pragma unroll 1
      for (int i = 0; i < 4; i++) {
        const int e = lane < 28 ? lane + 28 * (i & 1) : 0;
        const bool ok = i < 2 || (e < 48 && (e & 15) < 14);
        const int e4 = i < 2 ? (e < 48 ? 48 * c + e : 336 + 8 * c + e) : ok ? 448 + 112 * (e >> 4) + 14 * c + (e & 15) : 448;
        uint4 cv[1];
        ll_issue<0, 1>(cv, g_CS + e4, 0); ll_check<0, 1, false>(cv, g_CS + e4, 0, 1u);
        const uint2 bb = __ldg((const uint2*)b1 + (i < 2 ? e4 : 0));
        const uint32_t h0 = pack(__uint_as_float(cv[0].x), __uint_as_float(cv[0].y)), h1 = pack(__uint_as_float(cv[0].z), __uint_as_float(cv[0].w));
        const uint32_t l0 = pack(__uint_as_float(cv[0].x) - blo(h0), __uint_as_float(cv[0].y) - bhi(h0)), l1 = pack(__uint_as_float(cv[0].z) - blo(h1), __uint_as_float(cv[0].w) - bhi(h1));
#pragma unroll 1
        for (int j = 0; j < (i < 2 ? 5 : 3); j++) {
          const int r = i < 2 ? j : j + 5;
          const uint32_t ad = sb + OFF_CB + (e >> 3) * 512 + r * 64 + ((((e >> 1) ^ (r >> 1)) & 3) << 4) + (e & 1) * 8;
          sts32(ad, j < 2 ? h0 : j == 2 ? l0 : bb.x); sts32(ad + 4, j < 2 ? h1 : j == 2 ? l1 : bb.y);
        }
        if (i & 1) { fence_async(); if (i == 1) asm volatile("bar.arrive 4, 288;" ::: "memory"); else asm volatile("bar.arrive 8, 160; bar.arrive 9, 160;" ::: "memory"); }
      }
    } else if (warp >= 10) {
      const int h = warp - 10;
      uint4 wv[4];
#pragma unroll
      for (int i = 0; i < 4; i++) wv[i] = __ldg((const uint4*)wphi + (2 * c + h) * 98 + min(lane + 32 * i, 97));
#pragma unroll 1
      for (int e = h * 32 + lane; e < 672; e += 64) sts128(sb + OFF_WPHI + e * 16, 0, 0, 0, 0);
      asm volatile("bar.arrive 6, 96;" ::: "memory");
      asm volatile("bar.sync 5, 64;" ::: "memory");
#pragma unroll
      for (int i = 0; i < 4; i++) sts128(sb + OFF_V + h * 2048 + (lane + 32 * i) * 16, wv[i].x, wv[i].y, wv[i].z, wv[i].w);
      __syncwarp();
#pragma unroll 1
      for (int e = lane; e < 392; e += 32) {
        const int d = e / 14, f2 = 2 * (e - 14 * d), k = 28 * h + d;
        const uint32_t v = *(volatile uint32_t*)(sm + OFF_V + h * 2048 + e * 4);
        if (f2 < 24) sts32(sb + OFF_WPHI + sw128(k, 32 * h + f2), v);
        else { sts16(sb + OFF_WPHI + sw128(k, 2 * f2 - 24 + h), v); sts16(sb + OFF_WPHI + sw128(k, 2 * f2 - 22 + h), v >> 16); }
      }
      fence_async();
      asm volatile("bar.arrive 3, 320;" ::: "memory");
      mbar_wait(bfull + 8 * 5, 0);
#pragma unroll 2
      for (int e = t * 672 + h * 32 + lane; e < t * 672 + 672; e += 64) {
        const int r = e >> 3, st = r / 224, rr = r - st * 224, ch = (e & 7) ^ (rr & 7);
        const int k = st < 4 ? 112 * st + (rr >= 112 ? rr - 112 : rr) : 224 * (st - 4) + rr, col = (st < 4 ? (rr >= 112 ? 896 : 448) : 0) + 56 * c + 8 * ch;
        g_WQ[c * 10752 + e] = ch < 7 ? __ldg((const uint4*)(wqkv + k * 1344 + col)) : make_uint4(0, 0, 0, 0);
      }
      __syncwarp();
      if (lane == 0) asm volatile("red.release.gpu.global.add.u32 [%0], 1;" ::"l"(g_WQF + c) : "memory");
      if (h == 0 && blockIdx.x < 84) colsum(112 + blockIdx.x);
    }
  } else {
  asm volatile("setmaxnreg.inc.sync.aligned.u32 240;");

  const int wg = warp >> 2, g = lane >> 2, q = lane & 3;
  const int row0 = warp * 16 + g;
#define PTRS const int ln_ = laneid(); \
  uint4* const fm = g_F + ((t * 8 + warp) * 28) * 32 + ln_;            \
  uint4* const fr = g_F + ((t * 8 + c) * 28 + warp) * 32 + ln_;        \
  uint4* const sf = fm + (7 * (c >> 1) + 4 * (c & 1)) * 32;             \
  uint2* const f2 = (uint2*)(fm - ln_) + ln_;                           \
  uint2* const sh = f2 + (7 * (c >> 1) + 3) * 64 + 32 * (c & 1);        \
  uint32_t* const hme = g_H + (t * 8 + warp) * 8 + c; \
  const uint32_t* const hrow = g_H + (t * 8 + warp) * 8 + (ln_ & 7); \
  (void)fm; (void)fr; (void)sf; (void)f2; (void)sh; (void)hme; (void)hrow;
  float* sLN = (float*)(sm + OFF_V);
  const uint32_t sPK = sb + OFF_PHIK, sV = sb + OFF_V, d16 = (sb & 0x3FFFF) >> 4;
    uint32_t xw[4][4];
#pragma unroll
  for (int i = 0; i < 16; i++) xw[i >> 2][i & 3] = 0;
#define ACQ(I) (mbar_wait(bfull + 8 * ((I) % 6), ((I) / 6 + ((I) % 6 >= 4 ? L : 0)) & 1), d16 + ((I) % 6) * (STAGE >> 4))
#define REL(I) { if (lane == 0) mbar_arrive(bempty + 8 * ((I) % 6)); }
#define RISSUE(m, P, XA, XB, BA, BB) { ll_issue<0, 8>(P, pr + (m) * 256, 896); \
      { const uint4 v_ = ldll(fr + X1 + (m) * 256); XA = make_uint2(v_.x, v_.y); XB = make_uint2(v_.z, v_.w); } \
      const uint32_t* bp = (const uint32_t*)(b2 + 128 * (m) + 16 * warp) + (ln_ & 3); BA = __ldg(bp); BB = __ldg(bp + 4); }
#define REDU(m, P, XA, XB, BA, BB) { ll_check<0, 8, false>(P, pr + (m) * 256, 896, ptag); \
      float e[8] = {blo(XA.x) + blo(BA), bhi(XA.x) + bhi(BA), blo(XA.y) + blo(BA), bhi(XA.y) + bhi(BA), blo(XB.x) + blo(BB), bhi(XB.x) + bhi(BB), blo(XB.y) + blo(BB), bhi(XB.y) + bhi(BB)}; \
      _Pragma("unroll") for (int i = 0; i < 8; i++) { e[0] += blo(P[i].x); e[1] += bhi(P[i].x); e[2] += blo(P[i].y); e[3] += bhi(P[i].y); \
        e[4] += blo(P[i].z); e[5] += bhi(P[i].z); e[6] += blo(P[i].w); e[7] += bhi(P[i].w); } \
      xw[m][0] = pack(e[0], e[1]); xw[m][1] = pack(e[2], e[3]); xw[m][2] = pack(e[4], e[5]); xw[m][3] = pack(e[6], e[7]); }
#define RPUB(m) stll(fr + XR + (m) * 256, tg(xw[m][0], 0), xw[m][1], xw[m][2], xw[m][3]);
#define RLAST(ptag_) { const uint32_t ptag = ptag_; const uint4* pr = g_P + ((t * 8 + c) * 8 * 28 + warp) * 32 + ln_; uint4 p[8]; uint2 xa, xb; uint32_t ba, bb; \
      if (ptag_) probe_wait(pr - ln_ + 31 + 3 * 256 + (ln_ & 7) * 896, ptag); RISSUE(3, p, xa, xb, ba, bb) REDU(3, p, xa, xb, ba, bb) }
#pragma unroll 1
  for (int L = 0; L < 2; L++) {
    const uint32_t tag = 1 - L;
    uint32_t phq[2][2][7];
    const uint32_t hs = 10 * L;
    {
      PTRS
      uint4 a[28];
      const uint4* pa = fm + XR;
      uint32_t fa = 0, fb = 0;
      float r0 = 1.f, r1 = 1.f;
      if (L == 0) {
        hint_post(hme, 1, lane);
        mbar_wait(bempty + 8 * NST, 0);
        MARK(1);
        const int row = warp * 16 + (ln_ & 15);
        const uint32_t xb = sb + 2 * STAGE + row * 128;
        float cs_[4][4] = {};
#pragma unroll
        for (int ks = 0; ks < 28; ks++) { a[ks] = ldsm4(xb + (ks >> 2) * 16384 + (((2 * (ks & 3) + (ln_ >> 4)) ^ (row & 7)) << 4)); mma16816(cs_[ks & 3], a[ks], 0x3F803F80u, 0x3F803F80u); }
        if (c < 7) {
#pragma unroll
          for (int u = 0; u < 4; u++) { const uint4 v = ldsm4(xb + c * 16384 + (((2 * u + (ln_ >> 4)) ^ (row & 7)) << 4)); stll(fm + XR + 128 * c + u * 32, tg(v.x, tag), v.y, v.z, v.w); }
        }
        const float m0 = ((cs_[0][0] + cs_[1][0]) + (cs_[2][0] + cs_[3][0])) * (1.f / 448), m1 = ((cs_[0][2] + cs_[1][2]) + (cs_[2][2] + cs_[3][2])) * (1.f / 448);
        const uint32_t mb0 = pack(m0, m0), mb1 = pack(m1, m1);
        asm volatile("bar.arrive 2, 288;" ::"r"(mb0) : "memory");
#pragma unroll
        for (int ks = 0; ks < 28; ks++) {
          a[ks].x = bsub(a[ks].x, mb0); a[ks].y = bsub(a[ks].y, mb1); a[ks].z = bsub(a[ks].z, mb0); a[ks].w = bsub(a[ks].w, mb1);
        }
        r0 = m0 - blo(mb0); r1 = m1 - blo(mb1);
      } else {
        ll_issue<0, 14>(a, pa, 32);
        if (wg == 0) { RLAST(1u) xw[3][0] = tg(xw[3][0], 0); RPUB(3) } else { xw[3][0] = xw[3][1] = xw[3][2] = xw[3][3] = 0; }
        MARK(20);
        ll_issue<14, 7>(a, pa, 32);
        ln_stats(xw, sLN, warp, lane, g_S2 + (t * 8 + c) * 8);
      }
      MARK(2 + L * 19);
      float ak[28], av[28], aq[28], pp[28];
#define KVSTAGE(i) { if (L) ll_check<7 * i, 7, false>(a, pa, 32, tag); const uint32_t st = ACQ(i); wg_fence(); \
      _Pragma("unroll") for (int ks = 0; ks < 7; ks++) { const uint4 f = a[7 * i + ks]; \
        wgmma_rs56(ak, f.x, f.y, f.z, f.w, mkdesc(st, ks * 2048, 1024, 1024, 1), i | ks); \
        wgmma_rs56(av, f.x, f.y, f.z, f.w, mkdesc(st, 14336 + ks * 2048, 1024, 1024, 1), i | ks); } \
      wg_commit(); if (i > 0) { wg_wait<1>(); REL(i + 5) } }
      KVSTAGE(0) KVSTAGE(1)
      uint4 sv[1] = {make_uint4(0, 0, 0, 0)};
      const uint4* ps = g_S2 + (t * 8 + warp) * 8 + (ln_ >> 2);
      if (L) { ll_issue<21, 7>(a, pa, 32); ll_issue<0, 1>(sv, ps, 0); }
      else {
        float c0[2][4] = {}, c1[2][4] = {};
#pragma unroll
        for (int ks = 0; ks < 28; ks++) { mma16816(c0[ks & 1], a[ks], a[ks].x, a[ks].z); mma16816(c1[ks & 1], a[ks], a[ks].y, a[ks].w); }
        const int src = (ln_ & 28) | (g >> 1);
        const float q0 = __shfl_sync(~0u, (g & 1) ? c0[0][1] + c0[1][1] : c0[0][0] + c0[1][0], src), q1 = __shfl_sync(~0u, (g & 1) ? c1[0][3] + c1[1][3] : c1[0][2] + c1[1][2], src);
        r0 = rsqrtf(fmaxf(q0 * (1.f / 448) - r0 * r0, 0.f) + 1e-5f); r1 = rsqrtf(fmaxf(q1 * (1.f / 448) - r1 * r1, 0.f) + 1e-5f);
      }
      KVSTAGE(2) KVSTAGE(3)
      if (L) {
        if (wg) asm volatile("bar.sync 9, 160;" ::: "memory"); else asm volatile("bar.sync 8, 160;" ::: "memory");
        ll_check<0, 1, false>(sv, ps, 0, 1u);
        const float m0 = -__uint_as_float(sv[0].x), m1 = -__uint_as_float(sv[0].z), h0 = blo(pack(m0, 0.f)), h1 = blo(pack(m1, 0.f));
        r0 = __uint_as_float(sv[0].y); r1 = __uint_as_float(sv[0].w);
        fa = q == 2 ? pack(0.f, h0) : q == 3 ? pack(m0 - h0, h0) : 0u; fb = q == 2 ? pack(0.f, h1) : q == 3 ? pack(m1 - h1, h1) : 0u;
      } else {
        asm volatile("bar.sync 3, 320;" ::: "memory");
      }
      wg_fence();
      wgmma_rs56(ak, fa, fb, 0u, 0u, mkdesc(d16, OFF_CB + 1024, 512, 0, 2), 1);
      wgmma_rs56(av, fa, fb, 0u, 0u, mkdesc(d16, OFF_CB + 2048, 512, 0, 2), 1);
      wg_commit();
      wg_wait<0>(); REL(3) regfence(ak); regfence(av);
      MARK(3 + L * 19);
      bulk_wait_read<0>(lane);
      phi_gemm(ak, pp, d16 + (OFF_WPHI >> 4), r0, r1);
#pragma unroll
      for (int j = 0; j < 7; j++) {
        const int n = 8 * j + 2 * q, n2 = n < 28 ? n : n + 4;
        sts32(sV + sw128(row0, n2), pack(av[4 * j] * r0, av[4 * j + 1] * r0)); sts32(sV + sw128(row0 + 8, n2), pack(av[4 * j + 2] * r1, av[4 * j + 3] * r1));
      }
      { const int n2 = 28 + 2 * (q & 1) + 32 * (q >> 1); const uint32_t v = (q & 1) ? 0u : 0x3F80u; sts32(sV + sw128(row0, n2), v); sts32(sV + sw128(row0 + 8, n2), v); }
      wg_wait<0>(); regfence(pp);
      hedgehog(pp, [&](int r, int h, int p, uint32_t v) { sts32(sPK + h * 16384 + sw128(row0 + 8 * r, 8 * p + 2 * q), v); }, [] {});
#pragma unroll
      for (int i = 0; i < 4; i++) sts32(sPK + (i & 1) * 16384 + sw128(row0 + 8 * (i >> 1), 56 + 2 * q), 0u);
      fence_async();
      bar_cons();
      MARK(4 + L * 19);
      float kv[16];
      wg_fence();
#pragma unroll
      for (int ks = 0; ks < 8; ks++) wgmma_ss32(kv, mkdesc(d16 + wg * 1024, OFF_PHIK + ks * 2048, 1024, 1024, 1), mkdesc(d16 + wg * 4, OFF_V + ks * 2048, 1024, 1024, 1), ks);
      wg_commit(); wg_wait<0>(); regfence(kv);
      const int ln2 = laneid();
#pragma unroll
      for (int u = 0; u < 4; u++) {
        float e[4];
#pragma unroll
        for (int i = 0; i < 4; i++) e[i] = kv[4 * u + i];
        stll(g_KVP + (c * 16 + t) * 1024 + wg * 512 + u * 128 + (warp & 3) * 32 + ln2, tg(__float_as_uint(e[0]), tag), __float_as_uint(e[1]), __float_as_uint(e[2]), __float_as_uint(e[3]));
      }
      MARK(5 + L * 19);
      uint4 k4[4];
      const uint4* pk = g_KVP + (c * 16 + 4 * (ln2 & 3)) * 1024 + 64 * t + warp * 8 + (ln2 >> 2);
#pragma unroll
      for (int i = 0; i < 2; i++) {
        const uint32_t st = ACQ(4 + i); wg_fence();
#pragma unroll
        for (int ks = 0; ks < 14; ks++) { const uint4 f = a[14 * i + ks]; wgmma_rs56(aq, f.x, f.y, f.z, f.w, mkdesc(st, ks * 2048, 1024, 1024, 1), i | ks); }
        if (i == 1) wgmma_rs56(aq, fa, fb, 0u, 0u, mkdesc(d16, OFF_CB, 512, 0, 2), 1);
        wg_commit();
        if (i == 1) ll_issue<0, 4>(k4, pk, 1024);
      }
      ll_check<0, 4, false>(k4, pk, 1024, tag);
      float s0 = 0, s1 = 0, s2 = 0, s3 = 0;
#pragma unroll
      for (int i = 0; i < 4; i++) { s0 += __uint_as_float(k4[i].x); s1 += __uint_as_float(k4[i].y); s2 += __uint_as_float(k4[i].z); s3 += __uint_as_float(k4[i].w); }
      s0 = qsum(s0); s1 = qsum(s1); s2 = qsum(s2); s3 = qsum(s3);
      if (q == 0) stll2(g_KVR + c * 1024 + 64 * t + warp * 8 + (ln2 >> 2), tg(pack(s0, s1), tag), pack(s2, s3));
      MARK(6 + L * 19);
      wg_wait<0>(); REL(4) REL(5) regfence(aq);
      phi_gemm(aq, pp, d16 + (OFF_WPHI >> 4), r0, r1);
      bar_cons();
#pragma unroll
      for (int i = 0; i < 4; i++) sts128(sV + warp * 2048 + (lane + i * 32) * 16, 0, 0, 0, 0);
      wg_wait<0>(); regfence(pp);
      uint2 r[4];
      const uint2* pr = g_KVR + c * 1024 + wg * 512 + (warp & 3) * 32 + ln2;
      hedgehog(pp, [&](int r, int h, int p, uint32_t v) { phq[r][h][p] = v; }, [&] {
#pragma unroll
        for (int u = 0; u < 4; u++) r[u] = ldll2(pr + u * 128); });
      MARK(7 + L * 19);
#pragma unroll 1
      for (int it = 0; it < SPIN; it++) {
        if (!__any_sync(~0u, ((r[0].x ^ tag) | (r[1].x ^ tag) | (r[2].x ^ tag) | (r[3].x ^ tag)) & 1)) break;
#pragma unroll
        for (int u = 0; u < 4; u++) r[u] = ldll2(pr + u * 128);
      }
#pragma unroll
      for (int u = 0; u < 4; u++) {
        const int d = 8 * u + 2 * q;
        if (d < 28) { sts32(sV + sw128(row0, 28 * wg + d), r[u].x); sts32(sV + sw128(row0 + 8, 28 * wg + d), r[u].y); }
        else if (d == 28) {
#pragma unroll
          for (int j = 0; j < 4; j++) { sts16(sV + sw128(row0, 56 + 2 * j + wg), r[u].x); sts16(sV + sw128(row0 + 8, 56 + 2 * j + wg), r[u].y); }
        }
      }
      fence_async();
      bar_cons();
      MARK(8 + L * 19);
      float o[32];
      wg_fence();
#pragma unroll
      for (int ks = 0; ks < 8; ks++) {
        const int h = ks >> 2, p = 2 * (ks & 3);
        wgmma_rs64(o, phq[0][h][p], phq[1][h][p], p < 6 ? phq[0][h][p < 6 ? p + 1 : 0] : 0u, p < 6 ? phq[1][h][p < 6 ? p + 1 : 0] : 0u, mkdesc(d16, OFF_V + ks * 2048, 1024, 1024, 1), ks);
      }
      wg_commit(); wg_wait<0>(); regfence(o);
      const float iA0 = rcp(o[28] + 1e-6f), iB0 = rcp(o[29] + 1e-6f), iA1 = rcp(o[30] + 1e-6f), iB1 = rcp(o[31] + 1e-6f);
      uint32_t w[14];
      { PTRS
#pragma unroll
      for (int j = 0; j < 7; j++) {
        const bool hb = 8 * j + 2 * q >= 28; const float i0 = hb ? iB0 : iA0, i1 = hb ? iB1 : iA1;
        w[2 * j] = pack(o[4 * j] * i0, o[4 * j + 1] * i0); w[2 * j + 1] = pack(o[4 * j + 2] * i1, o[4 * j + 3] * i1);
        if (j == 0 || ((j ^ c) & 1) == 0) w[2 * j] = tg(w[2 * j], tag);
      }
      slice_store(sf + OO, sh + 2 * OO, w, c & 1);
      hint_post(hme, hs + 2, lane); }
    }
    MARK(9 + L * 19);
    uint4 xr[4];
    if (c < 7) {
      PTRS
      ll_issue<0, 4>(xr, fm + XR + 128 * c, 32);
      uint4 a[28];
      const uint4* pa = fm + OO;
      hint_wait(hrow, hs + 2);
      MARK(10 + L * 19);
      ll_issue<0, 28, true>(a, pa, 32, f2 + 2 * OO);
      float y[32];
      uint32_t st;
#define WOSTEP(i) { ll_check<7 * i, 7, true>(a, pa, 32, tag, f2 + 2 * OO); if (!(i & 1)) st = ACQ(6 + i / 2); wg_fence(); \
      _Pragma("unroll") for (int ks = 0; ks < 7; ks++) { const uint4 f = a[7 * i + ks]; \
        wgmma_rs64(y, f.x, f.y, f.z, f.w, mkdesc(st, ((i & 1) * 7 + ks) * 2048, 1024, 1024, 1), i | ks); } wg_commit(); }
      WOSTEP(0) WOSTEP(1) WOSTEP(2) WOSTEP(3)
      ll_check<0, 4, false>(xr, fm + XR + 128 * c, 32, tag);
      wg_wait<0>(); regfence(y);
      MARK(11 + L * 19);
#pragma unroll
      for (int u = 0; u < 4; u++) {
        xr[u].x = tg(pack(blo(xr[u].x) + y[8 * u], bhi(xr[u].x) + y[8 * u + 1]), tag); xr[u].y = pack(blo(xr[u].y) + y[8 * u + 2], bhi(xr[u].y) + y[8 * u + 3]);
        xr[u].z = pack(blo(xr[u].z) + y[8 * u + 4], bhi(xr[u].z) + y[8 * u + 5]); xr[u].w = pack(blo(xr[u].w) + y[8 * u + 6], bhi(xr[u].w) + y[8 * u + 7]);
        stll(fm + X1 + 128 * c + u * 32, xr[u].x, xr[u].y, xr[u].z, xr[u].w);
      }
      hint_post(hme, hs + 3, lane);
    } else {
      PTRS
      hint_post(hme, hs + 3, lane);
      (void)ACQ(6); (void)ACQ(7);
      hint_wait(hrow, hs + 3);
      ll_issue<0, 4>(xr, fm + X1, 32);
      MARK(10 + L * 19); MARK(11 + L * 19);
    }
    uint32_t hf[56];
    float rr0, rr1;
    {
      PTRS
      uint4 a[28];
      const uint4* pa = fm + X1;
      auto grp = [&](int i) -> const uint4* { const int k = i + c; return pa + ((k >= 7 ? k - 7 : k) - i) * 128; };
      if (c == 7) { ll_issue<4, 12>(a, pa, 32); ll_check<0, 4, false>(xr, pa, 32, tag); }
      else {
#pragma unroll
        for (int u = 4; u < 16; u++) a[u] = make_uint4(0, 0, 0, 0);
      }
#pragma unroll
      for (int u = 0; u < 4; u++) a[u] = xr[u];
      float y[96], z[16];
#define F1STAGE(i) { if (i > 0) ll_check<4 * i, 4, false>(a, grp(i), 32, tag); const uint32_t st = ACQ(8 + i); wg_fence(); \
      _Pragma("unroll") for (int ks = 0; ks < 4; ks++) { const uint4 f = a[4 * i + ks]; \
        wgmma_rs192(y, f.x, f.y, f.z, f.w, mkdesc(st, (ks >> 1) * 12288 + (ks & 1) * 2048, 4096, 1024, 1), i | ks); \
        wgmma_rs32(z, f.x, f.y, f.z, f.w, mkdesc(st, 24576 + ks * 1024, 512, 512, 2), i | ks); } \
      wg_commit(); if (i > 0) { wg_wait<1>(); REL(6 + i) if (i < 4) ll_issue<(i < 4 ? 4 * i + 12 : 0), 4>(a, grp(i + 3), 32); } }
      F1STAGE(0)
      MARK(12 + L * 19);
      if (c < 7) {
        hint_wait(hrow, hs + 3);
        ll_issue<4, 4>(a, grp(1), 32); ll_issue<8, 4>(a, grp(2), 32); ll_issue<12, 4>(a, grp(3), 32);
        float s0 = 0.f, s1 = 0.f, v0 = 0.f, v1 = 0.f;
#pragma unroll
        for (int u = 0; u < 4; u++) { s0 += (blo(xr[u].x) + bhi(xr[u].x)) + (blo(xr[u].z) + bhi(xr[u].z)); s1 += (blo(xr[u].y) + bhi(xr[u].y)) + (blo(xr[u].w) + bhi(xr[u].w)); }
        s0 = qsum(s0) * (1.f / 64); s1 = qsum(s1) * (1.f / 64);
#pragma unroll
        for (int u = 0; u < 4; u++) {
          const float d0 = blo(xr[u].x) - s0, d1 = bhi(xr[u].x) - s0, d2 = blo(xr[u].z) - s0, d3 = bhi(xr[u].z) - s0;
          const float d4 = blo(xr[u].y) - s1, d5 = bhi(xr[u].y) - s1, d6 = blo(xr[u].w) - s1, d7 = bhi(xr[u].w) - s1;
          v0 += (d0 * d0 + d1 * d1) + (d2 * d2 + d3 * d3); v1 += (d4 * d4 + d5 * d5) + (d6 * d6 + d7 * d7);
        }
        v0 = qsum(v0); v1 = qsum(v1);
        if (q == 0) stll(g_ST + ((t * 8 + warp) * 8 + c) * 8 + (ln_ >> 2), tg(__float_as_uint(s0), tag), __float_as_uint(v0), __float_as_uint(s1), __float_as_uint(v1));
      }
      REL(6)
      F1STAGE(1) MARK(13 + L * 19); F1STAGE(2) F1STAGE(3)
      uint4 sv[2];
      const uint4* ps = g_ST + ((t * 8 + warp) * 8 + 2 * (laneid() & 3)) * 8 + (laneid() >> 2);
      ll_issue<0, 2>(sv, ps, q < 3 ? 8 : 0);
      F1STAGE(4)
      ll_check<0, 2, false>(sv, ps, q < 3 ? 8 : 0, tag);
      const float wb = q < 3 ? 1.f : 0.f;
      const float ma = __uint_as_float(sv[0].x), mb = __uint_as_float(sv[1].x), mc = __uint_as_float(sv[0].z), md = __uint_as_float(sv[1].z);
      const float m0 = qsum(ma + wb * mb) * (1.f / 7), m1 = qsum(mc + wb * md) * (1.f / 7);
      const float v0 = qsum(__uint_as_float(sv[0].y) + 64.f * (ma - m0) * (ma - m0) + wb * (__uint_as_float(sv[1].y) + 64.f * (mb - m0) * (mb - m0)));
      const float v1 = qsum(__uint_as_float(sv[0].w) + 64.f * (mc - m1) * (mc - m1) + wb * (__uint_as_float(sv[1].w) + 64.f * (md - m1) * (md - m1)));
      const float e0 = v0 * (1.f / 448) + 1e-5f, e1 = v1 * (1.f / 448) + 1e-5f;
      rr0 = 1.f / e0; rr1 = 1.f / e1;
      auto fold = [&](float m, float sd) -> uint32_t {
        const float mh = blo(pack(-m, 0.f)), sh_ = blo(pack(sd, 0.f));
        return q == 0 ? pack(mh, -m - mh) : q == 1 ? pack(mh, sh_) : q == 2 ? pack(sd - sh_, 0.f) : 0u;
      };
      const uint32_t fa = fold(m0, sqrtf(e0)), fb = fold(m1, sqrtf(e1));
      if (L == 0) asm volatile("bar.sync 4, 288;" ::: "memory");
      wg_fence();
      wgmma_rs192(y, fa, fb, 0u, 0u, mkdesc(d16, OFF_CB, 512, 0, 2), 1);
      wgmma_rs32(z, fa, fb, 0u, 0u, mkdesc(d16, OFF_CB + 3072, 512, 0, 2), 1);
      F1STAGE(5) F1STAGE(6)
      wg_wait<0>(); REL(13) REL(14) regfence(y); regfence(z);
      MARK(14 + L * 19);
#pragma unroll
      for (int j = 0; j < 56; j++) {
        uint32_t r; asm("cvt.rn.relu.bf16x2.f32 %0, %1, %2;" : "=r"(r) : "f"(j < 48 ? y[j < 48 ? 2 * j + 1 : 0] : z[j < 48 ? 0 : 2 * j - 95]), "f"(j < 48 ? y[j < 48 ? 2 * j : 0] : z[j < 48 ? 0 : 2 * j - 96]));
        asm("mul.bf16x2 %0, %1, %1;" : "=r"(hf[j]) : "r"(r));
      }
    }
    MARK(15 + L * 19);
    {
      PTRS
      float ya[32], yb[32];
      uint4* pp = g_P + ((t * 8 + warp) * 8 + c) * 28 * 32 + ln_;
#define F2STORE(j, Y) { regfence(Y); if ((j) >= 3) bulk_wait_read<2>(lane); \
      const uint32_t bf = sPK + (((j) + 1) % 3) * 16384 + warp * 2048; \
      _Pragma("unroll") for (int u = 0; u < 4; u++) \
      sts128(bf + u * 512 + ln_ * 16, tg(pack(Y[8 * u] * rr0, Y[8 * u + 1] * rr0), tag), pack(Y[8 * u + 2] * rr1, Y[8 * u + 3] * rr1), \
             pack(Y[8 * u + 4] * rr0, Y[8 * u + 5] * rr0), pack(Y[8 * u + 6] * rr1, Y[8 * u + 7] * rr1)); \
      fence_async(); __syncwarp(); \
      if (lane == 0) asm volatile("cp.async.bulk.global.shared::cta.bulk_group [%0], [%1], 2048; cp.async.bulk.commit_group;" ::"l"(pp + (j) * 128), "r"(bf) : "memory"); }
#define F2PASS(j, Y, Z) { const uint32_t st = ACQ(15 + j); wg_fence(); \
      _Pragma("unroll") for (int ks = 0; ks < 14; ks++) wgmma_rs64(Y, hf[4 * ks], hf[4 * ks + 1], hf[4 * ks + 2], hf[4 * ks + 3], mkdesc(st, ks * 2048, 1024, 1024, 1), ks); \
      wg_commit(); if (j > 0) { wg_wait<1>(); REL(14 + j) F2STORE(j - 1, Z) } }
      const uint4* pr = g_P + ((t * 8 + c) * 8 * 28 + warp) * 32 + ln_;
      uint4 p[8], p2[8]; uint2 xa, xb, xc, xd; uint32_t ba, bb, bc, bd;
      const uint32_t ptag = tag;
      F2PASS(0, ya, yb) F2PASS(1, yb, ya) F2PASS(2, ya, yb) F2PASS(3, yb, ya)
      F2PASS(4, ya, yb)
      F2PASS(5, yb, ya)
      RISSUE(0, p2, xc, xd, bc, bd)
      F2PASS(6, ya, yb)
      RISSUE(1, p, xa, xb, ba, bb)
      wg_wait<0>(); REL(21) F2STORE(6, ya)
      MARK(16 + L * 19);
      REDU(0, p2, xc, xd, bc, bd)
      if (L == 0) { xw[0][0] = tg(xw[0][0], 0); RPUB(0) bulk_wait_read<2>(lane); bar_cons(); }
      if (wg) probe_wait(pr - ln_ + 31 + 2 * 256 + (ln_ & 7) * 896, tag);
      RISSUE(2, p2, xc, xd, bc, bd)
      REDU(1, p, xa, xb, ba, bb)
      if (L == 0) { xw[1][0] = tg(xw[1][0], 0); RPUB(1) }
      MARK(17 + L * 19);
      REDU(2, p2, xc, xd, bc, bd)
      if (L == 0) { xw[2][0] = tg(xw[2][0], 0); RPUB(2) }
    }
    MARK(18 + L * 19);
  }
  {
    PTRS
    uint32_t* op = (uint32_t*)(out + XOFF(ln_));
#define OUT(u) { op[u * 64] = xw[u][0]; op[u * 64 + 1792] = xw[u][1]; op[u * 64 + 4] = xw[u][2]; op[u * 64 + 1796] = xw[u][3]; }
    OUT(0) OUT(1) OUT(2)
    if (wg == 0) { RLAST(0u) OUT(3) }
    else if (warp == 7) {
      if (t == 0 && lane == 0) g_WQF[c] = 0;
      if (lane < 8) stll(g_S2 + (t * 8 + c) * 8 + lane, 0, 0, 0, 0);
      if (lane < 4) { stll(g_CS + blockIdx.x * 4 + lane, 0, 0, 0, 0); if (blockIdx.x < 68) stll(g_CS + 512 + blockIdx.x * 4 + lane, 0, 0, 0, 0); }
    }
  }
  if (lane == 0) asm volatile("cp.async.bulk.wait_group 0;" ::: "memory");
  MARK(38); GT(39);
  }
}

typedef CUresult (*EncFn)(CUtensorMap*, CUtensorMapDataType, cuuint32_t, void*, const cuuint64_t*, const cuuint64_t*, const cuuint32_t*, const cuuint32_t*,
                          CUtensorMapInterleave, CUtensorMapSwizzle, CUtensorMapL2promotion, CUtensorMapFloatOOBfill);

extern "C" void kernel_launch(void* const* d_in, const int* in_sizes, int n_in, void* d_out, int out_size) {
  static EncFn enc = nullptr;
  if (!enc) {
    void* fn = nullptr; cudaDriverEntryPointQueryResult qr;
    cudaGetDriverEntryPoint("cuTensorMapEncodeTiled", &fn, cudaEnableDefault, &qr);
    enc = (EncFn)fn;
    cudaFuncSetAttribute(fused_kernel, cudaFuncAttributeMaxDynamicSharedMemorySize, SMEM_BYTES);
  }
  CUtensorMap mQKV, mWO, mW1, mW1b, mW2, mW2b, mX;
  const cuuint32_t es[3] = {1, 1, 1};
  auto enc2 = [&](CUtensorMap* m, void* p, cuuint64_t cols, cuuint64_t rows, cuuint32_t bc, cuuint32_t br) {
    const cuuint64_t dims[2] = {cols, rows}, str[1] = {cols * 2}; const cuuint32_t box[2] = {bc, br};
    enc(m, CU_TENSOR_MAP_DATA_TYPE_BFLOAT16, 2, p, dims, str, box, es, CU_TENSOR_MAP_INTERLEAVE_NONE,
        bc == 64 ? CU_TENSOR_MAP_SWIZZLE_128B : CU_TENSOR_MAP_SWIZZLE_64B, CU_TENSOR_MAP_L2_PROMOTION_L2_128B, CU_TENSOR_MAP_FLOAT_OOB_FILL_NONE);
  };
  enc2(&mQKV, d_in[1], 1344, 448, 64, 112); enc2(&mWO, d_in[3], 448, 448, 64, 112); enc2(&mW1b, d_in[5], 1792, 448, 32, 32);
  enc2(&mX, d_in[0], 448, 2048, 64, 128);
  enc2(&mW2, d_in[7], 448, 1792, 64, 96); enc2(&mW2b, d_in[7], 448, 1792, 64, 16);
  {
    const cuuint64_t dims[3] = {64, 448, 28}, str[2] = {3584, 128}; const cuuint32_t box[3] = {64, 32, 3};
    enc(&mW1, CU_TENSOR_MAP_DATA_TYPE_BFLOAT16, 3, d_in[5], dims, str, box, es, CU_TENSOR_MAP_INTERLEAVE_NONE, CU_TENSOR_MAP_SWIZZLE_128B,
        CU_TENSOR_MAP_L2_PROMOTION_L2_128B, CU_TENSOR_MAP_FLOAT_OOB_FILL_NONE);
  }
  typedef const __nv_bfloat16* BP;
  fused_kernel<<<128, 384, SMEM_BYTES>>>(mQKV, mWO, mW1, mW1b, mW2, mW2b, mX, (BP)d_in[1], (BP)d_in[2], (BP)d_in[3], (BP)d_in[5], (BP)d_in[6], (BP)d_in[7], (BP)d_in[8],
                                         (__nv_bfloat16*)d_out);
}
```

```cpp
#include <cuda_runtime.h>
#include <cuda_bf16.h>
#include <cuda.h>
#include <stdint.h>

constexpr int NST = 6, STAGE = 28672;
constexpr int OFF_PHIK = NST * STAGE;
constexpr int OFF_V = OFF_PHIK + 32768;
constexpr int OFF_WPHI = OFF_V + 16384;
constexpr int OFF_CB = OFF_WPHI + 7168;
constexpr int OFF_BAR = OFF_CB + 3584;
constexpr int SMEM_BYTES = OFF_BAR + 16 * NST + 8;
constexpr int FR = 16 * 8 * 28 * 32;
constexpr int SPIN = 1 << 18;

__device__ uint4 g_F[3 * FR];
constexpr int XR = 0, OO = FR, X1 = 2 * FR;
__device__ uint4 g_P[8 * FR];
__device__ uint4 g_ST[16 * 8 * 8 * 8];
__device__ uint4 g_KVP[8 * 16 * 1024];
__device__ uint2 g_KVR[8 * 1024];
__device__ uint4 g_CS[784];
__device__ uint4 g_S2[16 * 8 * 8];
__device__ uint4 g_WQ[8 * 6 * (STAGE / 16)];
__device__ uint32_t g_WQF[8];
__device__ uint32_t g_H[16 * 8 * 8];
#define MARK(i)
#define GT(i)

__device__ __forceinline__ uint32_t s2u(const void* p) { return (uint32_t)__cvta_generic_to_shared(p); }
__device__ __forceinline__ void mbar_init(uint32_t b, uint32_t c) { asm volatile("mbarrier.init.shared::cta.b64 [%0], %1;" ::"r"(b), "r"(c)); }
__device__ __forceinline__ void mbar_expect(uint32_t b, uint32_t tx) { asm volatile("mbarrier.arrive.expect_tx.shared::cta.b64 _, [%0], %1;" ::"r"(b), "r"(tx) : "memory"); }
__device__ __forceinline__ void mbar_arrive(uint32_t b) { asm volatile("mbarrier.arrive.shared::cta.b64 _, [%0];" ::"r"(b) : "memory"); }
__device__ __forceinline__ void mbar_wait(uint32_t b, uint32_t ph) {
  uint32_t ok = 0;
#pragma unroll 1
  for (int it = 0; it < SPIN && !ok; it++)
    asm volatile("{.reg .pred p; mbarrier.try_wait.parity.shared::cta.b64 p,[%1],%2; selp.u32 %0,1,0,p;}" : "=r"(ok) : "r"(b), "r"(ph) : "memory");
}
__device__ __forceinline__ void tma2d(uint32_t dst, const CUtensorMap* m, int c0, int c1, uint32_t bar) {
  asm volatile("cp.async.bulk.tensor.2d.shared::cluster.global.mbarrier::complete_tx::bytes [%0], [%1, {%3, %4}], [%2];"
               ::"r"(dst), "l"(m), "r"(bar), "r"(c0), "r"(c1) : "memory");
}
__device__ __forceinline__ void tma3d(uint32_t dst, const CUtensorMap* m, int c0, int c1, int c2, uint32_t bar) {
  asm volatile("cp.async.bulk.tensor.3d.shared::cluster.global.mbarrier::complete_tx::bytes [%0], [%1, {%3, %4, %5}], [%2];"
               ::"r"(dst), "l"(m), "r"(bar), "r"(c0), "r"(c1), "r"(c2) : "memory");
}
__device__ __forceinline__ void l2pf(const void* p, uint32_t bytes) { asm volatile("cp.async.bulk.prefetch.L2.global [%0], %1;" ::"l"(p), "r"(bytes) : "memory"); }
__device__ __forceinline__ void wg_fence() { asm volatile("wgmma.fence.sync.aligned;" ::: "memory"); }
__device__ __forceinline__ void wg_commit() { asm volatile("wgmma.commit_group.sync.aligned;" ::: "memory"); }
template <int N> __device__ __forceinline__ void wg_wait() { asm volatile("wgmma.wait_group.sync.aligned %0;" ::"n"(N) : "memory"); }
template <int N> __device__ __forceinline__ void regfence(float (&d)[N]) {
#pragma unroll
  for (int i = 0; i < N; i++) asm volatile("" : "+f"(d[i])::"memory");
}
__device__ __forceinline__ void bar_cons() { asm volatile("bar.sync 1, 256;" ::: "memory"); }
__device__ __forceinline__ void fence_async() { asm volatile("fence.proxy.async.shared::cta;" ::: "memory"); }
struct Desc { uint32_t lo, hi; };
__device__ __forceinline__ Desc mkdesc(uint32_t base16, uint32_t off, uint32_t lbo, uint32_t sbo, uint32_t swz) {
  return Desc{base16 + ((off >> 4) | ((lbo >> 4) << 16)), (sbo >> 4) | (swz << 30)};
}
__device__ __forceinline__ uint4 ldll(const uint4* p) {
  uint4 v; asm volatile("ld.relaxed.gpu.global.v4.u32 {%0,%1,%2,%3}, [%4];" : "=r"(v.x), "=r"(v.y), "=r"(v.z), "=r"(v.w) : "l"(p) : "memory"); return v;
}
__device__ __forceinline__ uint2 ldll2(const uint2* p) {
  uint2 v; asm volatile("ld.relaxed.gpu.global.v2.u32 {%0,%1}, [%2];" : "=r"(v.x), "=r"(v.y) : "l"(p) : "memory"); return v;
}
__device__ __forceinline__ void stll(uint4* p, uint32_t x, uint32_t y, uint32_t z, uint32_t w) {
  asm volatile("st.relaxed.gpu.global.v4.u32 [%0], {%1,%2,%3,%4};" ::"l"(p), "r"(x), "r"(y), "r"(z), "r"(w) : "memory");
}
__device__ __forceinline__ void stll2(void* p, uint32_t x, uint32_t y) {
  asm volatile("st.relaxed.gpu.global.v2.u32 [%0], {%1,%2};" ::"l"(p), "r"(x), "r"(y) : "memory");
}
__device__ __forceinline__ int laneid() { int l; asm volatile("mov.u32 %0, %%laneid;" : "=r"(l)); return l; }
__device__ __forceinline__ uint32_t tg(uint32_t w, uint32_t tag) { return (w & ~1u) | tag; }
__device__ __forceinline__ uint32_t pack(float lo, float hi) {
  uint32_t r; asm("cvt.rn.bf16x2.f32 %0, %1, %2;" : "=r"(r) : "f"(hi), "f"(lo)); return r;
}
__device__ __forceinline__ float blo(uint32_t w) { return __uint_as_float(w << 16); }
__device__ __forceinline__ float bhi(uint32_t w) { return __uint_as_float(w & 0xffff0000u); }
__device__ __forceinline__ float ex2(float x) { float r; asm("ex2.approx.ftz.f32 %0, %1;" : "=f"(r) : "f"(x)); return r; }
__device__ __forceinline__ float rcp(float x) { float r; asm("rcp.approx.ftz.f32 %0, %1;" : "=f"(r) : "f"(x)); return r; }
__device__ __forceinline__ float qsum(float v) { v += __shfl_xor_sync(~0u, v, 1); v += __shfl_xor_sync(~0u, v, 2); return v; }
__device__ __forceinline__ void sts32(uint32_t a, uint32_t v) { asm volatile("st.shared.u32 [%0], %1;" ::"r"(a), "r"(v) : "memory"); }
__device__ __forceinline__ void sts16(uint32_t a, uint32_t v) { asm volatile("st.shared.u16 [%0], %1;" ::"r"(a), "h"((uint16_t)v) : "memory"); }
__device__ __forceinline__ void sts128(uint32_t a, uint32_t x, uint32_t y, uint32_t z, uint32_t w) {
  asm volatile("st.shared.v4.u32 [%0], {%1,%2,%3,%4};" ::"r"(a), "r"(x), "r"(y), "r"(z), "r"(w) : "memory");
}
__device__ __forceinline__ uint32_t sw128(int row, int col) { return row * 128 + ((((col >> 3) ^ row) & 7) << 4) + (col & 7) * 2; }

__device__ __forceinline__ void wgmma_rs56(float (&d)[28], const uint32_t a0, const uint32_t a1, const uint32_t a2, const uint32_t a3, Desc db, int sd) {
  asm volatile("{.reg .pred p; .reg .b64 da, db; setp.ne.b32 p, %33, 0; mov.b64 db, {%32, %34};\n wgmma.mma_async.sync.aligned.m64n56k16.f32.bf16.bf16 {%0,%1,%2,%3,%4,%5,%6,%7,%8,%9,%10,%11,%12,%13,%14,%15,%16,%17,%18,%19,%20,%21,%22,%23,%24,%25,%26,%27}, {%28,%29,%30,%31}, db, p, 1, 1, 1;}"
   : "+f"(d[0]),"+f"(d[1]),"+f"(d[2]),"+f"(d[3]),"+f"(d[4]),"+f"(d[5]),"+f"(d[6]),"+f"(d[7]),"+f"(d[8]),"+f"(d[9]),"+f"(d[10]),"+f"(d[11]),"+f"(d[12]),"+f"(d[13]),"+f"(d[14]),"+f"(d[15]),"+f"(d[16]),"+f"(d[17]),"+f"(d[18]),"+f"(d[19]),"+f"(d[20]),"+f"(d[21]),"+f"(d[22]),"+f"(d[23]),"+f"(d[24]),"+f"(d[25]),"+f"(d[26]),"+f"(d[27])
   : "r"(a0),"r"(a1),"r"(a2),"r"(a3),"r"(db.lo),"r"(sd),"r"(db.hi));
}
__device__ __forceinline__ void wgmma_rs64(float (&d)[32], const uint32_t a0, const uint32_t a1, const uint32_t a2, const uint32_t a3, Desc db, int sd) {
  asm volatile("{.reg .pred p; .reg .b64 da, db; setp.ne.b32 p, %37, 0; mov.b64 db, {%36, %38};\n wgmma.mma_async.sync.aligned.m64n64k16.f32.bf16.bf16 {%0,%1,%2,%3,%4,%5,%6,%7,%8,%9,%10,%11,%12,%13,%14,%15,%16,%17,%18,%19,%20,%21,%22,%23,%24,%25,%26,%27,%28,%29,%30,%31}, {%32,%33,%34,%35}, db, p, 1, 1, 1;}"
   : "+f"(d[0]),"+f"(d[1]),"+f"(d[2]),"+f"(d[3]),"+f"(d[4]),"+f"(d[5]),"+f"(d[6]),"+f"(d[7]),"+f"(d[8]),"+f"(d[9]),"+f"(d[10]),"+f"(d[11]),"+f"(d[12]),"+f"(d[13]),"+f"(d[14]),"+f"(d[15]),"+f"(d[16]),"+f"(d[17]),"+f"(d[18]),"+f"(d[19]),"+f"(d[20]),"+f"(d[21]),"+f"(d[22]),"+f"(d[23]),"+f"(d[24]),"+f"(d[25]),"+f"(d[26]),"+f"(d[27]),"+f"(d[28]),"+f"(d[29]),"+f"(d[30]),"+f"(d[31])
   : "r"(a0),"r"(a1),"r"(a2),"r"(a3),"r"(db.lo),"r"(sd),"r"(db.hi));
}
__device__ __forceinline__ void wgmma_rs192(float (&d)[96], const uint32_t a0, const uint32_t a1, const uint32_t a2, const uint32_t a3, Desc db, int sd) {
  asm volatile("{.reg .pred p; .reg .b64 db; setp.ne.b32 p, %101, 0; mov.b64 db, {%100, %102};\n wgmma.mma_async.sync.aligned.m64n192k16.f32.bf16.bf16 {%0,%1,%2,%3,%4,%5,%6,%7,%8,%9,%10,%11,%12,%13,%14,%15,%16,%17,%18,%19,%20,%21,%22,%23,%24,%25,%26,%27,%28,%29,%30,%31,%32,%33,%34,%35,%36,%37,%38,%39,%40,%41,%42,%43,%44,%45,%46,%47,%48,%49,%50,%51,%52,%53,%54,%55,%56,%57,%58,%59,%60,%61,%62,%63,%64,%65,%66,%67,%68,%69,%70,%71,%72,%73,%74,%75,%76,%77,%78,%79,%80,%81,%82,%83,%84,%85,%86,%87,%88,%89,%90,%91,%92,%93,%94,%95}, {%96,%97,%98,%99}, db, p, 1, 1, 1;}"
   : "+f"(d[0]),"+f"(d[1]),"+f"(d[2]),"+f"(d[3]),"+f"(d[4]),"+f"(d[5]),"+f"(d[6]),"+f"(d[7]),"+f"(d[8]),"+f"(d[9]),"+f"(d[10]),"+f"(d[11]),"+f"(d[12]),"+f"(d[13]),"+f"(d[14]),"+f"(d[15]),"+f"(d[16]),"+f"(d[17]),"+f"(d[18]),"+f"(d[19]),"+f"(d[20]),"+f"(d[21]),"+f"(d[22]),"+f"(d[23]),"+f"(d[24]),"+f"(d[25]),"+f"(d[26]),"+f"(d[27]),"+f"(d[28]),"+f"(d[29]),"+f"(d[30]),"+f"(d[31]),"+f"(d[32]),"+f"(d[33]),"+f"(d[34]),"+f"(d[35]),"+f"(d[36]),"+f"(d[37]),"+f"(d[38]),"+f"(d[39]),"+f"(d[40]),"+f"(d[41]),"+f"(d[42]),"+f"(d[43]),"+f"(d[44]),"+f"(d[45]),"+f"(d[46]),"+f"(d[47]),"+f"(d[48]),"+f"(d[49]),"+f"(d[50]),"+f"(d[51]),"+f"(d[52]),"+f"(d[53]),"+f"(d[54]),"+f"(d[55]),"+f"(d[56]),"+f"(d[57]),"+f"(d[58]),"+f"(d[59]),"+f"(d[60]),"+f"(d[61]),"+f"(d[62]),"+f"(d[63]),"+f"(d[64]),"+f"(d[65]),"+f"(d[66]),"+f"(d[67]),"+f"(d[68]),"+f"(d[69]),"+f"(d[70]),"+f"(d[71]),"+f"(d[72]),"+f"(d[73]),"+f"(d[74]),"+f"(d[75]),"+f"(d[76]),"+f"(d[77]),"+f"(d[78]),"+f"(d[79]),"+f"(d[80]),"+f"(d[81]),"+f"(d[82]),"+f"(d[83]),"+f"(d[84]),"+f"(d[85]),"+f"(d[86]),"+f"(d[87]),"+f"(d[88]),"+f"(d[89]),"+f"(d[90]),"+f"(d[91]),"+f"(d[92]),"+f"(d[93]),"+f"(d[94]),"+f"(d[95])
   : "r"(a0),"r"(a1),"r"(a2),"r"(a3),"r"(db.lo),"r"(sd),"r"(db.hi));
}
__device__ __forceinline__ void wgmma_rs32(float (&d)[16], const uint32_t a0, const uint32_t a1, const uint32_t a2, const uint32_t a3, Desc db, int sd) {
  asm volatile("{.reg .pred p; .reg .b64 db; setp.ne.b32 p, %21, 0; mov.b64 db, {%20, %22};\n wgmma.mma_async.sync.aligned.m64n32k16.f32.bf16.bf16 {%0,%1,%2,%3,%4,%5,%6,%7,%8,%9,%10,%11,%12,%13,%14,%15}, {%16,%17,%18,%19}, db, p, 1, 1, 1;}"
   : "+f"(d[0]),"+f"(d[1]),"+f"(d[2]),"+f"(d[3]),"+f"(d[4]),"+f"(d[5]),"+f"(d[6]),"+f"(d[7]),"+f"(d[8]),"+f"(d[9]),"+f"(d[10]),"+f"(d[11]),"+f"(d[12]),"+f"(d[13]),"+f"(d[14]),"+f"(d[15])
   : "r"(a0),"r"(a1),"r"(a2),"r"(a3),"r"(db.lo),"r"(sd),"r"(db.hi));
}
__device__ __forceinline__ void wgmma_ss32(float (&d)[16], Desc da, Desc db, int sd) {
  asm volatile("{.reg .pred p; .reg .b64 da, db; setp.ne.b32 p, %18, 0; mov.b64 da, {%16, %19}; mov.b64 db, {%17, %19};\n wgmma.mma_async.sync.aligned.m64n32k16.f32.bf16.bf16 {%0,%1,%2,%3,%4,%5,%6,%7,%8,%9,%10,%11,%12,%13,%14,%15}, da, db, p, 1, 1, 1, 1;}"
   : "+f"(d[0]),"+f"(d[1]),"+f"(d[2]),"+f"(d[3]),"+f"(d[4]),"+f"(d[5]),"+f"(d[6]),"+f"(d[7]),"+f"(d[8]),"+f"(d[9]),"+f"(d[10]),"+f"(d[11]),"+f"(d[12]),"+f"(d[13]),"+f"(d[14]),"+f"(d[15])
   : "r"(da.lo),"r"(db.lo),"r"(sd),"r"(db.hi));
}

__device__ __forceinline__ uint4 ldsm4(uint32_t a) {
  uint4 v; asm volatile("ldmatrix.sync.aligned.m8n8.x4.shared.b16 {%0,%1,%2,%3}, [%4];" : "=r"(v.x), "=r"(v.y), "=r"(v.z), "=r"(v.w) : "r"(a) : "memory"); return v;
}
__device__ __forceinline__ void mma16816(float (&d)[4], const uint4& a, uint32_t b0, uint32_t b1) {
  asm("mma.sync.aligned.m16n8k16.row.col.f32.bf16.bf16.f32 {%0,%1,%2,%3}, {%4,%5,%6,%7}, {%8,%9}, {%0,%1,%2,%3};"
      : "+f"(d[0]), "+f"(d[1]), "+f"(d[2]), "+f"(d[3]) : "r"(a.x), "r"(a.y), "r"(a.z), "r"(a.w), "r"(b0), "r"(b1));
}
__device__ __forceinline__ uint32_t bsub(uint32_t a, uint32_t b) { uint32_t r; asm("sub.bf16x2 %0, %1, %2;" : "=r"(r) : "r"(a), "r"(b)); return r; }
__device__ __forceinline__ uint32_t hint_ld(const uint32_t* p) { uint32_t v; asm volatile("ld.relaxed.gpu.global.u32 %0, [%1];" : "=r"(v) : "l"(p) : "memory"); return v; }
template <int S, int N, bool SPL = false, int T> __device__ __forceinline__ void ll_issue(uint4 (&v)[T], const uint4* p, int stride, const uint2* p2 = nullptr) {
#pragma unroll
  for (int i = S; i < S + N; i++) {
    if (SPL && i % 7 == 3) { const uint2 lo = ldll2(p2 + i * 64), hi = ldll2(p2 + i * 64 + 32); v[i] = make_uint4(lo.x, lo.y, hi.x, hi.y); }
    else v[i] = ldll(p + i * stride);
  }
}
template <int S, int N, bool SPL, int T> __device__ __forceinline__ void ll_check(uint4 (&v)[T], const uint4* p, int stride, uint32_t tag, const uint2* p2 = nullptr) {
#pragma unroll 1
  for (int it = 0; it < SPIN; it++) {
    uint32_t bad = 0;
#pragma unroll
    for (int i = S; i < S + N; i++) bad |= (v[i].x ^ tag) | ((SPL && i % 7 == 3) ? (v[i].z ^ tag) : 0u);
    if (!__any_sync(~0u, bad & 1)) break;
    ll_issue<S, N, SPL>(v, p, stride, p2);
  }
}
__device__ __forceinline__ void hint_post(uint32_t* p, uint32_t v, int lane) {
  if (lane == 0) asm volatile("st.relaxed.gpu.global.u32 [%0], %1;" ::"l"(p), "r"(v) : "memory");
}
__device__ __forceinline__ void hint_wait(const uint32_t* p, uint32_t s, uint32_t v = 0xffffu) {
#pragma unroll 1
  for (int it = 0; it < SPIN; it++) {
    if (__all_sync(~0u, v - s < 10u)) break;
    v = hint_ld(p);
  }
}
__device__ __forceinline__ void p_issue(uint4 (&v)[8], const uint4* p, uint32_t own) {
  ll_issue<1, 7>(v, p, 896);
  asm volatile("ld.volatile.shared.v4.u32 {%0,%1,%2,%3}, [%4];" : "=r"(v[0].x), "=r"(v[0].y), "=r"(v[0].z), "=r"(v[0].w) : "r"(own) : "memory");
}
__device__ __forceinline__ void p_check(uint4 (&v)[8], const uint4* p, uint32_t own, uint32_t tag) {
#pragma unroll 1
  for (int it = 0; it < SPIN; it++) {
    uint32_t bad = 0;
#pragma unroll
    for (int i = 0; i < 8; i++) bad |= v[i].x ^ tag;
    if (!__any_sync(~0u, bad & 1)) break;
    p_issue(v, p, own);
  }
}
__device__ __forceinline__ void slice_store(uint4* pf, uint2* ph, const uint32_t (&w)[14], bool odd) {
#pragma unroll
  for (int u = 0; u < 3; u++)
    stll(pf + u * 32, odd ? w[4 * u + 2] : w[4 * u], odd ? w[4 * u + 3] : w[4 * u + 1], odd ? w[4 * u + 4] : w[4 * u + 2], odd ? w[4 * u + 5] : w[4 * u + 3]);
  stll2(ph, odd ? w[0] : w[12], odd ? w[1] : w[13]);
}
template <class F, class M> __device__ __forceinline__ void hedgehog(const float (&d)[28], F sink, M mid) {
  const float L2E = 1.4426950408889634f;
#define HX(G, p) ((p) < 6 ? d[((G) & 1) * 16 + ((p) >> 1) * 4 + ((p) & 1) + ((G) & 2)] : d[12 + (G)])
  float mx[4], mn[4], sp[4], sn[4], ep[4][7], en[4][7];
#pragma unroll
  for (int G = 0; G < 4; G++) {
    mx[G] = mn[G] = HX(G, 0);
#pragma unroll
    for (int p = 1; p < 7; p++) { mx[G] = fmaxf(mx[G], HX(G, p)); mn[G] = fminf(mn[G], HX(G, p)); }
  }
#pragma unroll
  for (int o = 1; o < 4; o <<= 1)
#pragma unroll
    for (int G = 0; G < 4; G++) { mx[G] = fmaxf(mx[G], __shfl_xor_sync(~0u, mx[G], o)); mn[G] = fminf(mn[G], __shfl_xor_sync(~0u, mn[G], o)); }
#pragma unroll
  for (int G = 0; G < 4; G++) {
    const float a = -mx[G] * L2E, b = mn[G] * L2E;
#pragma unroll
    for (int p = 0; p < 7; p++) { ep[G][p] = ex2(fmaf(HX(G, p), L2E, a)); en[G][p] = ex2(fmaf(HX(G, p), -L2E, b)); }
    sp[G] = ((ep[G][0] + ep[G][1]) + (ep[G][2] + ep[G][3])) + ((ep[G][4] + ep[G][5]) + ep[G][6]);
    sn[G] = ((en[G][0] + en[G][1]) + (en[G][2] + en[G][3])) + ((en[G][4] + en[G][5]) + en[G][6]);
    if (G == 1) mid();
  }
#pragma unroll
  for (int o = 1; o < 4; o <<= 1)
#pragma unroll
    for (int G = 0; G < 4; G++) { sp[G] += __shfl_xor_sync(~0u, sp[G], o); sn[G] += __shfl_xor_sync(~0u, sn[G], o); }
#pragma unroll
  for (int G = 0; G < 4; G++) {
    const float a = rcp(sp[G]), b = rcp(sn[G]);
#pragma unroll
    for (int p = 0; p < 7; p++) sink(G >> 1, G & 1, p, pack(ep[G][p] * a, en[G][p] * b));
  }
}
__device__ __forceinline__ void phi_gemm(const float (&x)[28], float (&y)[28], uint32_t wphi, float r0, float r1) {
  uint32_t f[14];
#pragma unroll
  for (int j = 0; j < 14; j++) f[j] = pack(x[2 * j] * (j & 1 ? r1 : r0), x[2 * j + 1] * (j & 1 ? r1 : r0));
  wg_fence();
#pragma unroll
  for (int ks = 0; ks < 3; ks++) wgmma_rs56(y, f[4 * ks], f[4 * ks + 1], f[4 * ks + 2], f[4 * ks + 3], mkdesc(wphi, ks * 2048, 1024, 1024, 1), ks);
  wgmma_rs56(y, f[12], f[13], 0u, 0u, mkdesc(wphi, 3 * 2048, 1024, 1024, 1), 1);
  wg_commit();
}
__device__ __forceinline__ void ln_stats(uint32_t (&xw)[4][4], float* sLN, int warp, int lane, uint4* dst) {
  const int g = lane >> 2; const bool full = warp < 4;
  float s0 = 0.f, s1 = 0.f;
#pragma unroll
  for (int u = 0; u < 4; u++) {
    s0 += (blo(xw[u][0]) + bhi(xw[u][0])) + (blo(xw[u][2]) + bhi(xw[u][2]));
    s1 += (blo(xw[u][1]) + bhi(xw[u][1])) + (blo(xw[u][3]) + bhi(xw[u][3]));
  }
  const float rc = full ? 1.f / 64 : 1.f / 48;
  s0 = qsum(s0); s1 = qsum(s1);
  const float a0 = s0 * rc, a1 = s1 * rc;
  float v0 = 0.f, v1 = 0.f;
#pragma unroll
  for (int u = 0; u < 4; u++)
    if (u < 3 || full) {
#pragma unroll
      for (int k = 0; k < 4; k += 2) {
        float a = blo(xw[u][k]) - a0, b = bhi(xw[u][k]) - a0, c2 = blo(xw[u][k + 1]) - a1, d2 = bhi(xw[u][k + 1]) - a1;
        v0 += a * a + b * b; v1 += c2 * c2 + d2 * d2;
      }
    }
  v0 = qsum(v0); v1 = qsum(v1);
  if ((lane & 3) == 0) *(float4*)(sLN + (g * 8 + warp) * 4) = make_float4(s0, v0, s1, v1);
  if (warp < 4) asm volatile("bar.arrive 10, 256;" ::: "memory");
  if (warp) { asm volatile("bar.arrive 7, 256;" ::: "memory"); return; }
  asm volatile("bar.sync 7, 256;" ::: "memory");
  const float4 ea = *(const float4*)(sLN + (g * 8 + (lane & 3)) * 4), eb = *(const float4*)(sLN + (g * 8 + 4 + (lane & 3)) * 4);
  const float m0 = qsum(ea.x + eb.x) * (1.f / 448), m1 = qsum(ea.z + eb.z) * (1.f / 448);
  const float d0 = ea.x * (1.f / 64) - m0, d1 = eb.x * (1.f / 48) - m0, d2 = ea.z * (1.f / 64) - m1, d3 = eb.z * (1.f / 48) - m1;
  v0 = qsum(ea.y + eb.y + 64.f * d0 * d0 + 48.f * d1 * d1); v1 = qsum(ea.w + eb.w + 64.f * d2 * d2 + 48.f * d3 * d3);
  if ((lane & 3) == 0) stll(dst + g, tg(__float_as_uint(m0), 1), __float_as_uint(rsqrtf(v0 * (1.f / 448) + 1e-5f)), __float_as_uint(m1), __float_as_uint(rsqrtf(v1 * (1.f / 448) + 1e-5f)));
}

__global__ void __launch_bounds__(384, 1)
fused_kernel(const __grid_constant__ CUtensorMap mQKV, const __grid_constant__ CUtensorMap mWO, const __grid_constant__ CUtensorMap mW1,
             const __grid_constant__ CUtensorMap mW1b, const __grid_constant__ CUtensorMap mW2, const __grid_constant__ CUtensorMap mW2b,
             const __grid_constant__ CUtensorMap mX, const __nv_bfloat16* __restrict__ wqkv, const __nv_bfloat16* __restrict__ wphi,
             const __nv_bfloat16* __restrict__ wo, const __nv_bfloat16* __restrict__ w1, const __nv_bfloat16* __restrict__ b1,
             const __nv_bfloat16* __restrict__ w2, const __nv_bfloat16* __restrict__ b2, __nv_bfloat16* __restrict__ out) {
  extern __shared__ __align__(1024) uint8_t sm[];
  constexpr uint32_t sb = 1024;
  if (s2u(sm) != sb) __trap();
  const int tid = threadIdx.x, warp = __shfl_sync(~0u, tid >> 5, 0), lane = tid & 31,
            t = blockIdx.x >> 3, c = blockIdx.x & 7;
  const uint32_t bfull = sb + OFF_BAR, bempty = bfull + 8 * NST;

#define XOFF(l) ((t * 128 + c * 16 + ((l) >> 2)) * 448 + warp * 16 + 2 * ((l) & 3))
  if (warp < 8) { MARK(0); GT(19); }
  if (tid == 256) {
    for (int s = 0; s < NST; s++) { mbar_init(bfull + 8 * s, 1); mbar_init(bempty + 8 * s, 8); }
    mbar_init(bempty + 8 * NST, 1);
    asm volatile("fence.mbarrier_init.release.cluster;" ::: "memory");
    fence_async();
    mbar_expect(bempty + 8 * NST, 114688);
    for (int i = 0; i < 7; i++)
      asm volatile("cp.async.bulk.tensor.2d.shared::cluster.global.mbarrier::complete_tx::bytes [%0], [%1, {%3, %4}], [%2];"
                   ::"r"(sb + 2 * STAGE + i * 16384), "l"(&mX), "r"(bempty + 8 * NST), "r"(64 * i), "r"(128 * t) : "memory");
  }
  __syncthreads();
  if (warp >= 8) {
    asm volatile("setmaxnreg.dec.sync.aligned.u32 24;");
    auto issue = [&](int i, int s) {
      const uint32_t dst = sb + s * STAGE, bar = bfull + 8 * s;
      mbar_expect(bar, STAGE);
#pragma unroll 1
      for (int rk = 0; rk < 2; rk++)
      if (i < 4) tma2d(dst + rk * 14336, &mQKV, 448 + 448 * rk + 56 * c, 112 * i, bar);
      else if (i < 8) tma2d(dst + rk * 14336, i < 6 ? &mQKV : &mWO, (i < 6 ? 56 : 64) * c, 224 * (i & 1) + 112 * rk, bar);
      else if (i < 15) { const int k0 = 64 * ((i - 8 + c) % 7) + 32 * rk;
        tma3d(dst + rk * 12288, &mW1, 0, k0, 3 * c, bar); tma2d(dst + 24576 + rk * 2048, &mW1b, 1536 + 32 * c, k0, bar); }
      else { tma2d(dst + rk * 12288, &mW2, 64 * (i - 15), 192 * c + 96 * rk, bar); tma2d(dst + 24576 + rk * 2048, &mW2b, 64 * (i - 15), 1536 + 32 * c + 16 * rk, bar); }
    };
    auto colsum = [&](int job) {
        const int ld4 = job < 112 ? 448 : 336;
        const uint2* wp = (job < 112 ? (const uint2*)w1 + job * 4 : (const uint2*)wqkv + (job - 112) * 4) + (lane >> 2) * ld4 + (lane & 3);
        float s0 = 0.f, s1 = 0.f, s2 = 0.f, s3 = 0.f;
#pragma unroll 8
        for (int i = 0; i < 56; i++) { const uint2 v = __ldg(wp + i * 8 * ld4); s0 += blo(v.x); s1 += bhi(v.x); s2 += blo(v.y); s3 += bhi(v.y); }
#pragma unroll 1
        for (int o = 4; o < 32; o <<= 1) { s0 += __shfl_xor_sync(~0u, s0, o); s1 += __shfl_xor_sync(~0u, s1, o); s2 += __shfl_xor_sync(~0u, s2, o); s3 += __shfl_xor_sync(~0u, s3, o); }
        if (lane < 4) stll(g_CS + job * 4 + lane, tg(__float_as_uint(s0), 1), __float_as_uint(s1), __float_as_uint(s2), __float_as_uint(s3));
      };
    if (warp == 8) {
#pragma unroll 1
      for (int n = 0; n < 44; n++) {
        const int L = n >= 22, i = L ? (n < 28 ? (n - 18) % 6 : n - 22) : n, s = i % 6;
        if (n == 2) asm volatile("bar.sync 2, 288;" ::: "memory");
        mbar_wait(bempty + 8 * s, (i / 6 + (s >= 4 ? L : 0) + 1) & 1);
        if (n == 22) {
          uint32_t v = 0;
#pragma unroll 1
          for (int it = 0; it < SPIN && v < 32; it++) asm volatile("ld.acquire.gpu.global.u32 %0, [%1];" : "=r"(v) : "l"(g_WQF + c) : "memory");
          asm volatile("fence.proxy.async.global;" ::: "memory");
        }
        if (lane == 0) {
          if (n >= 22 && n < 28) {
            mbar_expect(bfull + 8 * s, STAGE);
            asm volatile("cp.async.bulk.shared::cluster.global.mbarrier::complete_tx::bytes [%0], [%1], %2, [%3];"
                         ::"r"(sb + s * STAGE), "l"(g_WQ + c * 10752 + i * (STAGE / 16)), "r"(STAGE), "r"(bfull + 8 * s) : "memory");
          } else issue(i, s);
        }
        __syncwarp();
      }
    } else if (warp == 9) {
      mbar_wait(bfull + 8 * 3, 0);
      if (lane == 0) {
        l2pf((const uint8_t*)wo + blockIdx.x * 3136, 3136);
        l2pf((const uint8_t*)w1 + blockIdx.x * 12544, 12544);
        l2pf((const uint8_t*)w2 + blockIdx.x * 12544, 12544);
      }
      if (blockIdx.x < 112) colsum(blockIdx.x);
      asm volatile("bar.sync 6, 96;" ::: "memory");
#pragma unroll 1
      for (int i = 0; i < 4; i++) {
        const int e = lane < 28 ? lane + 28 * (i & 1) : 0;
        const bool ok = i < 2 || (e < 48 && (e & 15) < 14);
        const int e4 = i < 2 ? (e < 48 ? 48 * c + e : 336 + 8 * c + e) : ok ? 448 + 112 * (e >> 4) + 14 * c + (e & 15) : 448;
        uint4 cv[1];
        ll_issue<0, 1>(cv, g_CS + e4, 0); ll_check<0, 1, false>(cv, g_CS + e4, 0, 1u);
        const uint2 bb = __ldg((const uint2*)b1 + (i < 2 ? e4 : 0));
        const uint32_t h0 = pack(__uint_as_float(cv[0].x), __uint_as_float(cv[0].y)), h1 = pack(__uint_as_float(cv[0].z), __uint_as_float(cv[0].w));
        const uint32_t l0 = pack(__uint_as_float(cv[0].x) - blo(h0), __uint_as_float(cv[0].y) - bhi(h0)), l1 = pack(__uint_as_float(cv[0].z) - blo(h1), __uint_as_float(cv[0].w) - bhi(h1));
#pragma unroll 1
        for (int j = 0; j < (i < 2 ? 5 : 3); j++) {
          const int r = i < 2 ? j : j + 5;
          const uint32_t ad = sb + OFF_CB + (e >> 3) * 512 + r * 64 + ((((e >> 1) ^ (r >> 1)) & 3) << 4) + (e & 1) * 8;
          sts32(ad, j < 2 ? h0 : j == 2 ? l0 : bb.x); sts32(ad + 4, j < 2 ? h1 : j == 2 ? l1 : bb.y);
        }
        if (i & 1) { fence_async(); if (i == 1) asm volatile("bar.arrive 4, 288;" ::: "memory"); else asm volatile("bar.arrive 8, 160; bar.arrive 9, 160;" ::: "memory"); }
      }
    } else if (warp >= 10) {
      const int h = warp - 10;
      uint4 wv[4];
#pragma unroll
      for (int i = 0; i < 4; i++) wv[i] = __ldg((const uint4*)wphi + (2 * c + h) * 98 + min(lane + 32 * i, 97));
#pragma unroll 1
      for (int e = h * 32 + lane; e < 672; e += 64) sts128(sb + OFF_WPHI + e * 16, 0, 0, 0, 0);
      asm volatile("bar.arrive 6, 96;" ::: "memory");
      asm volatile("bar.sync 5, 64;" ::: "memory");
#pragma unroll
      for (int i = 0; i < 4; i++) sts128(sb + OFF_V + h * 2048 + (lane + 32 * i) * 16, wv[i].x, wv[i].y, wv[i].z, wv[i].w);
      __syncwarp();
#pragma unroll 1
      for (int e = lane; e < 392; e += 32) {
        const int d = e / 14, f2 = 2 * (e - 14 * d), k = 28 * h + d;
        const uint32_t v = *(volatile uint32_t*)(sm + OFF_V + h * 2048 + e * 4);
        if (f2 < 24) sts32(sb + OFF_WPHI + sw128(k, 32 * h + f2), v);
        else { sts16(sb + OFF_WPHI + sw128(k, 2 * f2 - 24 + h), v); sts16(sb + OFF_WPHI + sw128(k, 2 * f2 - 22 + h), v >> 16); }
      }
      fence_async();
      asm volatile("bar.arrive 3, 320;" ::: "memory");
      mbar_wait(bfull + 8 * 5, 0);
#pragma unroll 2
      for (int e = t * 672 + h * 32 + lane; e < t * 672 + 672; e += 64) {
        const int r = e >> 3, st = r / 224, rr = r - st * 224, ch = (e & 7) ^ (rr & 7);
        const int k = st < 4 ? 112 * st + (rr >= 112 ? rr - 112 : rr) : 224 * (st - 4) + rr, col = (st < 4 ? (rr >= 112 ? 896 : 448) : 0) + 56 * c + 8 * ch;
        g_WQ[c * 10752 + e] = ch < 7 ? __ldg((const uint4*)(wqkv + k * 1344 + col)) : make_uint4(0, 0, 0, 0);
      }
      __syncwarp();
      if (lane == 0) asm volatile("red.release.gpu.global.add.u32 [%0], 1;" ::"l"(g_WQF + c) : "memory");
      if (h == 0 && blockIdx.x < 84) colsum(112 + blockIdx.x);
    }
  } else {
  asm volatile("setmaxnreg.inc.sync.aligned.u32 240;");

  const int wg = warp >> 2, g = lane >> 2, q = lane & 3;
  const int row0 = warp * 16 + g;
#define PTRS const int ln_ = laneid(); \
  uint4* const fm = g_F + ((t * 8 + warp) * 28) * 32 + ln_;            \
  uint4* const fr = g_F + ((t * 8 + c) * 28 + warp) * 32 + ln_;        \
  uint4* const sf = fm + (7 * (c >> 1) + 4 * (c & 1)) * 32;             \
  uint2* const f2 = (uint2*)(fm - ln_) + ln_;                           \
  uint2* const sh = f2 + (7 * (c >> 1) + 3) * 64 + 32 * (c & 1);        \
  uint32_t* const hme = g_H + (t * 8 + warp) * 8 + c; \
  const uint32_t* const hrow = g_H + (t * 8 + warp) * 8 + (ln_ & 7); \
  (void)fm; (void)fr; (void)sf; (void)f2; (void)sh; (void)hme; (void)hrow;
  float* sLN = (float*)(sm + OFF_V);
  const uint32_t sPK = sb + OFF_PHIK, sV = sb + OFF_V, d16 = (sb & 0x3FFFF) >> 4;
    uint32_t xw[4][4];
#pragma unroll
  for (int i = 0; i < 16; i++) xw[i >> 2][i & 3] = 0;
#define ACQ(I) (mbar_wait(bfull + 8 * ((I) % 6), ((I) / 6 + ((I) % 6 >= 4 ? L : 0)) & 1), d16 + ((I) % 6) * (STAGE >> 4))
#define REL(I) { if (lane == 0) mbar_arrive(bempty + 8 * ((I) % 6)); }
#define RISSUE(m, P, XA, XB, BA, BB) { p_issue(P, pr + (m) * 256, sPK + (8 * (m) + warp) * 512 + ln_ * 16); \
      { const uint4 v_ = ldll(fr + X1 + (m) * 256); XA = make_uint2(v_.x, v_.y); XB = make_uint2(v_.z, v_.w); } \
      const uint32_t* bp = (const uint32_t*)(b2 + 128 * (m) + 16 * warp) + (ln_ & 3); BA = __ldg(bp); BB = __ldg(bp + 4); }
#define REDU(m, P, XA, XB, BA, BB) { p_check(P, pr + (m) * 256, sPK + (8 * (m) + warp) * 512 + ln_ * 16, ptag); \
      float e[8] = {blo(XA.x) + blo(BA), bhi(XA.x) + bhi(BA), blo(XA.y) + blo(BA), bhi(XA.y) + bhi(BA), blo(XB.x) + blo(BB), bhi(XB.x) + bhi(BB), blo(XB.y) + blo(BB), bhi(XB.y) + bhi(BB)}; \
      _Pragma("unroll") for (int i = 0; i < 8; i++) { e[0] += blo(P[i].x); e[1] += bhi(P[i].x); e[2] += blo(P[i].y); e[3] += bhi(P[i].y); \
        e[4] += blo(P[i].z); e[5] += bhi(P[i].z); e[6] += blo(P[i].w); e[7] += bhi(P[i].w); } \
      xw[m][0] = pack(e[0], e[1]); xw[m][1] = pack(e[2], e[3]); xw[m][2] = pack(e[4], e[5]); xw[m][3] = pack(e[6], e[7]); }
#define RPUB(m) stll(fr + XR + (m) * 256, tg(xw[m][0], 0), xw[m][1], xw[m][2], xw[m][3]);
#define RLAST(ptag_, hv) { const uint32_t ptag = ptag_; const uint4* pr = g_P + ((t * 8 + c) * 8 * 28 + warp) * 32 + ln_; uint4 p[8]; uint2 xa, xb; uint32_t ba, bb; \
      if (ptag_) hint_wait(g_H + (t * 8 + c) * 8 + (ln_ & 7), hv); RISSUE(3, p, xa, xb, ba, bb) REDU(3, p, xa, xb, ba, bb) }
#pragma unroll 1
  for (int L = 0; L < 2; L++) {
    const uint32_t tag = 1 - L;
    uint32_t phq[2][2][7];
    const uint32_t hs = 10 * L;
    {
      PTRS
      uint4 a[28];
      const uint4* pa = fm + XR;
      uint32_t fa = 0, fb = 0;
      float r0 = 1.f, r1 = 1.f;
      if (L == 0) {
        hint_post(hme, 1, lane);
        mbar_wait(bempty + 8 * NST, 0);
        MARK(1);
        const int row = warp * 16 + (ln_ & 15);
        const uint32_t xb = sb + 2 * STAGE + row * 128;
        float cs_[4][4] = {};
#pragma unroll
        for (int ks = 0; ks < 28; ks++) { a[ks] = ldsm4(xb + (ks >> 2) * 16384 + (((2 * (ks & 3) + (ln_ >> 4)) ^ (row & 7)) << 4)); mma16816(cs_[ks & 3], a[ks], 0x3F803F80u, 0x3F803F80u); }
        if (c < 7) {
#pragma unroll
          for (int u = 0; u < 4; u++) { const uint4 v = ldsm4(xb + c * 16384 + (((2 * u + (ln_ >> 4)) ^ (row & 7)) << 4)); stll(fm + XR + 128 * c + u * 32, tg(v.x, tag), v.y, v.z, v.w); }
        }
        const float m0 = ((cs_[0][0] + cs_[1][0]) + (cs_[2][0] + cs_[3][0])) * (1.f / 448), m1 = ((cs_[0][2] + cs_[1][2]) + (cs_[2][2] + cs_[3][2])) * (1.f / 448);
        const uint32_t mb0 = pack(m0, m0), mb1 = pack(m1, m1);
        asm volatile("bar.arrive 2, 288;" ::"r"(mb0) : "memory");
#pragma unroll
        for (int ks = 0; ks < 28; ks++) {
          a[ks].x = bsub(a[ks].x, mb0); a[ks].y = bsub(a[ks].y, mb1); a[ks].z = bsub(a[ks].z, mb0); a[ks].w = bsub(a[ks].w, mb1);
        }
        r0 = m0 - blo(mb0); r1 = m1 - blo(mb1);
      } else {
        ll_issue<0, 14>(a, pa, 32);
        if (wg == 0) { RLAST(1u, 10u) xw[3][0] = tg(xw[3][0], 0); RPUB(3) } else { xw[3][0] = xw[3][1] = xw[3][2] = xw[3][3] = 0; }
        MARK(20);
        ll_issue<14, 7>(a, pa, 32);
        ln_stats(xw, sLN, warp, lane, g_S2 + (t * 8 + c) * 8);
      }
      MARK(2 + L * 19);
      float ak[28], av[28], aq[28], pp[28];
#define KVSTAGE(i) { if (L) ll_check<7 * i, 7, false>(a, pa, 32, tag); const uint32_t st = ACQ(i); wg_fence(); \
      _Pragma("unroll") for (int ks = 0; ks < 7; ks++) { const uint4 f = a[7 * i + ks]; \
        wgmma_rs56(ak, f.x, f.y, f.z, f.w, mkdesc(st, ks * 2048, 1024, 1024, 1), i | ks); \
        wgmma_rs56(av, f.x, f.y, f.z, f.w, mkdesc(st, 14336 + ks * 2048, 1024, 1024, 1), i | ks); } \
      wg_commit(); if (i > 0) { wg_wait<1>(); REL(i + 5) } }
      KVSTAGE(0) KVSTAGE(1)
      uint4 sv[1] = {make_uint4(0, 0, 0, 0)};
      const uint4* ps = g_S2 + (t * 8 + warp) * 8 + (ln_ >> 2);
      if (L) { ll_issue<21, 7>(a, pa, 32); ll_issue<0, 1>(sv, ps, 0); }
      else {
        float c0[2][4] = {}, c1[2][4] = {};
#pragma unroll
        for (int ks = 0; ks < 28; ks++) { mma16816(c0[ks & 1], a[ks], a[ks].x, a[ks].z); mma16816(c1[ks & 1], a[ks], a[ks].y, a[ks].w); }
        const int src = (ln_ & 28) | (g >> 1);
        const float q0 = __shfl_sync(~0u, (g & 1) ? c0[0][1] + c0[1][1] : c0[0][0] + c0[1][0], src), q1 = __shfl_sync(~0u, (g & 1) ? c1[0][3] + c1[1][3] : c1[0][2] + c1[1][2], src);
        r0 = rsqrtf(fmaxf(q0 * (1.f / 448) - r0 * r0, 0.f) + 1e-5f); r1 = rsqrtf(fmaxf(q1 * (1.f / 448) - r1 * r1, 0.f) + 1e-5f);
      }
      KVSTAGE(2) KVSTAGE(3)
      if (L) {
        if (wg) asm volatile("bar.sync 9, 160; bar.sync 10, 256;" ::: "memory"); else asm volatile("bar.sync 8, 160;" ::: "memory");
        ll_check<0, 1, false>(sv, ps, 0, 1u);
        const float m0 = -__uint_as_float(sv[0].x), m1 = -__uint_as_float(sv[0].z), h0 = blo(pack(m0, 0.f)), h1 = blo(pack(m1, 0.f));
        r0 = __uint_as_float(sv[0].y); r1 = __uint_as_float(sv[0].w);
        fa = q == 2 ? pack(0.f, h0) : q == 3 ? pack(m0 - h0, h0) : 0u; fb = q == 2 ? pack(0.f, h1) : q == 3 ? pack(m1 - h1, h1) : 0u;
      } else {
        asm volatile("bar.sync 3, 320;" ::: "memory");
      }
      wg_fence();
      wgmma_rs56(ak, fa, fb, 0u, 0u, mkdesc(d16, OFF_CB + 1024, 512, 0, 2), 1);
      wgmma_rs56(av, fa, fb, 0u, 0u, mkdesc(d16, OFF_CB + 2048, 512, 0, 2), 1);
      wg_commit();
      wg_wait<0>(); REL(3) regfence(ak); regfence(av);
      MARK(3 + L * 19);
      phi_gemm(ak, pp, d16 + (OFF_WPHI >> 4), r0, r1);
#pragma unroll
      for (int j = 0; j < 7; j++) {
        const int n = 8 * j + 2 * q, n2 = n < 28 ? n : n + 4;
        sts32(sV + sw128(row0, n2), pack(av[4 * j] * r0, av[4 * j + 1] * r0)); sts32(sV + sw128(row0 + 8, n2), pack(av[4 * j + 2] * r1, av[4 * j + 3] * r1));
      }
      { const int n2 = 28 + 2 * (q & 1) + 32 * (q >> 1); const uint32_t v = (q & 1) ? 0u : 0x3F80u; sts32(sV + sw128(row0, n2), v); sts32(sV + sw128(row0 + 8, n2), v); }
      wg_wait<0>(); regfence(pp);
      hedgehog(pp, [&](int r, int h, int p, uint32_t v) { sts32(sPK + h * 16384 + sw128(row0 + 8 * r, 8 * p + 2 * q), v); }, [] {});
#pragma unroll
      for (int i = 0; i < 4; i++) sts32(sPK + (i & 1) * 16384 + sw128(row0 + 8 * (i >> 1), 56 + 2 * q), 0u);
      fence_async();
      bar_cons();
      MARK(4 + L * 19);
      float kv[16];
      wg_fence();
#pragma unroll
      for (int ks = 0; ks < 8; ks++) wgmma_ss32(kv, mkdesc(d16 + wg * 1024, OFF_PHIK + ks * 2048, 1024, 1024, 1), mkdesc(d16 + wg * 4, OFF_V + ks * 2048, 1024, 1024, 1), ks);
      wg_commit(); wg_wait<0>(); regfence(kv);
      const int ln2 = laneid();
#pragma unroll
      for (int u = 0; u < 4; u++) {
        float e[4];
#pragma unroll
        for (int i = 0; i < 4; i++) e[i] = kv[4 * u + i];
        stll(g_KVP + (c * 16 + t) * 1024 + wg * 512 + u * 128 + (warp & 3) * 32 + ln2, tg(__float_as_uint(e[0]), tag), __float_as_uint(e[1]), __float_as_uint(e[2]), __float_as_uint(e[3]));
      }
      MARK(5 + L * 19);
      uint4 k4[4];
      const uint4* pk = g_KVP + (c * 16 + 4 * (ln2 & 3)) * 1024 + 64 * t + warp * 8 + (ln2 >> 2);
#pragma unroll
      for (int i = 0; i < 2; i++) {
        const uint32_t st = ACQ(4 + i); wg_fence();
#pragma unroll
        for (int ks = 0; ks < 14; ks++) { const uint4 f = a[14 * i + ks]; wgmma_rs56(aq, f.x, f.y, f.z, f.w, mkdesc(st, ks * 2048, 1024, 1024, 1), i | ks); }
        if (i == 1) wgmma_rs56(aq, fa, fb, 0u, 0u, mkdesc(d16, OFF_CB, 512, 0, 2), 1);
        wg_commit();
        if (i == 1) ll_issue<0, 4>(k4, pk, 1024);
      }
      wg_wait<0>(); REL(4) REL(5) regfence(aq);
      phi_gemm(aq, pp, d16 + (OFF_WPHI >> 4), r0, r1);
      bar_cons();
#pragma unroll
      for (int i = 0; i < 4; i++) { sts128(sV + warp * 2048 + (lane + i * 32) * 16, 0, 0, 0, 0); sts128(sPK + warp * 2048 + (lane + i * 32) * 16, L, 0, 0, 0); }
      ll_check<0, 4, false>(k4, pk, 1024, tag);
      float s0 = 0, s1 = 0, s2 = 0, s3 = 0;
#pragma unroll
      for (int i = 0; i < 4; i++) { s0 += __uint_as_float(k4[i].x); s1 += __uint_as_float(k4[i].y); s2 += __uint_as_float(k4[i].z); s3 += __uint_as_float(k4[i].w); }
      s0 = qsum(s0); s1 = qsum(s1); s2 = qsum(s2); s3 = qsum(s3);
      if (q == 0) stll2(g_KVR + c * 1024 + 64 * t + warp * 8 + (ln2 >> 2), tg(pack(s0, s1), tag), pack(s2, s3));
      MARK(6 + L * 19);
      wg_wait<0>(); regfence(pp);
      uint2 r[4];
      const uint2* pr = g_KVR + c * 1024 + wg * 512 + (warp & 3) * 32 + ln2;
      hedgehog(pp, [&](int r, int h, int p, uint32_t v) { phq[r][h][p] = v; }, [&] {
#pragma unroll
        for (int u = 0; u < 4; u++) r[u] = ldll2(pr + u * 128); });
      MARK(7 + L * 19);
#pragma unroll 1
      for (int it = 0; it < SPIN; it++) {
        if (!__any_sync(~0u, ((r[0].x ^ tag) | (r[1].x ^ tag) | (r[2].x ^ tag) | (r[3].x ^ tag)) & 1)) break;
#pragma unroll
        for (int u = 0; u < 4; u++) r[u] = ldll2(pr + u * 128);
      }
#pragma unroll
      for (int u = 0; u < 4; u++) {
        const int d = 8 * u + 2 * q;
        if (d < 28) { sts32(sV + sw128(row0, 28 * wg + d), r[u].x); sts32(sV + sw128(row0 + 8, 28 * wg + d), r[u].y); }
        else if (d == 28) {
#pragma unroll
          for (int j = 0; j < 4; j++) { sts16(sV + sw128(row0, 56 + 2 * j + wg), r[u].x); sts16(sV + sw128(row0 + 8, 56 + 2 * j + wg), r[u].y); }
        }
      }
      fence_async();
      bar_cons();
      MARK(8 + L * 19);
      float o[32];
      wg_fence();
#pragma unroll
      for (int ks = 0; ks < 8; ks++) {
        const int h = ks >> 2, p = 2 * (ks & 3);
        wgmma_rs64(o, phq[0][h][p], phq[1][h][p], p < 6 ? phq[0][h][p < 6 ? p + 1 : 0] : 0u, p < 6 ? phq[1][h][p < 6 ? p + 1 : 0] : 0u, mkdesc(d16, OFF_V + ks * 2048, 1024, 1024, 1), ks);
      }
      wg_commit(); wg_wait<0>(); regfence(o);
      const float iA0 = rcp(o[28] + 1e-6f), iB0 = rcp(o[29] + 1e-6f), iA1 = rcp(o[30] + 1e-6f), iB1 = rcp(o[31] + 1e-6f);
      uint32_t w[14];
      { PTRS
#pragma unroll
      for (int j = 0; j < 7; j++) {
        const bool hb = 8 * j + 2 * q >= 28; const float i0 = hb ? iB0 : iA0, i1 = hb ? iB1 : iA1;
        w[2 * j] = pack(o[4 * j] * i0, o[4 * j + 1] * i0); w[2 * j + 1] = pack(o[4 * j + 2] * i1, o[4 * j + 3] * i1);
        if (j == 0 || ((j ^ c) & 1) == 0) w[2 * j] = tg(w[2 * j], tag);
      }
      slice_store(sf + OO, sh + 2 * OO, w, c & 1);
      hint_post(hme, hs + 2, lane); }
    }
    MARK(9 + L * 19);
    uint4 xr[4];
    if (c < 7) {
      PTRS
      ll_issue<0, 4>(xr, fm + XR + 128 * c, 32);
      uint4 a[28];
      const uint4* pa = fm + OO;
      hint_wait(hrow, hs + 2);
      MARK(10 + L * 19);
      ll_issue<0, 28, true>(a, pa, 32, f2 + 2 * OO);
      float y[32];
      uint32_t st;
#define WOSTEP(i) { ll_check<7 * i, 7, true>(a, pa, 32, tag, f2 + 2 * OO); if (!(i & 1)) st = ACQ(6 + i / 2); wg_fence(); \
      _Pragma("unroll") for (int ks = 0; ks < 7; ks++) { const uint4 f = a[7 * i + ks]; \
        wgmma_rs64(y, f.x, f.y, f.z, f.w, mkdesc(st, ((i & 1) * 7 + ks) * 2048, 1024, 1024, 1), i | ks); } wg_commit(); }
      WOSTEP(0) WOSTEP(1) WOSTEP(2) WOSTEP(3)
      ll_check<0, 4, false>(xr, fm + XR + 128 * c, 32, tag);
      wg_wait<0>(); regfence(y);
      MARK(11 + L * 19);
#pragma unroll
      for (int u = 0; u < 4; u++) {
        xr[u].x = tg(pack(blo(xr[u].x) + y[8 * u], bhi(xr[u].x) + y[8 * u + 1]), tag); xr[u].y = pack(blo(xr[u].y) + y[8 * u + 2], bhi(xr[u].y) + y[8 * u + 3]);
        xr[u].z = pack(blo(xr[u].z) + y[8 * u + 4], bhi(xr[u].z) + y[8 * u + 5]); xr[u].w = pack(blo(xr[u].w) + y[8 * u + 6], bhi(xr[u].w) + y[8 * u + 7]);
        stll(fm + X1 + 128 * c + u * 32, xr[u].x, xr[u].y, xr[u].z, xr[u].w);
      }
      hint_post(hme, hs + 3, lane);
    } else {
      PTRS
      hint_post(hme, hs + 3, lane);
      (void)ACQ(6); (void)ACQ(7);
      hint_wait(hrow, hs + 3);
      ll_issue<0, 4>(xr, fm + X1, 32);
      MARK(10 + L * 19); MARK(11 + L * 19);
    }
    uint32_t hf[56];
    float rr0, rr1;
    {
      PTRS
      uint4 a[28];
      const uint4* pa = fm + X1;
      auto grp = [&](int i) -> const uint4* { const int k = i + c; return pa + ((k >= 7 ? k - 7 : k) - i) * 128; };
      if (c == 7) { ll_issue<4, 12>(a, pa, 32); ll_check<0, 4, false>(xr, pa, 32, tag); }
      else {
#pragma unroll
        for (int u = 4; u < 16; u++) a[u] = make_uint4(0, 0, 0, 0);
      }
#pragma unroll
      for (int u = 0; u < 4; u++) a[u] = xr[u];
      float y[96], z[16];
#define F1STAGE(i) { if (i > 0) ll_check<4 * i, 4, false>(a, grp(i), 32, tag); const uint32_t st = ACQ(8 + i); wg_fence(); \
      _Pragma("unroll") for (int ks = 0; ks < 4; ks++) { const uint4 f = a[4 * i + ks]; \
        wgmma_rs192(y, f.x, f.y, f.z, f.w, mkdesc(st, (ks >> 1) * 12288 + (ks & 1) * 2048, 4096, 1024, 1), i | ks); \
        wgmma_rs32(z, f.x, f.y, f.z, f.w, mkdesc(st, 24576 + ks * 1024, 512, 512, 2), i | ks); } \
      wg_commit(); if (i > 0) { wg_wait<1>(); REL(6 + i) if (i < 4) ll_issue<(i < 4 ? 4 * i + 12 : 0), 4>(a, grp(i + 3), 32); } }
      F1STAGE(0)
      MARK(12 + L * 19);
      if (c < 7) {
        if (L == 0) hint_wait(hrow, hs + 3);
        ll_issue<4, 4>(a, grp(1), 32); ll_issue<8, 4>(a, grp(2), 32); ll_issue<12, 4>(a, grp(3), 32);
        float s0 = 0.f, s1 = 0.f, v0 = 0.f, v1 = 0.f;
#pragma unroll
        for (int u = 0; u < 4; u++) { s0 += (blo(xr[u].x) + bhi(xr[u].x)) + (blo(xr[u].z) + bhi(xr[u].z)); s1 += (blo(xr[u].y) + bhi(xr[u].y)) + (blo(xr[u].w) + bhi(xr[u].w)); }
        s0 = qsum(s0) * (1.f / 64); s1 = qsum(s1) * (1.f / 64);
#pragma unroll
        for (int u = 0; u < 4; u++) {
          const float d0 = blo(xr[u].x) - s0, d1 = bhi(xr[u].x) - s0, d2 = blo(xr[u].z) - s0, d3 = bhi(xr[u].z) - s0;
          const float d4 = blo(xr[u].y) - s1, d5 = bhi(xr[u].y) - s1, d6 = blo(xr[u].w) - s1, d7 = bhi(xr[u].w) - s1;
          v0 += (d0 * d0 + d1 * d1) + (d2 * d2 + d3 * d3); v1 += (d4 * d4 + d5 * d5) + (d6 * d6 + d7 * d7);
        }
        v0 = qsum(v0); v1 = qsum(v1);
        if (q == 0) stll(g_ST + ((t * 8 + warp) * 8 + c) * 8 + (ln_ >> 2), tg(__float_as_uint(s0), tag), __float_as_uint(v0), __float_as_uint(s1), __float_as_uint(v1));
      }
      REL(6)
      F1STAGE(1) MARK(13 + L * 19); F1STAGE(2) F1STAGE(3)
      uint4 sv[2];
      const uint4* ps = g_ST + ((t * 8 + warp) * 8 + 2 * (laneid() & 3)) * 8 + (laneid() >> 2);
      ll_issue<0, 2>(sv, ps, q < 3 ? 8 : 0);
      F1STAGE(4)
      ll_check<0, 2, false>(sv, ps, q < 3 ? 8 : 0, tag);
      const float wb = q < 3 ? 1.f : 0.f;
      const float ma = __uint_as_float(sv[0].x), mb = __uint_as_float(sv[1].x), mc = __uint_as_float(sv[0].z), md = __uint_as_float(sv[1].z);
      const float m0 = qsum(ma + wb * mb) * (1.f / 7), m1 = qsum(mc + wb * md) * (1.f / 7);
      const float v0 = qsum(__uint_as_float(sv[0].y) + 64.f * (ma - m0) * (ma - m0) + wb * (__uint_as_float(sv[1].y) + 64.f * (mb - m0) * (mb - m0)));
      const float v1 = qsum(__uint_as_float(sv[0].w) + 64.f * (mc - m1) * (mc - m1) + wb * (__uint_as_float(sv[1].w) + 64.f * (md - m1) * (md - m1)));
      const float e0 = v0 * (1.f / 448) + 1e-5f, e1 = v1 * (1.f / 448) + 1e-5f;
      rr0 = 1.f / e0; rr1 = 1.f / e1;
      auto fold = [&](float m, float sd) -> uint32_t {
        const float mh = blo(pack(-m, 0.f)), sh_ = blo(pack(sd, 0.f));
        return q == 0 ? pack(mh, -m - mh) : q == 1 ? pack(mh, sh_) : q == 2 ? pack(sd - sh_, 0.f) : 0u;
      };
      const uint32_t fa = fold(m0, sqrtf(e0)), fb = fold(m1, sqrtf(e1));
      if (L == 0) asm volatile("bar.sync 4, 288;" ::: "memory");
      wg_fence();
      wgmma_rs192(y, fa, fb, 0u, 0u, mkdesc(d16, OFF_CB, 512, 0, 2), 1);
      wgmma_rs32(z, fa, fb, 0u, 0u, mkdesc(d16, OFF_CB + 3072, 512, 0, 2), 1);
      F1STAGE(5) F1STAGE(6)
      wg_wait<0>(); REL(13) REL(14) regfence(y); regfence(z);
      MARK(14 + L * 19);
#pragma unroll
      for (int j = 0; j < 56; j++) {
        uint32_t r; asm("cvt.rn.relu.bf16x2.f32 %0, %1, %2;" : "=r"(r) : "f"(j < 48 ? y[j < 48 ? 2 * j + 1 : 0] : z[j < 48 ? 0 : 2 * j - 95]), "f"(j < 48 ? y[j < 48 ? 2 * j : 0] : z[j < 48 ? 0 : 2 * j - 96]));
        asm("mul.bf16x2 %0, %1, %1;" : "=r"(hf[j]) : "r"(r));
      }
    }
    MARK(15 + L * 19);
    {
      PTRS
      float ya[32], yb[32];
      uint4* pp = g_P + ((t * 8 + warp) * 8 + ((c - warp) & 7)) * 28 * 32 + ln_;
#define F2STORE(j, Y) { regfence(Y); _Pragma("unroll") for (int u = 0; u < 4; u++) { \
      const uint32_t w0 = tg(pack(Y[8 * u] * rr0, Y[8 * u + 1] * rr0), tag), w1_ = pack(Y[8 * u + 2] * rr1, Y[8 * u + 3] * rr1), \
                     w2_ = pack(Y[8 * u + 4] * rr0, Y[8 * u + 5] * rr0), w3 = pack(Y[8 * u + 6] * rr1, Y[8 * u + 7] * rr1); \
      if (warp == c) sts128(sPK + (4 * (j) + u) * 512 + ln_ * 16, w0, w1_, w2_, w3); else stll(pp + (4 * (j) + u) * 32, w0, w1_, w2_, w3); } \
      if ((j) >= 5) hint_post(hme, hs + (4 + (j)), lane); }
#define F2PASS(j, Y, Z) { const uint32_t st = ACQ(15 + j); wg_fence(); \
      _Pragma("unroll") for (int ks = 0; ks < 14; ks++) wgmma_rs64(Y, hf[4 * ks], hf[4 * ks + 1], hf[4 * ks + 2], hf[4 * ks + 3], mkdesc(st, ks * 2048, 1024, 1024, 1), ks); \
      wg_commit(); if (j > 0) { wg_wait<1>(); REL(14 + j) F2STORE(j - 1, Z) } }
      const uint4* pr = g_P + ((t * 8 + c) * 8 * 28 + warp) * 32 + ln_;
      uint4 p[8], p2[8]; uint2 xa, xb, xc, xd; uint32_t ba, bb, bc, bd;
      const uint32_t ptag = tag;
      const uint32_t* hred = g_H + (t * 8 + c) * 8 + (ln_ & 7);
      F2PASS(0, ya, yb) F2PASS(1, yb, ya) F2PASS(2, ya, yb) F2PASS(3, yb, ya)
      F2PASS(4, ya, yb)
      RISSUE(0, p, xa, xb, ba, bb)
      F2PASS(5, yb, ya)
      REDU(0, p, xa, xb, ba, bb)
      if (L == 0) { xw[0][0] = tg(xw[0][0], 0); RPUB(0) }
      F2PASS(6, ya, yb)
      RISSUE(1, p, xa, xb, ba, bb)
      wg_wait<0>(); REL(21) F2STORE(6, ya)
      MARK(16 + L * 19);
      if (wg) hint_wait(hred, hs + 9);
      RISSUE(2, p2, xc, xd, bc, bd)
      REDU(1, p, xa, xb, ba, bb)
      if (L == 0) { xw[1][0] = tg(xw[1][0], 0); RPUB(1) }
      MARK(17 + L * 19);
      REDU(2, p2, xc, xd, bc, bd)
      if (L == 0) { xw[2][0] = tg(xw[2][0], 0); RPUB(2) }
    }
    MARK(18 + L * 19);
  }
  {
    PTRS
    uint32_t* op = (uint32_t*)(out + XOFF(ln_));
#define OUT(u) { op[u * 64] = xw[u][0]; op[u * 64 + 1792] = xw[u][1]; op[u * 64 + 4] = xw[u][2]; op[u * 64 + 1796] = xw[u][3]; }
    OUT(0) OUT(1) OUT(2)
    if (wg == 0) { RLAST(0u, 20u) OUT(3) }
    else if (warp == 7) {
      if (t == 0 && lane == 0) g_WQF[c] = 0;
      if (lane < 8) stll(g_S2 + (t * 8 + c) * 8 + lane, 0, 0, 0, 0);
      if (lane < 4) { stll(g_CS + blockIdx.x * 4 + lane, 0, 0, 0, 0); if (blockIdx.x < 68) stll(g_CS + 512 + blockIdx.x * 4 + lane, 0, 0, 0, 0); }
    }
  }
  MARK(38); GT(39);
  }
}

typedef CUresult (*EncFn)(CUtensorMap*, CUtensorMapDataType, cuuint32_t, void*, const cuuint64_t*, const cuuint64_t*, const cuuint32_t*, const cuuint32_t*,
                          CUtensorMapInterleave, CUtensorMapSwizzle, CUtensorMapL2promotion, CUtensorMapFloatOOBfill);

extern "C" void kernel_launch(void* const* d_in, const int* in_sizes, int n_in, void* d_out, int out_size) {
  static EncFn enc = nullptr;
  if (!enc) {
    void* fn = nullptr; cudaDriverEntryPointQueryResult qr;
    cudaGetDriverEntryPoint("cuTensorMapEncodeTiled", &fn, cudaEnableDefault, &qr);
    enc = (EncFn)fn;
    cudaFuncSetAttribute(fused_kernel, cudaFuncAttributeMaxDynamicSharedMemorySize, SMEM_BYTES);
  }
  CUtensorMap mQKV, mWO, mW1, mW1b, mW2, mW2b, mX;
  const cuuint32_t es[3] = {1, 1, 1};
  auto enc2 = [&](CUtensorMap* m, void* p, cuuint64_t cols, cuuint64_t rows, cuuint32_t bc, cuuint32_t br) {
    const cuuint64_t dims[2] = {cols, rows}, str[1] = {cols * 2}; const cuuint32_t box[2] = {bc, br};
    enc(m, CU_TENSOR_MAP_DATA_TYPE_BFLOAT16, 2, p, dims, str, box, es, CU_TENSOR_MAP_INTERLEAVE_NONE,
        bc == 64 ? CU_TENSOR_MAP_SWIZZLE_128B : CU_TENSOR_MAP_SWIZZLE_64B, CU_TENSOR_MAP_L2_PROMOTION_L2_128B, CU_TENSOR_MAP_FLOAT_OOB_FILL_NONE);
  };
  enc2(&mQKV, d_in[1], 1344, 448, 64, 112); enc2(&mWO, d_in[3], 448, 448, 64, 112); enc2(&mW1b, d_in[5], 1792, 448, 32, 32);
  enc2(&mX, d_in[0], 448, 2048, 64, 128);
  enc2(&mW2, d_in[7], 448, 1792, 64, 96); enc2(&mW2b, d_in[7], 448, 1792, 64, 16);
  {
    const cuuint64_t dims[3] = {64, 448, 28}, str[2] = {3584, 128}; const cuuint32_t box[3] = {64, 32, 3};
    enc(&mW1, CU_TENSOR_MAP_DATA_TYPE_BFLOAT16, 3, d_in[5], dims, str, box, es, CU_TENSOR_MAP_INTERLEAVE_NONE, CU_TENSOR_MAP_SWIZZLE_128B,
        CU_TENSOR_MAP_L2_PROMOTION_L2_128B, CU_TENSOR_MAP_FLOAT_OOB_FILL_NONE);
  }
  typedef const __nv_bfloat16* BP;
  fused_kernel<<<128, 384, SMEM_BYTES>>>(mQKV, mWO, mW1, mW1b, mW2, mW2b, mX, (BP)d_in[1], (BP)d_in[2], (BP)d_in[3], (BP)d_in[5], (BP)d_in[6], (BP)d_in[7], (BP)d_in[8],
                                         (__nv_bfloat16*)d_out);
}
```

```cpp
#include <cuda_runtime.h>
#include <cuda_bf16.h>
#include <cuda.h>
#include <stdint.h>

constexpr int NST = 6, STAGE = 28672;
constexpr int OFF_PHIK = NST * STAGE;
constexpr int OFF_V = OFF_PHIK + 32768;
constexpr int OFF_WPHI = OFF_V + 16384;
constexpr int OFF_CB = OFF_WPHI + 7168;
constexpr int OFF_BAR = OFF_CB + 3584;
constexpr int OFF_X = OFF_V - 114688;
constexpr int SMEM_BYTES = OFF_BAR + 16 * NST + 8;
constexpr int FR = 16 * 8 * 28 * 32;
constexpr int SPIN = 1 << 18;

__device__ uint4 g_F[3 * FR];
constexpr int XR = 0, OO = FR, X1 = 2 * FR;
__device__ uint4 g_P[8 * FR];
__device__ uint4 g_ST[16 * 8 * 8 * 8];
__device__ uint4 g_KVP[8 * 16 * 1024];
__device__ uint2 g_KVR[8 * 1024];
__device__ uint4 g_CS[784];
__device__ uint4 g_S2[16 * 8 * 8];
__device__ uint4 g_WQ[8 * 6 * (STAGE / 16)];
__device__ uint32_t g_WQF[8];
__device__ uint32_t g_H[16 * 8 * 8];
#define MARK(i)
#define GT(i)

__device__ __forceinline__ uint32_t s2u(const void* p) { return (uint32_t)__cvta_generic_to_shared(p); }
__device__ __forceinline__ void mbar_init(uint32_t b, uint32_t c) { asm volatile("mbarrier.init.shared::cta.b64 [%0], %1;" ::"r"(b), "r"(c)); }
__device__ __forceinline__ void mbar_expect(uint32_t b, uint32_t tx) { asm volatile("mbarrier.arrive.expect_tx.shared::cta.b64 _, [%0], %1;" ::"r"(b), "r"(tx) : "memory"); }
__device__ __forceinline__ void mbar_arrive(uint32_t b) { asm volatile("mbarrier.arrive.shared::cta.b64 _, [%0];" ::"r"(b) : "memory"); }
__device__ __forceinline__ void mbar_wait(uint32_t b, uint32_t ph) {
  uint32_t ok = 0;
#pragma unroll 1
  for (int it = 0; it < SPIN && !ok; it++)
    asm volatile("{.reg .pred p; mbarrier.try_wait.parity.shared::cta.b64 p,[%1],%2; selp.u32 %0,1,0,p;}" : "=r"(ok) : "r"(b), "r"(ph) : "memory");
}
__device__ __forceinline__ void tma2d(uint32_t dst, const CUtensorMap* m, int c0, int c1, uint32_t bar) {
  asm volatile("cp.async.bulk.tensor.2d.shared::cluster.global.mbarrier::complete_tx::bytes [%0], [%1, {%3, %4}], [%2];"
               ::"r"(dst), "l"(m), "r"(bar), "r"(c0), "r"(c1) : "memory");
}
__device__ __forceinline__ void tma3d(uint32_t dst, const CUtensorMap* m, int c0, int c1, int c2, uint32_t bar) {
  asm volatile("cp.async.bulk.tensor.3d.shared::cluster.global.mbarrier::complete_tx::bytes [%0], [%1, {%3, %4, %5}], [%2];"
               ::"r"(dst), "l"(m), "r"(bar), "r"(c0), "r"(c1), "r"(c2) : "memory");
}
__device__ __forceinline__ void l2pf(const void* p, uint32_t bytes) { asm volatile("cp.async.bulk.prefetch.L2.global [%0], %1;" ::"l"(p), "r"(bytes) : "memory"); }
__device__ __forceinline__ void wg_fence() { asm volatile("wgmma.fence.sync.aligned;" ::: "memory"); }
__device__ __forceinline__ void wg_commit() { asm volatile("wgmma.commit_group.sync.aligned;" ::: "memory"); }
template <int N> __device__ __forceinline__ void wg_wait() { asm volatile("wgmma.wait_group.sync.aligned %0;" ::"n"(N) : "memory"); }
template <int N> __device__ __forceinline__ void regfence(float (&d)[N]) {
#pragma unroll
  for (int i = 0; i < N; i++) asm volatile("" : "+f"(d[i])::"memory");
}
__device__ __forceinline__ void bar_cons() { asm volatile("bar.sync 1, 256;" ::: "memory"); }
__device__ __forceinline__ void fence_async() { asm volatile("fence.proxy.async.shared::cta;" ::: "memory"); }
struct Desc { uint32_t lo, hi; };
__device__ __forceinline__ Desc mkdesc(uint32_t base16, uint32_t off, uint32_t lbo, uint32_t sbo, uint32_t swz) {
  return Desc{base16 + ((off >> 4) | ((lbo >> 4) << 16)), (sbo >> 4) | (swz << 30)};
}
__device__ __forceinline__ uint4 ldll(const uint4* p) {
  uint4 v; asm volatile("ld.relaxed.gpu.global.v4.u32 {%0,%1,%2,%3}, [%4];" : "=r"(v.x), "=r"(v.y), "=r"(v.z), "=r"(v.w) : "l"(p) : "memory"); return v;
}
__device__ __forceinline__ uint2 ldll2(const uint2* p) {
  uint2 v; asm volatile("ld.relaxed.gpu.global.v2.u32 {%0,%1}, [%2];" : "=r"(v.x), "=r"(v.y) : "l"(p) : "memory"); return v;
}
__device__ __forceinline__ void stll(uint4* p, uint32_t x, uint32_t y, uint32_t z, uint32_t w) {
  asm volatile("st.relaxed.gpu.global.v4.u32 [%0], {%1,%2,%3,%4};" ::"l"(p), "r"(x), "r"(y), "r"(z), "r"(w) : "memory");
}
__device__ __forceinline__ void stll2(void* p, uint32_t x, uint32_t y) {
  asm volatile("st.relaxed.gpu.global.v2.u32 [%0], {%1,%2};" ::"l"(p), "r"(x), "r"(y) : "memory");
}
__device__ __forceinline__ int laneid() { int l; asm volatile("mov.u32 %0, %%laneid;" : "=r"(l)); return l; }
__device__ __forceinline__ uint32_t tg(uint32_t w, uint32_t tag) { return (w & ~1u) | tag; }
__device__ __forceinline__ uint32_t pack(float lo, float hi) {
  uint32_t r; asm("cvt.rn.bf16x2.f32 %0, %1, %2;" : "=r"(r) : "f"(hi), "f"(lo)); return r;
}
__device__ __forceinline__ float blo(uint32_t w) { return __uint_as_float(w << 16); }
__device__ __forceinline__ float bhi(uint32_t w) { return __uint_as_float(w & 0xffff0000u); }
__device__ __forceinline__ float ex2(float x) { float r; asm("ex2.approx.ftz.f32 %0, %1;" : "=f"(r) : "f"(x)); return r; }
__device__ __forceinline__ float rcp(float x) { float r; asm("rcp.approx.ftz.f32 %0, %1;" : "=f"(r) : "f"(x)); return r; }
__device__ __forceinline__ float qsum(float v) { v += __shfl_xor_sync(~0u, v, 1); v += __shfl_xor_sync(~0u, v, 2); return v; }
__device__ __forceinline__ void sts32(uint32_t a, uint32_t v) { asm volatile("st.shared.u32 [%0], %1;" ::"r"(a), "r"(v) : "memory"); }
__device__ __forceinline__ void sts16(uint32_t a, uint32_t v) { asm volatile("st.shared.u16 [%0], %1;" ::"r"(a), "h"((uint16_t)v) : "memory"); }
__device__ __forceinline__ void sts128(uint32_t a, uint32_t x, uint32_t y, uint32_t z, uint32_t w) {
  asm volatile("st.shared.v4.u32 [%0], {%1,%2,%3,%4};" ::"r"(a), "r"(x), "r"(y), "r"(z), "r"(w) : "memory");
}
__device__ __forceinline__ uint32_t sw128(int row, int col) { return row * 128 + ((((col >> 3) ^ row) & 7) << 4) + (col & 7) * 2; }

__device__ __forceinline__ void wgmma_rs56(float (&d)[28], const uint32_t a0, const uint32_t a1, const uint32_t a2, const uint32_t a3, Desc db, int sd) {
  asm volatile("{.reg .pred p; .reg .b64 da, db; setp.ne.b32 p, %33, 0; mov.b64 db, {%32, %34};\n wgmma.mma_async.sync.aligned.m64n56k16.f32.bf16.bf16 {%0,%1,%2,%3,%4,%5,%6,%7,%8,%9,%10,%11,%12,%13,%14,%15,%16,%17,%18,%19,%20,%21,%22,%23,%24,%25,%26,%27}, {%28,%29,%30,%31}, db, p, 1, 1, 1;}"
   : "+f"(d[0]),"+f"(d[1]),"+f"(d[2]),"+f"(d[3]),"+f"(d[4]),"+f"(d[5]),"+f"(d[6]),"+f"(d[7]),"+f"(d[8]),"+f"(d[9]),"+f"(d[10]),"+f"(d[11]),"+f"(d[12]),"+f"(d[13]),"+f"(d[14]),"+f"(d[15]),"+f"(d[16]),"+f"(d[17]),"+f"(d[18]),"+f"(d[19]),"+f"(d[20]),"+f"(d[21]),"+f"(d[22]),"+f"(d[23]),"+f"(d[24]),"+f"(d[25]),"+f"(d[26]),"+f"(d[27])
   : "r"(a0),"r"(a1),"r"(a2),"r"(a3),"r"(db.lo),"r"(sd),"r"(db.hi));
}
__device__ __forceinline__ void wgmma_rs64(float (&d)[32], const uint32_t a0, const uint32_t a1, const uint32_t a2, const uint32_t a3, Desc db, int sd) {
  asm volatile("{.reg .pred p; .reg .b64 da, db; setp.ne.b32 p, %37, 0; mov.b64 db, {%36, %38};\n wgmma.mma_async.sync.aligned.m64n64k16.f32.bf16.bf16 {%0,%1,%2,%3,%4,%5,%6,%7,%8,%9,%10,%11,%12,%13,%14,%15,%16,%17,%18,%19,%20,%21,%22,%23,%24,%25,%26,%27,%28,%29,%30,%31}, {%32,%33,%34,%35}, db, p, 1, 1, 1;}"
   : "+f"(d[0]),"+f"(d[1]),"+f"(d[2]),"+f"(d[3]),"+f"(d[4]),"+f"(d[5]),"+f"(d[6]),"+f"(d[7]),"+f"(d[8]),"+f"(d[9]),"+f"(d[10]),"+f"(d[11]),"+f"(d[12]),"+f"(d[13]),"+f"(d[14]),"+f"(d[15]),"+f"(d[16]),"+f"(d[17]),"+f"(d[18]),"+f"(d[19]),"+f"(d[20]),"+f"(d[21]),"+f"(d[22]),"+f"(d[23]),"+f"(d[24]),"+f"(d[25]),"+f"(d[26]),"+f"(d[27]),"+f"(d[28]),"+f"(d[29]),"+f"(d[30]),"+f"(d[31])
   : "r"(a0),"r"(a1),"r"(a2),"r"(a3),"r"(db.lo),"r"(sd),"r"(db.hi));
}
__device__ __forceinline__ void wgmma_rs192(float (&d)[96], const uint32_t a0, const uint32_t a1, const uint32_t a2, const uint32_t a3, Desc db, int sd) {
  asm volatile("{.reg .pred p; .reg .b64 db; setp.ne.b32 p, %101, 0; mov.b64 db, {%100, %102};\n wgmma.mma_async.sync.aligned.m64n192k16.f32.bf16.bf16 {%0,%1,%2,%3,%4,%5,%6,%7,%8,%9,%10,%11,%12,%13,%14,%15,%16,%17,%18,%19,%20,%21,%22,%23,%24,%25,%26,%27,%28,%29,%30,%31,%32,%33,%34,%35,%36,%37,%38,%39,%40,%41,%42,%43,%44,%45,%46,%47,%48,%49,%50,%51,%52,%53,%54,%55,%56,%57,%58,%59,%60,%61,%62,%63,%64,%65,%66,%67,%68,%69,%70,%71,%72,%73,%74,%75,%76,%77,%78,%79,%80,%81,%82,%83,%84,%85,%86,%87,%88,%89,%90,%91,%92,%93,%94,%95}, {%96,%97,%98,%99}, db, p, 1, 1, 1;}"
   : "+f"(d[0]),"+f"(d[1]),"+f"(d[2]),"+f"(d[3]),"+f"(d[4]),"+f"(d[5]),"+f"(d[6]),"+f"(d[7]),"+f"(d[8]),"+f"(d[9]),"+f"(d[10]),"+f"(d[11]),"+f"(d[12]),"+f"(d[13]),"+f"(d[14]),"+f"(d[15]),"+f"(d[16]),"+f"(d[17]),"+f"(d[18]),"+f"(d[19]),"+f"(d[20]),"+f"(d[21]),"+f"(d[22]),"+f"(d[23]),"+f"(d[24]),"+f"(d[25]),"+f"(d[26]),"+f"(d[27]),"+f"(d[28]),"+f"(d[29]),"+f"(d[30]),"+f"(d[31]),"+f"(d[32]),"+f"(d[33]),"+f"(d[34]),"+f"(d[35]),"+f"(d[36]),"+f"(d[37]),"+f"(d[38]),"+f"(d[39]),"+f"(d[40]),"+f"(d[41]),"+f"(d[42]),"+f"(d[43]),"+f"(d[44]),"+f"(d[45]),"+f"(d[46]),"+f"(d[47]),"+f"(d[48]),"+f"(d[49]),"+f"(d[50]),"+f"(d[51]),"+f"(d[52]),"+f"(d[53]),"+f"(d[54]),"+f"(d[55]),"+f"(d[56]),"+f"(d[57]),"+f"(d[58]),"+f"(d[59]),"+f"(d[60]),"+f"(d[61]),"+f"(d[62]),"+f"(d[63]),"+f"(d[64]),"+f"(d[65]),"+f"(d[66]),"+f"(d[67]),"+f"(d[68]),"+f"(d[69]),"+f"(d[70]),"+f"(d[71]),"+f"(d[72]),"+f"(d[73]),"+f"(d[74]),"+f"(d[75]),"+f"(d[76]),"+f"(d[77]),"+f"(d[78]),"+f"(d[79]),"+f"(d[80]),"+f"(d[81]),"+f"(d[82]),"+f"(d[83]),"+f"(d[84]),"+f"(d[85]),"+f"(d[86]),"+f"(d[87]),"+f"(d[88]),"+f"(d[89]),"+f"(d[90]),"+f"(d[91]),"+f"(d[92]),"+f"(d[93]),"+f"(d[94]),"+f"(d[95])
   : "r"(a0),"r"(a1),"r"(a2),"r"(a3),"r"(db.lo),"r"(sd),"r"(db.hi));
}
__device__ __forceinline__ void wgmma_rs32(float (&d)[16], const uint32_t a0, const uint32_t a1, const uint32_t a2, const uint32_t a3, Desc db, int sd) {
  asm volatile("{.reg .pred p; .reg .b64 db; setp.ne.b32 p, %21, 0; mov.b64 db, {%20, %22};\n wgmma.mma_async.sync.aligned.m64n32k16.f32.bf16.bf16 {%0,%1,%2,%3,%4,%5,%6,%7,%8,%9,%10,%11,%12,%13,%14,%15}, {%16,%17,%18,%19}, db, p, 1, 1, 1;}"
   : "+f"(d[0]),"+f"(d[1]),"+f"(d[2]),"+f"(d[3]),"+f"(d[4]),"+f"(d[5]),"+f"(d[6]),"+f"(d[7]),"+f"(d[8]),"+f"(d[9]),"+f"(d[10]),"+f"(d[11]),"+f"(d[12]),"+f"(d[13]),"+f"(d[14]),"+f"(d[15])
   : "r"(a0),"r"(a1),"r"(a2),"r"(a3),"r"(db.lo),"r"(sd),"r"(db.hi));
}
__device__ __forceinline__ void wgmma_ss32(float (&d)[16], Desc da, Desc db, int sd) {
  asm volatile("{.reg .pred p; .reg .b64 da, db; setp.ne.b32 p, %18, 0; mov.b64 da, {%16, %19}; mov.b64 db, {%17, %19};\n wgmma.mma_async.sync.aligned.m64n32k16.f32.bf16.bf16 {%0,%1,%2,%3,%4,%5,%6,%7,%8,%9,%10,%11,%12,%13,%14,%15}, da, db, p, 1, 1, 1, 1;}"
   : "+f"(d[0]),"+f"(d[1]),"+f"(d[2]),"+f"(d[3]),"+f"(d[4]),"+f"(d[5]),"+f"(d[6]),"+f"(d[7]),"+f"(d[8]),"+f"(d[9]),"+f"(d[10]),"+f"(d[11]),"+f"(d[12]),"+f"(d[13]),"+f"(d[14]),"+f"(d[15])
   : "r"(da.lo),"r"(db.lo),"r"(sd),"r"(db.hi));
}

__device__ __forceinline__ uint4 ldsm4(uint32_t a) {
  uint4 v; asm volatile("ldmatrix.sync.aligned.m8n8.x4.shared.b16 {%0,%1,%2,%3}, [%4];" : "=r"(v.x), "=r"(v.y), "=r"(v.z), "=r"(v.w) : "r"(a) : "memory"); return v;
}
__device__ __forceinline__ void mma16816(float (&d)[4], const uint4& a, uint32_t b0, uint32_t b1) {
  asm("mma.sync.aligned.m16n8k16.row.col.f32.bf16.bf16.f32 {%0,%1,%2,%3}, {%4,%5,%6,%7}, {%8,%9}, {%0,%1,%2,%3};"
      : "+f"(d[0]), "+f"(d[1]), "+f"(d[2]), "+f"(d[3]) : "r"(a.x), "r"(a.y), "r"(a.z), "r"(a.w), "r"(b0), "r"(b1));
}
__device__ __forceinline__ uint32_t bsub(uint32_t a, uint32_t b) { uint32_t r; asm("sub.bf16x2 %0, %1, %2;" : "=r"(r) : "r"(a), "r"(b)); return r; }
__device__ __forceinline__ uint32_t hint_ld(const uint32_t* p) { uint32_t v; asm volatile("ld.relaxed.gpu.global.u32 %0, [%1];" : "=r"(v) : "l"(p) : "memory"); return v; }
template <int S, int N, bool SPL = false, int T> __device__ __forceinline__ void ll_issue(uint4 (&v)[T], const uint4* p, int stride, const uint2* p2 = nullptr) {
#pragma unroll
  for (int i = S; i < S + N; i++) {
    if (SPL && i % 7 == 3) { const uint2 lo = ldll2(p2 + i * 64), hi = ldll2(p2 + i * 64 + 32); v[i] = make_uint4(lo.x, lo.y, hi.x, hi.y); }
    else v[i] = ldll(p + i * stride);
  }
}
template <int S, int N, bool SPL, int T> __device__ __forceinline__ void ll_check(uint4 (&v)[T], const uint4* p, int stride, uint32_t tag, const uint2* p2 = nullptr) {
#pragma unroll 1
  for (int it = 0; it < SPIN; it++) {
    uint32_t bad = 0;
#pragma unroll
    for (int i = S; i < S + N; i++) bad |= (v[i].x ^ tag) | ((SPL && i % 7 == 3) ? (v[i].z ^ tag) : 0u);
    if (!__any_sync(~0u, bad & 1)) break;
    ll_issue<S, N, SPL>(v, p, stride, p2);
  }
}
__device__ __forceinline__ void hint_post(uint32_t* p, uint32_t v, int lane) {
  if (lane == 0) asm volatile("st.relaxed.gpu.global.u32 [%0], %1;" ::"l"(p), "r"(v) : "memory");
}
__device__ __forceinline__ void hint_wait(const uint32_t* p, uint32_t s, uint32_t v = 0xffffu) {
#pragma unroll 1
  for (int it = 0; it < SPIN; it++) {
    if (__all_sync(~0u, v - s < 10u)) break;
    v = hint_ld(p);
  }
}
__device__ __forceinline__ void p_issue(uint4 (&v)[8], const uint4* p, uint32_t own) {
  ll_issue<1, 7>(v, p, 896);
  asm volatile("ld.volatile.shared.v4.u32 {%0,%1,%2,%3}, [%4];" : "=r"(v[0].x), "=r"(v[0].y), "=r"(v[0].z), "=r"(v[0].w) : "r"(own) : "memory");
}
__device__ __forceinline__ void p_check(uint4 (&v)[8], const uint4* p, uint32_t own, uint32_t tag) {
#pragma unroll 1
  for (int it = 0; it < SPIN; it++) {
    uint32_t bad = 0;
#pragma unroll
    for (int i = 0; i < 8; i++) bad |= v[i].x ^ tag;
    if (!__any_sync(~0u, bad & 1)) break;
    p_issue(v, p, own);
  }
}
__device__ __forceinline__ void slice_store(uint4* pf, uint2* ph, const uint32_t (&w)[14], bool odd) {
#pragma unroll
  for (int u = 0; u < 3; u++)
    stll(pf + u * 32, odd ? w[4 * u + 2] : w[4 * u], odd ? w[4 * u + 3] : w[4 * u + 1], odd ? w[4 * u + 4] : w[4 * u + 2], odd ? w[4 * u + 5] : w[4 * u + 3]);
  stll2(ph, odd ? w[0] : w[12], odd ? w[1] : w[13]);
}
template <class F, class M> __device__ __forceinline__ void hedgehog(const float (&d)[28], F sink, M mid) {
  const float L2E = 1.4426950408889634f;
#define HX(G, p) ((p) < 6 ? d[((G) & 1) * 16 + ((p) >> 1) * 4 + ((p) & 1) + ((G) & 2)] : d[12 + (G)])
  float mx[4], mn[4], sp[4], sn[4], ep[4][7], en[4][7];
#pragma unroll
  for (int G = 0; G < 4; G++) {
    mx[G] = mn[G] = HX(G, 0);
#pragma unroll
    for (int p = 1; p < 7; p++) { mx[G] = fmaxf(mx[G], HX(G, p)); mn[G] = fminf(mn[G], HX(G, p)); }
  }
#pragma unroll
  for (int o = 1; o < 4; o <<= 1)
#pragma unroll
    for (int G = 0; G < 4; G++) { mx[G] = fmaxf(mx[G], __shfl_xor_sync(~0u, mx[G], o)); mn[G] = fminf(mn[G], __shfl_xor_sync(~0u, mn[G], o)); }
#pragma unroll
  for (int G = 0; G < 4; G++) {
    const float a = -mx[G] * L2E, b = mn[G] * L2E;
#pragma unroll
    for (int p = 0; p < 7; p++) { ep[G][p] = ex2(fmaf(HX(G, p), L2E, a)); en[G][p] = ex2(fmaf(HX(G, p), -L2E, b)); }
    sp[G] = ((ep[G][0] + ep[G][1]) + (ep[G][2] + ep[G][3])) + ((ep[G][4] + ep[G][5]) + ep[G][6]);
    sn[G] = ((en[G][0] + en[G][1]) + (en[G][2] + en[G][3])) + ((en[G][4] + en[G][5]) + en[G][6]);
    if (G == 1) mid();
  }
#pragma unroll
  for (int o = 1; o < 4; o <<= 1)
#pragma unroll
    for (int G = 0; G < 4; G++) { sp[G] += __shfl_xor_sync(~0u, sp[G], o); sn[G] += __shfl_xor_sync(~0u, sn[G], o); }
#pragma unroll
  for (int G = 0; G < 4; G++) {
    const float a = rcp(sp[G]), b = rcp(sn[G]);
#pragma unroll
    for (int p = 0; p < 7; p++) sink(G >> 1, G & 1, p, pack(ep[G][p] * a, en[G][p] * b));
  }
}
__device__ __forceinline__ void phi_gemm(const float (&x)[28], float (&y)[28], uint32_t wphi, float r0, float r1) {
  uint32_t f[14];
#pragma unroll
  for (int j = 0; j < 14; j++) f[j] = pack(x[2 * j] * (j & 1 ? r1 : r0), x[2 * j + 1] * (j & 1 ? r1 : r0));
  wg_fence();
#pragma unroll
  for (int ks = 0; ks < 3; ks++) wgmma_rs56(y, f[4 * ks], f[4 * ks + 1], f[4 * ks + 2], f[4 * ks + 3], mkdesc(wphi, ks * 2048, 1024, 1024, 1), ks);
  wgmma_rs56(y, f[12], f[13], 0u, 0u, mkdesc(wphi, 3 * 2048, 1024, 1024, 1), 1);
  wg_commit();
}
__device__ __forceinline__ void ln_stats(uint32_t (&xw)[4][4], float* sLN, int warp, int lane, uint4* dst) {
  const int g = lane >> 2; const bool full = warp < 4;
  float s0 = 0.f, s1 = 0.f;
#pragma unroll
  for (int u = 0; u < 4; u++) {
    s0 += (blo(xw[u][0]) + bhi(xw[u][0])) + (blo(xw[u][2]) + bhi(xw[u][2]));
    s1 += (blo(xw[u][1]) + bhi(xw[u][1])) + (blo(xw[u][3]) + bhi(xw[u][3]));
  }
  const float rc = full ? 1.f / 64 : 1.f / 48;
  s0 = qsum(s0); s1 = qsum(s1);
  const float a0 = s0 * rc, a1 = s1 * rc;
  float v0 = 0.f, v1 = 0.f;
#pragma unroll
  for (int u = 0; u < 4; u++)
    if (u < 3 || full) {
#pragma unroll
      for (int k = 0; k < 4; k += 2) {
        float a = blo(xw[u][k]) - a0, b = bhi(xw[u][k]) - a0, c2 = blo(xw[u][k + 1]) - a1, d2 = bhi(xw[u][k + 1]) - a1;
        v0 += a * a + b * b; v1 += c2 * c2 + d2 * d2;
      }
    }
  v0 = qsum(v0); v1 = qsum(v1);
  if ((lane & 3) == 0) *(float4*)(sLN + (g * 8 + warp) * 4) = make_float4(s0, v0, s1, v1);
  if (warp < 4) asm volatile("bar.arrive 10, 256;" ::: "memory");
  if (warp) { asm volatile("bar.arrive 7, 256;" ::: "memory"); return; }
  asm volatile("bar.sync 7, 256;" ::: "memory");
  const float4 ea = *(const float4*)(sLN + (g * 8 + (lane & 3)) * 4), eb = *(const float4*)(sLN + (g * 8 + 4 + (lane & 3)) * 4);
  const float m0 = qsum(ea.x + eb.x) * (1.f / 448), m1 = qsum(ea.z + eb.z) * (1.f / 448);
  const float d0 = ea.x * (1.f / 64) - m0, d1 = eb.x * (1.f / 48) - m0, d2 = ea.z * (1.f / 64) - m1, d3 = eb.z * (1.f / 48) - m1;
  v0 = qsum(ea.y + eb.y + 64.f * d0 * d0 + 48.f * d1 * d1); v1 = qsum(ea.w + eb.w + 64.f * d2 * d2 + 48.f * d3 * d3);
  if ((lane & 3) == 0) stll(dst + g, tg(__float_as_uint(m0), 1), __float_as_uint(rsqrtf(v0 * (1.f / 448) + 1e-5f)), __float_as_uint(m1), __float_as_uint(rsqrtf(v1 * (1.f / 448) + 1e-5f)));
}

__global__ void __launch_bounds__(384, 1)
fused_kernel(const __grid_constant__ CUtensorMap mQKV, const __grid_constant__ CUtensorMap mWO, const __grid_constant__ CUtensorMap mW1,
             const __grid_constant__ CUtensorMap mW1b, const __grid_constant__ CUtensorMap mW2, const __grid_constant__ CUtensorMap mW2b,
             const __grid_constant__ CUtensorMap mX, const __nv_bfloat16* __restrict__ wqkv, const __nv_bfloat16* __restrict__ wphi,
             const __nv_bfloat16* __restrict__ wo, const __nv_bfloat16* __restrict__ w1, const __nv_bfloat16* __restrict__ b1,
             const __nv_bfloat16* __restrict__ w2, const __nv_bfloat16* __restrict__ b2, __nv_bfloat16* __restrict__ out) {
  extern __shared__ __align__(1024) uint8_t sm[];
  constexpr uint32_t sb = 1024;
  if (s2u(sm) != sb) __trap();
  const int tid = threadIdx.x, warp = __shfl_sync(~0u, tid >> 5, 0), lane = tid & 31,
            t = blockIdx.x >> 3, c = blockIdx.x & 7;
  const uint32_t bfull = sb + OFF_BAR, bempty = bfull + 8 * NST;

#define XOFF(l) ((t * 128 + c * 16 + ((l) >> 2)) * 448 + warp * 16 + 2 * ((l) & 3))
  if (warp < 8) { MARK(0); GT(19); }
  if (tid == 256) {
    for (int s = 0; s < NST; s++) { mbar_init(bfull + 8 * s, 1); mbar_init(bempty + 8 * s, 8); }
    mbar_init(bempty + 8 * NST, 1);
    asm volatile("fence.mbarrier_init.release.cluster;" ::: "memory");
    fence_async();
    mbar_expect(bempty + 8 * NST, 114688);
    for (int i = 0; i < 7; i++)
      asm volatile("cp.async.bulk.tensor.2d.shared::cluster.global.mbarrier::complete_tx::bytes [%0], [%1, {%3, %4}], [%2];"
                   ::"r"(sb + OFF_X + i * 16384), "l"(&mX), "r"(bempty + 8 * NST), "r"(64 * i), "r"(128 * t) : "memory");
  }
  __syncthreads();
  if (warp >= 8) {
    asm volatile("setmaxnreg.dec.sync.aligned.u32 24;");
    auto issue = [&](int i, int s) {
      const uint32_t dst = sb + s * STAGE, bar = bfull + 8 * s;
      mbar_expect(bar, STAGE);
#pragma unroll 1
      for (int rk = 0; rk < 2; rk++)
      if (i < 4) tma2d(dst + rk * 14336, &mQKV, 448 + 448 * rk + 56 * c, 112 * i, bar);
      else if (i < 8) tma2d(dst + rk * 14336, i < 6 ? &mQKV : &mWO, (i < 6 ? 56 : 64) * c, 224 * (i & 1) + 112 * rk, bar);
      else if (i < 15) { const int k0 = 64 * ((i - 8 + c) % 7) + 32 * rk;
        tma3d(dst + rk * 12288, &mW1, 0, k0, 3 * c, bar); tma2d(dst + 24576 + rk * 2048, &mW1b, 1536 + 32 * c, k0, bar); }
      else { tma2d(dst + rk * 12288, &mW2, 64 * (i - 15), 192 * c + 96 * rk, bar); tma2d(dst + 24576 + rk * 2048, &mW2b, 64 * (i - 15), 1536 + 32 * c + 16 * rk, bar); }
    };
    auto colsum = [&](int job) {
        const int ld4 = job < 112 ? 448 : 336;
        const uint2* wp = (job < 112 ? (const uint2*)w1 + job * 4 : (const uint2*)wqkv + (job - 112) * 4) + (lane >> 2) * ld4 + (lane & 3);
        float s0 = 0.f, s1 = 0.f, s2 = 0.f, s3 = 0.f;
#pragma unroll 8
        for (int i = 0; i < 56; i++) { const uint2 v = __ldg(wp + i * 8 * ld4); s0 += blo(v.x); s1 += bhi(v.x); s2 += blo(v.y); s3 += bhi(v.y); }
#pragma unroll 1
        for (int o = 4; o < 32; o <<= 1) { s0 += __shfl_xor_sync(~0u, s0, o); s1 += __shfl_xor_sync(~0u, s1, o); s2 += __shfl_xor_sync(~0u, s2, o); s3 += __shfl_xor_sync(~0u, s3, o); }
        if (lane < 4) stll(g_CS + job * 4 + lane, tg(__float_as_uint(s0), 1), __float_as_uint(s1), __float_as_uint(s2), __float_as_uint(s3));
      };
    if (warp == 8) {
#pragma unroll 1
      for (int n = 0; n < 44; n++) {
        const int L = n >= 22, i = L ? (n < 28 ? (n - 18) % 6 : n - 22) : n, s = i % 6;
        if (n == 3) asm volatile("bar.sync 2, 288;" ::: "memory");
        mbar_wait(bempty + 8 * s, (i / 6 + (s >= 4 ? L : 0) + 1) & 1);
        if (n == 22) {
          uint32_t v = 0;
#pragma unroll 1
          for (int it = 0; it < SPIN && v < 32; it++) asm volatile("ld.acquire.gpu.global.u32 %0, [%1];" : "=r"(v) : "l"(g_WQF + c) : "memory");
          asm volatile("fence.proxy.async.global;" ::: "memory");
        }
        if (lane == 0) {
          if (n >= 22 && n < 28) {
            mbar_expect(bfull + 8 * s, STAGE);
            asm volatile("cp.async.bulk.shared::cluster.global.mbarrier::complete_tx::bytes [%0], [%1], %2, [%3];"
                         ::"r"(sb + s * STAGE), "l"(g_WQ + c * 10752 + i * (STAGE / 16)), "r"(STAGE), "r"(bfull + 8 * s) : "memory");
          } else issue(i, s);
        }
        __syncwarp();
      }
    } else if (warp == 9) {
      mbar_wait(bfull + 8 * 3, 0);
      if (lane == 0) {
        l2pf((const uint8_t*)wo + blockIdx.x * 3136, 3136);
        l2pf((const uint8_t*)w1 + blockIdx.x * 12544, 12544);
        l2pf((const uint8_t*)w2 + blockIdx.x * 12544, 12544);
      }
      if (blockIdx.x < 112) colsum(blockIdx.x);
      asm volatile("bar.sync 6, 96;" ::: "memory");
#pragma unroll 1
      for (int i = 0; i < 4; i++) {
        const int e = lane < 28 ? lane + 28 * (i & 1) : 0;
        const bool ok = i < 2 || (e < 48 && (e & 15) < 14);
        const int e4 = i < 2 ? (e < 48 ? 48 * c + e : 336 + 8 * c + e) : ok ? 448 + 112 * (e >> 4) + 14 * c + (e & 15) : 448;
        uint4 cv[1];
        ll_issue<0, 1>(cv, g_CS + e4, 0); ll_check<0, 1, false>(cv, g_CS + e4, 0, 1u);
        const uint2 bb = __ldg((const uint2*)b1 + (i < 2 ? e4 : 0));
        const uint32_t h0 = pack(__uint_as_float(cv[0].x), __uint_as_float(cv[0].y)), h1 = pack(__uint_as_float(cv[0].z), __uint_as_float(cv[0].w));
        const uint32_t l0 = pack(__uint_as_float(cv[0].x) - blo(h0), __uint_as_float(cv[0].y) - bhi(h0)), l1 = pack(__uint_as_float(cv[0].z) - blo(h1), __uint_as_float(cv[0].w) - bhi(h1));
#pragma unroll 1
        for (int j = 0; j < (i < 2 ? 5 : 3); j++) {
          const int r = i < 2 ? j : j + 5;
          const uint32_t ad = sb + OFF_CB + (e >> 3) * 512 + r * 64 + ((((e >> 1) ^ (r >> 1)) & 3) << 4) + (e & 1) * 8;
          sts32(ad, j < 2 ? h0 : j == 2 ? l0 : bb.x); sts32(ad + 4, j < 2 ? h1 : j == 2 ? l1 : bb.y);
        }
        if (i & 1) { fence_async(); if (i == 1) asm volatile("bar.arrive 4, 288;" ::: "memory"); else asm volatile("bar.arrive 8, 160; bar.arrive 9, 160;" ::: "memory"); }
      }
    } else if (warp >= 10) {
      const int h = warp - 10;
      uint4 wv[4];
#pragma unroll
      for (int i = 0; i < 4; i++) wv[i] = __ldg((const uint4*)wphi + (2 * c + h) * 98 + min(lane + 32 * i, 97));
#pragma unroll 1
      for (int e = h * 32 + lane; e < 672; e += 64) sts128(sb + OFF_WPHI + e * 16, 0, 0, 0, 0);
      asm volatile("bar.arrive 6, 96;" ::: "memory");
      asm volatile("bar.sync 5, 64;" ::: "memory");
#pragma unroll
      for (int i = 0; i < 4; i++) sts128(sb + OFF_V + h * 2048 + (lane + 32 * i) * 16, wv[i].x, wv[i].y, wv[i].z, wv[i].w);
      __syncwarp();
#pragma unroll 1
      for (int e = lane; e < 392; e += 32) {
        const int d = e / 14, f2 = 2 * (e - 14 * d), k = 28 * h + d;
        const uint32_t v = *(volatile uint32_t*)(sm + OFF_V + h * 2048 + e * 4);
        if (f2 < 24) sts32(sb + OFF_WPHI + sw128(k, 32 * h + f2), v);
        else { sts16(sb + OFF_WPHI + sw128(k, 2 * f2 - 24 + h), v); sts16(sb + OFF_WPHI + sw128(k, 2 * f2 - 22 + h), v >> 16); }
      }
      fence_async();
      asm volatile("bar.arrive 3, 320;" ::: "memory");
      mbar_wait(bfull + 8 * 5, 0);
#pragma unroll 2
      for (int e = t * 672 + h * 32 + lane; e < t * 672 + 672; e += 64) {
        const int r = e >> 3, st = r / 224, rr = r - st * 224, ch = (e & 7) ^ (rr & 7);
        const int k = st < 4 ? 112 * st + (rr >= 112 ? rr - 112 : rr) : 224 * (st - 4) + rr, col = (st < 4 ? (rr >= 112 ? 896 : 448) : 0) + 56 * c + 8 * ch;
        g_WQ[c * 10752 + e] = ch < 7 ? __ldg((const uint4*)(wqkv + k * 1344 + col)) : make_uint4(0, 0, 0, 0);
      }
      __syncwarp();
      if (lane == 0) asm volatile("red.release.gpu.global.add.u32 [%0], 1;" ::"l"(g_WQF + c) : "memory");
      if (h == 0 && blockIdx.x < 84) colsum(112 + blockIdx.x);
    }
  } else {
  asm volatile("setmaxnreg.inc.sync.aligned.u32 240;");

  const int wg = warp >> 2, g = lane >> 2, q = lane & 3;
  const int row0 = warp * 16 + g;
#define PTRS const int ln_ = laneid(); \
  uint4* const fm = g_F + ((t * 8 + warp) * 28) * 32 + ln_;            \
  uint4* const fr = g_F + ((t * 8 + c) * 28 + warp) * 32 + ln_;        \
  uint4* const sf = fm + (7 * (c >> 1) + 4 * (c & 1)) * 32;             \
  uint2* const f2 = (uint2*)(fm - ln_) + ln_;                           \
  uint2* const sh = f2 + (7 * (c >> 1) + 3) * 64 + 32 * (c & 1);        \
  uint32_t* const hme = g_H + (t * 8 + warp) * 8 + c; \
  const uint32_t* const hrow = g_H + (t * 8 + warp) * 8 + (ln_ & 7); \
  (void)fm; (void)fr; (void)sf; (void)f2; (void)sh; (void)hme; (void)hrow;
  float* sLN = (float*)(sm + OFF_V);
  const uint32_t sPK = sb + OFF_PHIK, sV = sb + OFF_V, d16 = (sb & 0x3FFFF) >> 4;
    uint32_t xw[4][4];
#pragma unroll
  for (int i = 0; i < 16; i++) xw[i >> 2][i & 3] = 0;
#define ACQ(I) (mbar_wait(bfull + 8 * ((I) % 6), ((I) / 6 + ((I) % 6 >= 4 ? L : 0)) & 1), d16 + ((I) % 6) * (STAGE >> 4))
#define REL(I) { if (lane == 0) mbar_arrive(bempty + 8 * ((I) % 6)); }
#define RISSUE(m, P, XA, XB, BA, BB) { p_issue(P, pr + (m) * 256, sPK + (8 * (m) + warp) * 512 + ln_ * 16); \
      { const uint4 v_ = ldll(fr + X1 + (m) * 256); XA = make_uint2(v_.x, v_.y); XB = make_uint2(v_.z, v_.w); } \
      const uint32_t* bp = (const uint32_t*)(b2 + 128 * (m) + 16 * warp) + (ln_ & 3); BA = __ldg(bp); BB = __ldg(bp + 4); }
#define REDU(m, P, XA, XB, BA, BB) { p_check(P, pr + (m) * 256, sPK + (8 * (m) + warp) * 512 + ln_ * 16, ptag); \
      float e[8] = {blo(XA.x) + blo(BA), bhi(XA.x) + bhi(BA), blo(XA.y) + blo(BA), bhi(XA.y) + bhi(BA), blo(XB.x) + blo(BB), bhi(XB.x) + bhi(BB), blo(XB.y) + blo(BB), bhi(XB.y) + bhi(BB)}; \
      _Pragma("unroll") for (int i = 0; i < 8; i++) { e[0] += blo(P[i].x); e[1] += bhi(P[i].x); e[2] += blo(P[i].y); e[3] += bhi(P[i].y); \
        e[4] += blo(P[i].z); e[5] += bhi(P[i].z); e[6] += blo(P[i].w); e[7] += bhi(P[i].w); } \
      xw[m][0] = pack(e[0], e[1]); xw[m][1] = pack(e[2], e[3]); xw[m][2] = pack(e[4], e[5]); xw[m][3] = pack(e[6], e[7]); }
#define RPUB(m) stll(fr + XR + (m) * 256, tg(xw[m][0], 0), xw[m][1], xw[m][2], xw[m][3]);
#define RLAST(ptag_, hv) { const uint32_t ptag = ptag_; const uint4* pr = g_P + ((t * 8 + c) * 8 * 28 + warp) * 32 + ln_; uint4 p[8]; uint2 xa, xb; uint32_t ba, bb; \
      if (ptag_) hint_wait(g_H + (t * 8 + c) * 8 + (ln_ & 7), hv); RISSUE(3, p, xa, xb, ba, bb) REDU(3, p, xa, xb, ba, bb) }
#pragma unroll 1
  for (int L = 0; L < 2; L++) {
    const uint32_t tag = 1 - L;
    uint32_t phq[2][2][7];
    const uint32_t hs = 10 * L;
    {
      PTRS
      uint4 a[28];
      const uint4* pa = fm + XR;
      uint32_t fa = 0, fb = 0;
      float r0 = 1.f, r1 = 1.f;
      if (L == 0) {
        hint_post(hme, 1, lane);
        mbar_wait(bempty + 8 * NST, 0);
        MARK(1);
        const int row = warp * 16 + (ln_ & 15);
        const uint32_t xb = sb + OFF_X + row * 128;
        float cs_[4][4] = {};
#pragma unroll
        for (int ks = 0; ks < 28; ks++) { a[ks] = ldsm4(xb + (ks >> 2) * 16384 + (((2 * (ks & 3) + (ln_ >> 4)) ^ (row & 7)) << 4)); mma16816(cs_[ks & 3], a[ks], 0x3F803F80u, 0x3F803F80u); }
        if (c < 7) {
#pragma unroll
          for (int u = 0; u < 4; u++) { const uint4 v = ldsm4(xb + c * 16384 + (((2 * u + (ln_ >> 4)) ^ (row & 7)) << 4)); stll(fm + XR + 128 * c + u * 32, tg(v.x, tag), v.y, v.z, v.w); }
        }
        const float m0 = ((cs_[0][0] + cs_[1][0]) + (cs_[2][0] + cs_[3][0])) * (1.f / 448), m1 = ((cs_[0][2] + cs_[1][2]) + (cs_[2][2] + cs_[3][2])) * (1.f / 448);
        const uint32_t mb0 = pack(m0, m0), mb1 = pack(m1, m1);
        asm volatile("bar.arrive 2, 288;" ::"r"(mb0) : "memory");
#pragma unroll
        for (int ks = 0; ks < 28; ks++) {
          a[ks].x = bsub(a[ks].x, mb0); a[ks].y = bsub(a[ks].y, mb1); a[ks].z = bsub(a[ks].z, mb0); a[ks].w = bsub(a[ks].w, mb1);
        }
        r0 = m0 - blo(mb0); r1 = m1 - blo(mb1);
      } else {
        ll_issue<0, 14>(a, pa, 32);
        if (wg == 0) { RLAST(1u, 10u) xw[3][0] = tg(xw[3][0], 0); RPUB(3) } else { xw[3][0] = xw[3][1] = xw[3][2] = xw[3][3] = 0; }
        MARK(20);
        ll_issue<14, 7>(a, pa, 32);
        ln_stats(xw, sLN, warp, lane, g_S2 + (t * 8 + c) * 8);
      }
      MARK(2 + L * 19);
      float ak[28], av[28], aq[28], pp[28];
#define KVSTAGE(i) { if (L) ll_check<7 * i, 7, false>(a, pa, 32, tag); const uint32_t st = ACQ(i); wg_fence(); \
      _Pragma("unroll") for (int ks = 0; ks < 7; ks++) { const uint4 f = a[7 * i + ks]; \
        wgmma_rs56(ak, f.x, f.y, f.z, f.w, mkdesc(st, ks * 2048, 1024, 1024, 1), i | ks); \
        wgmma_rs56(av, f.x, f.y, f.z, f.w, mkdesc(st, 14336 + ks * 2048, 1024, 1024, 1), i | ks); } \
      wg_commit(); if (i > 0) { wg_wait<1>(); REL(i + 5) } }
      KVSTAGE(0) KVSTAGE(1)
      uint4 sv[1] = {make_uint4(0, 0, 0, 0)};
      const uint4* ps = g_S2 + (t * 8 + warp) * 8 + (ln_ >> 2);
      if (L) { ll_issue<21, 7>(a, pa, 32); ll_issue<0, 1>(sv, ps, 0); }
      else {
        float c0[2][4] = {}, c1[2][4] = {};
#pragma unroll
        for (int ks = 0; ks < 28; ks++) { mma16816(c0[ks & 1], a[ks], a[ks].x, a[ks].z); mma16816(c1[ks & 1], a[ks], a[ks].y, a[ks].w); }
        const int src = (ln_ & 28) | (g >> 1);
        const float q0 = __shfl_sync(~0u, (g & 1) ? c0[0][1] + c0[1][1] : c0[0][0] + c0[1][0], src), q1 = __shfl_sync(~0u, (g & 1) ? c1[0][3] + c1[1][3] : c1[0][2] + c1[1][2], src);
        r0 = rsqrtf(fmaxf(q0 * (1.f / 448) - r0 * r0, 0.f) + 1e-5f); r1 = rsqrtf(fmaxf(q1 * (1.f / 448) - r1 * r1, 0.f) + 1e-5f);
      }
      KVSTAGE(2) KVSTAGE(3)
      if (L) {
        if (wg) asm volatile("bar.sync 9, 160; bar.sync 10, 256;" ::: "memory"); else asm volatile("bar.sync 8, 160;" ::: "memory");
        ll_check<0, 1, false>(sv, ps, 0, 1u);
        const float m0 = -__uint_as_float(sv[0].x), m1 = -__uint_as_float(sv[0].z), h0 = blo(pack(m0, 0.f)), h1 = blo(pack(m1, 0.f));
        r0 = __uint_as_float(sv[0].y); r1 = __uint_as_float(sv[0].w);
        fa = q == 2 ? pack(0.f, h0) : q == 3 ? pack(m0 - h0, h0) : 0u; fb = q == 2 ? pack(0.f, h1) : q == 3 ? pack(m1 - h1, h1) : 0u;
      } else {
        asm volatile("bar.sync 3, 320;" ::: "memory");
      }
      wg_fence();
      wgmma_rs56(ak, fa, fb, 0u, 0u, mkdesc(d16, OFF_CB + 1024, 512, 0, 2), 1);
      wgmma_rs56(av, fa, fb, 0u, 0u, mkdesc(d16, OFF_CB + 2048, 512, 0, 2), 1);
      wg_commit();
      wg_wait<0>(); REL(3) regfence(ak); regfence(av);
      MARK(3 + L * 19);
      phi_gemm(ak, pp, d16 + (OFF_WPHI >> 4), r0, r1);
#pragma unroll
      for (int j = 0; j < 7; j++) {
        const int n = 8 * j + 2 * q, n2 = n < 28 ? n : n + 4;
        sts32(sV + sw128(row0, n2), pack(av[4 * j] * r0, av[4 * j + 1] * r0)); sts32(sV + sw128(row0 + 8, n2), pack(av[4 * j + 2] * r1, av[4 * j + 3] * r1));
      }
      { const int n2 = 28 + 2 * (q & 1) + 32 * (q >> 1); const uint32_t v = (q & 1) ? 0u : 0x3F80u; sts32(sV + sw128(row0, n2), v); sts32(sV + sw128(row0 + 8, n2), v); }
      wg_wait<0>(); regfence(pp);
      hedgehog(pp, [&](int r, int h, int p, uint32_t v) { sts32(sPK + h * 16384 + sw128(row0 + 8 * r, 8 * p + 2 * q), v); }, [] {});
#pragma unroll
      for (int i = 0; i < 4; i++) sts32(sPK + (i & 1) * 16384 + sw128(row0 + 8 * (i >> 1), 56 + 2 * q), 0u);
      fence_async();
      bar_cons();
      MARK(4 + L * 19);
      float kv[16];
      wg_fence();
#pragma unroll
      for (int ks = 0; ks < 8; ks++) wgmma_ss32(kv, mkdesc(d16 + wg * 1024, OFF_PHIK + ks * 2048, 1024, 1024, 1), mkdesc(d16 + wg * 4, OFF_V + ks * 2048, 1024, 1024, 1), ks);
      wg_commit(); wg_wait<0>(); regfence(kv);
      const int ln2 = laneid();
#pragma unroll
      for (int u = 0; u < 4; u++) {
        float e[4];
#pragma unroll
        for (int i = 0; i < 4; i++) e[i] = kv[4 * u + i];
        stll(g_KVP + (c * 16 + t) * 1024 + wg * 512 + u * 128 + (warp & 3) * 32 + ln2, tg(__float_as_uint(e[0]), tag), __float_as_uint(e[1]), __float_as_uint(e[2]), __float_as_uint(e[3]));
      }
      MARK(5 + L * 19);
      uint4 k4[4];
      const uint4* pk = g_KVP + (c * 16 + 4 * (ln2 & 3)) * 1024 + 64 * t + warp * 8 + (ln2 >> 2);
#pragma unroll
      for (int i = 0; i < 2; i++) {
        const uint32_t st = ACQ(4 + i); wg_fence();
#pragma unroll
        for (int ks = 0; ks < 14; ks++) { const uint4 f = a[14 * i + ks]; wgmma_rs56(aq, f.x, f.y, f.z, f.w, mkdesc(st, ks * 2048, 1024, 1024, 1), i | ks); }
        if (i == 1) wgmma_rs56(aq, fa, fb, 0u, 0u, mkdesc(d16, OFF_CB, 512, 0, 2), 1);
        wg_commit();
        if (i == 1) ll_issue<0, 4>(k4, pk, 1024);
      }
      wg_wait<0>(); REL(4) REL(5) regfence(aq);
      phi_gemm(aq, pp, d16 + (OFF_WPHI >> 4), r0, r1);
      bar_cons();
#pragma unroll
      for (int i = 0; i < 4; i++) { sts128(sV + warp * 2048 + (lane + i * 32) * 16, 0, 0, 0, 0); sts128(sPK + warp * 2048 + (lane + i * 32) * 16, L, 0, 0, 0); }
      ll_check<0, 4, false>(k4, pk, 1024, tag);
      float s0 = 0, s1 = 0, s2 = 0, s3 = 0;
#pragma unroll
      for (int i = 0; i < 4; i++) { s0 += __uint_as_float(k4[i].x); s1 += __uint_as_float(k4[i].y); s2 += __uint_as_float(k4[i].z); s3 += __uint_as_float(k4[i].w); }
      s0 = qsum(s0); s1 = qsum(s1); s2 = qsum(s2); s3 = qsum(s3);
      if (q == 0) stll2(g_KVR + c * 1024 + 64 * t + warp * 8 + (ln2 >> 2), tg(pack(s0, s1), tag), pack(s2, s3));
      MARK(6 + L * 19);
      wg_wait<0>(); regfence(pp);
      uint2 r[4];
      const uint2* pr = g_KVR + c * 1024 + wg * 512 + (warp & 3) * 32 + ln2;
      hedgehog(pp, [&](int r, int h, int p, uint32_t v) { phq[r][h][p] = v; }, [&] {
#pragma unroll
        for (int u = 0; u < 4; u++) r[u] = ldll2(pr + u * 128); });
      MARK(7 + L * 19);
#pragma unroll 1
      for (int it = 0; it < SPIN; it++) {
        if (!__any_sync(~0u, ((r[0].x ^ tag) | (r[1].x ^ tag) | (r[2].x ^ tag) | (r[3].x ^ tag)) & 1)) break;
#pragma unroll
        for (int u = 0; u < 4; u++) r[u] = ldll2(pr + u * 128);
      }
#pragma unroll
      for (int u = 0; u < 4; u++) {
        const int d = 8 * u + 2 * q;
        if (d < 28) { sts32(sV + sw128(row0, 28 * wg + d), r[u].x); sts32(sV + sw128(row0 + 8, 28 * wg + d), r[u].y); }
        else if (d == 28) {
#pragma unroll
          for (int j = 0; j < 4; j++) { sts16(sV + sw128(row0, 56 + 2 * j + wg), r[u].x); sts16(sV + sw128(row0 + 8, 56 + 2 * j + wg), r[u].y); }
        }
      }
      fence_async();
      bar_cons();
      MARK(8 + L * 19);
      float o[32];
      wg_fence();
#pragma unroll
      for (int ks = 0; ks < 8; ks++) {
        const int h = ks >> 2, p = 2 * (ks & 3);
        wgmma_rs64(o, phq[0][h][p], phq[1][h][p], p < 6 ? phq[0][h][p < 6 ? p + 1 : 0] : 0u, p < 6 ? phq[1][h][p < 6 ? p + 1 : 0] : 0u, mkdesc(d16, OFF_V + ks * 2048, 1024, 1024, 1), ks);
      }
      wg_commit(); wg_wait<0>(); regfence(o);
      const float iA0 = rcp(o[28] + 1e-6f), iB0 = rcp(o[29] + 1e-6f), iA1 = rcp(o[30] + 1e-6f), iB1 = rcp(o[31] + 1e-6f);
      uint32_t w[14];
      { PTRS
#pragma unroll
      for (int j = 0; j < 7; j++) {
        const bool hb = 8 * j + 2 * q >= 28; const float i0 = hb ? iB0 : iA0, i1 = hb ? iB1 : iA1;
        w[2 * j] = pack(o[4 * j] * i0, o[4 * j + 1] * i0); w[2 * j + 1] = pack(o[4 * j + 2] * i1, o[4 * j + 3] * i1);
        if (j == 0 || ((j ^ c) & 1) == 0) w[2 * j] = tg(w[2 * j], tag);
      }
      slice_store(sf + OO, sh + 2 * OO, w, c & 1);
      hint_post(hme, hs + 2, lane); }
    }
    MARK(9 + L * 19);
    uint4 xr[4];
    if (c < 7) {
      PTRS
      ll_issue<0, 4>(xr, fm + XR + 128 * c, 32);
      uint4 a[28];
      const uint4* pa = fm + OO;
      hint_wait(hrow, hs + 2);
      MARK(10 + L * 19);
      ll_issue<0, 28, true>(a, pa, 32, f2 + 2 * OO);
      float y[32];
      uint32_t st;
#define WOSTEP(i) { ll_check<7 * i, 7, true>(a, pa, 32, tag, f2 + 2 * OO); if (!(i & 1)) st = ACQ(6 + i / 2); wg_fence(); \
      _Pragma("unroll") for (int ks = 0; ks < 7; ks++) { const uint4 f = a[7 * i + ks]; \
        wgmma_rs64(y, f.x, f.y, f.z, f.w, mkdesc(st, ((i & 1) * 7 + ks) * 2048, 1024, 1024, 1), i | ks); } wg_commit(); }
      WOSTEP(0) WOSTEP(1) WOSTEP(2) WOSTEP(3)
      ll_check<0, 4, false>(xr, fm + XR + 128 * c, 32, tag);
      wg_wait<0>(); regfence(y);
      MARK(11 + L * 19);
#pragma unroll
      for (int u = 0; u < 4; u++) {
        xr[u].x = tg(pack(blo(xr[u].x) + y[8 * u], bhi(xr[u].x) + y[8 * u + 1]), tag); xr[u].y = pack(blo(xr[u].y) + y[8 * u + 2], bhi(xr[u].y) + y[8 * u + 3]);
        xr[u].z = pack(blo(xr[u].z) + y[8 * u + 4], bhi(xr[u].z) + y[8 * u + 5]); xr[u].w = pack(blo(xr[u].w) + y[8 * u + 6], bhi(xr[u].w) + y[8 * u + 7]);
        stll(fm + X1 + 128 * c + u * 32, xr[u].x, xr[u].y, xr[u].z, xr[u].w);
      }
      hint_post(hme, hs + 3, lane);
    } else {
      PTRS
      hint_post(hme, hs + 3, lane);
      (void)ACQ(6); (void)ACQ(7);
      hint_wait(hrow, hs + 3);
      ll_issue<0, 4>(xr, fm + X1, 32);
      MARK(10 + L * 19); MARK(11 + L * 19);
    }
    uint32_t hf[56];
    float rr0, rr1;
    {
      PTRS
      uint4 a[28];
      const uint4* pa = fm + X1;
      auto grp = [&](int i) -> const uint4* { const int k = i + c; return pa + ((k >= 7 ? k - 7 : k) - i) * 128; };
      if (c == 7) { ll_issue<4, 12>(a, pa, 32); ll_check<0, 4, false>(xr, pa, 32, tag); }
      else {
#pragma unroll
        for (int u = 4; u < 16; u++) a[u] = make_uint4(0, 0, 0, 0);
      }
#pragma unroll
      for (int u = 0; u < 4; u++) a[u] = xr[u];
      float y[96], z[16];
#define F1STAGE(i) { if (i > 0) ll_check<4 * i, 4, false>(a, grp(i), 32, tag); const uint32_t st = ACQ(8 + i); wg_fence(); \
      _Pragma("unroll") for (int ks = 0; ks < 4; ks++) { const uint4 f = a[4 * i + ks]; \
        wgmma_rs192(y, f.x, f.y, f.z, f.w, mkdesc(st, (ks >> 1) * 12288 + (ks & 1) * 2048, 4096, 1024, 1), i | ks); \
        wgmma_rs32(z, f.x, f.y, f.z, f.w, mkdesc(st, 24576 + ks * 1024, 512, 512, 2), i | ks); } \
      wg_commit(); if (i > 0) { wg_wait<1>(); REL(6 + i) if (i < 4) ll_issue<(i < 4 ? 4 * i + 12 : 0), 4>(a, grp(i + 3), 32); } }
      F1STAGE(0)
      MARK(12 + L * 19);
      if (c < 7) {
        if (L == 0) hint_wait(hrow, hs + 3);
        ll_issue<4, 4>(a, grp(1), 32); ll_issue<8, 4>(a, grp(2), 32); ll_issue<12, 4>(a, grp(3), 32);
        float s0 = 0.f, s1 = 0.f, v0 = 0.f, v1 = 0.f;
#pragma unroll
        for (int u = 0; u < 4; u++) { s0 += (blo(xr[u].x) + bhi(xr[u].x)) + (blo(xr[u].z) + bhi(xr[u].z)); s1 += (blo(xr[u].y) + bhi(xr[u].y)) + (blo(xr[u].w) + bhi(xr[u].w)); }
        s0 = qsum(s0) * (1.f / 64); s1 = qsum(s1) * (1.f / 64);
#pragma unroll
        for (int u = 0; u < 4; u++) {
          const float d0 = blo(xr[u].x) - s0, d1 = bhi(xr[u].x) - s0, d2 = blo(xr[u].z) - s0, d3 = bhi(xr[u].z) - s0;
          const float d4 = blo(xr[u].y) - s1, d5 = bhi(xr[u].y) - s1, d6 = blo(xr[u].w) - s1, d7 = bhi(xr[u].w) - s1;
          v0 += (d0 * d0 + d1 * d1) + (d2 * d2 + d3 * d3); v1 += (d4 * d4 + d5 * d5) + (d6 * d6 + d7 * d7);
        }
        v0 = qsum(v0); v1 = qsum(v1);
        if (q == 0) stll(g_ST + ((t * 8 + warp) * 8 + c) * 8 + (ln_ >> 2), tg(__float_as_uint(s0), tag), __float_as_uint(v0), __float_as_uint(s1), __float_as_uint(v1));
      }
      REL(6)
      F1STAGE(1) MARK(13 + L * 19); F1STAGE(2) F1STAGE(3)
      uint4 sv[2];
      const uint4* ps = g_ST + ((t * 8 + warp) * 8 + 2 * (laneid() & 3)) * 8 + (laneid() >> 2);
      ll_issue<0, 2>(sv, ps, q < 3 ? 8 : 0);
      F1STAGE(4)
      ll_check<0, 2, false>(sv, ps, q < 3 ? 8 : 0, tag);
      const float wb = q < 3 ? 1.f : 0.f;
      const float ma = __uint_as_float(sv[0].x), mb = __uint_as_float(sv[1].x), mc = __uint_as_float(sv[0].z), md = __uint_as_float(sv[1].z);
      const float m0 = qsum(ma + wb * mb) * (1.f / 7), m1 = qsum(mc + wb * md) * (1.f / 7);
      const float v0 = qsum(__uint_as_float(sv[0].y) + 64.f * (ma - m0) * (ma - m0) + wb * (__uint_as_float(sv[1].y) + 64.f * (mb - m0) * (mb - m0)));
      const float v1 = qsum(__uint_as_float(sv[0].w) + 64.f * (mc - m1) * (mc - m1) + wb * (__uint_as_float(sv[1].w) + 64.f * (md - m1) * (md - m1)));
      const float e0 = v0 * (1.f / 448) + 1e-5f, e1 = v1 * (1.f / 448) + 1e-5f;
      rr0 = 1.f / e0; rr1 = 1.f / e1;
      auto fold = [&](float m, float sd) -> uint32_t {
        const float mh = blo(pack(-m, 0.f)), sh_ = blo(pack(sd, 0.f));
        return q == 0 ? pack(mh, -m - mh) : q == 1 ? pack(mh, sh_) : q == 2 ? pack(sd - sh_, 0.f) : 0u;
      };
      const uint32_t fa = fold(m0, sqrtf(e0)), fb = fold(m1, sqrtf(e1));
      if (L == 0) asm volatile("bar.sync 4, 288;" ::: "memory");
      wg_fence();
      wgmma_rs192(y, fa, fb, 0u, 0u, mkdesc(d16, OFF_CB, 512, 0, 2), 1);
      wgmma_rs32(z, fa, fb, 0u, 0u, mkdesc(d16, OFF_CB + 3072, 512, 0, 2), 1);
      F1STAGE(5) F1STAGE(6)
      wg_wait<0>(); REL(13) REL(14) regfence(y); regfence(z);
      MARK(14 + L * 19);
#pragma unroll
      for (int j = 0; j < 56; j++) {
        uint32_t r; asm("cvt.rn.relu.bf16x2.f32 %0, %1, %2;" : "=r"(r) : "f"(j < 48 ? y[j < 48 ? 2 * j + 1 : 0] : z[j < 48 ? 0 : 2 * j - 95]), "f"(j < 48 ? y[j < 48 ? 2 * j : 0] : z[j < 48 ? 0 : 2 * j - 96]));
        asm("mul.bf16x2 %0, %1, %1;" : "=r"(hf[j]) : "r"(r));
      }
    }
    MARK(15 + L * 19);
    {
      PTRS
      float ya[32], yb[32];
      uint4* pp = g_P + ((t * 8 + warp) * 8 + ((c - warp) & 7)) * 28 * 32 + ln_;
#define F2STORE(j, Y) { regfence(Y); _Pragma("unroll") for (int u = 0; u < 4; u++) { \
      const uint32_t w0 = tg(pack(Y[8 * u] * rr0, Y[8 * u + 1] * rr0), tag), w1_ = pack(Y[8 * u + 2] * rr1, Y[8 * u + 3] * rr1), \
                     w2_ = pack(Y[8 * u + 4] * rr0, Y[8 * u + 5] * rr0), w3 = pack(Y[8 * u + 6] * rr1, Y[8 * u + 7] * rr1); \
      if (warp == c) sts128(sPK + (4 * (j) + u) * 512 + ln_ * 16, w0, w1_, w2_, w3); else stll(pp + (4 * (j) + u) * 32, w0, w1_, w2_, w3); } \
      if ((j) >= 5) hint_post(hme, hs + (4 + (j)), lane); }
#define F2PASS(j, Y, Z) { const uint32_t st = ACQ(15 + j); wg_fence(); \
      _Pragma("unroll") for (int ks = 0; ks < 14; ks++) wgmma_rs64(Y, hf[4 * ks], hf[4 * ks + 1], hf[4 * ks + 2], hf[4 * ks + 3], mkdesc(st, ks * 2048, 1024, 1024, 1), ks); \
      wg_commit(); if (j > 0) { wg_wait<1>(); REL(14 + j) F2STORE(j - 1, Z) } }
      const uint4* pr = g_P + ((t * 8 + c) * 8 * 28 + warp) * 32 + ln_;
      uint4 p[8], p2[8]; uint2 xa, xb, xc, xd; uint32_t ba, bb, bc, bd;
      const uint32_t ptag = tag;
      const uint32_t* hred = g_H + (t * 8 + c) * 8 + (ln_ & 7);
      F2PASS(0, ya, yb) F2PASS(1, yb, ya) F2PASS(2, ya, yb) F2PASS(3, yb, ya)
      F2PASS(4, ya, yb)
      RISSUE(0, p, xa, xb, ba, bb)
      F2PASS(5, yb, ya)
      REDU(0, p, xa, xb, ba, bb)
      if (L == 0) { xw[0][0] = tg(xw[0][0], 0); RPUB(0) }
      F2PASS(6, ya, yb)
      RISSUE(1, p, xa, xb, ba, bb)
      wg_wait<0>(); REL(21) F2STORE(6, ya)
      MARK(16 + L * 19);
      if (wg) hint_wait(hred, hs + 9);
      RISSUE(2, p2, xc, xd, bc, bd)
      REDU(1, p, xa, xb, ba, bb)
      if (L == 0) { xw[1][0] = tg(xw[1][0], 0); RPUB(1) }
      MARK(17 + L * 19);
      REDU(2, p2, xc, xd, bc, bd)
      if (L == 0) { xw[2][0] = tg(xw[2][0], 0); RPUB(2) }
    }
    MARK(18 + L * 19);
  }
  {
    PTRS
    uint32_t* op = (uint32_t*)(out + XOFF(ln_));
#define OUT(u) { op[u * 64] = xw[u][0]; op[u * 64 + 1792] = xw[u][1]; op[u * 64 + 4] = xw[u][2]; op[u * 64 + 1796] = xw[u][3]; }
    OUT(0) OUT(1) OUT(2)
    if (wg == 0) { RLAST(0u, 20u) OUT(3) }
    else if (warp == 7) {
      if (t == 0 && lane == 0) g_WQF[c] = 0;
      if (lane < 8) stll(g_S2 + (t * 8 + c) * 8 + lane, 0, 0, 0, 0);
      if (lane < 4) { stll(g_CS + blockIdx.x * 4 + lane, 0, 0, 0, 0); if (blockIdx.x < 68) stll(g_CS + 512 + blockIdx.x * 4 + lane, 0, 0, 0, 0); }
    }
  }
  MARK(38); GT(39);
  }
}

typedef CUresult (*EncFn)(CUtensorMap*, CUtensorMapDataType, cuuint32_t, void*, const cuuint64_t*, const cuuint64_t*, const cuuint32_t*, const cuuint32_t*,
                          CUtensorMapInterleave, CUtensorMapSwizzle, CUtensorMapL2promotion, CUtensorMapFloatOOBfill);

extern "C" void kernel_launch(void* const* d_in, const int* in_sizes, int n_in, void* d_out, int out_size) {
  static EncFn enc = nullptr;
  if (!enc) {
    void* fn = nullptr; cudaDriverEntryPointQueryResult qr;
    cudaGetDriverEntryPoint("cuTensorMapEncodeTiled", &fn, cudaEnableDefault, &qr);
    enc = (EncFn)fn;
    cudaFuncSetAttribute(fused_kernel, cudaFuncAttributeMaxDynamicSharedMemorySize, SMEM_BYTES);
  }
  CUtensorMap mQKV, mWO, mW1, mW1b, mW2, mW2b, mX;
  const cuuint32_t es[3] = {1, 1, 1};
  auto enc2 = [&](CUtensorMap* m, void* p, cuuint64_t cols, cuuint64_t rows, cuuint32_t bc, cuuint32_t br) {
    const cuuint64_t dims[2] = {cols, rows}, str[1] = {cols * 2}; const cuuint32_t box[2] = {bc, br};
    enc(m, CU_TENSOR_MAP_DATA_TYPE_BFLOAT16, 2, p, dims, str, box, es, CU_TENSOR_MAP_INTERLEAVE_NONE,
        bc == 64 ? CU_TENSOR_MAP_SWIZZLE_128B : CU_TENSOR_MAP_SWIZZLE_64B, CU_TENSOR_MAP_L2_PROMOTION_L2_128B, CU_TENSOR_MAP_FLOAT_OOB_FILL_NONE);
  };
  enc2(&mQKV, d_in[1], 1344, 448, 64, 112); enc2(&mWO, d_in[3], 448, 448, 64, 112); enc2(&mW1b, d_in[5], 1792, 448, 32, 32);
  enc2(&mX, d_in[0], 448, 2048, 64, 128);
  enc2(&mW2, d_in[7], 448, 1792, 64, 96); enc2(&mW2b, d_in[7], 448, 1792, 64, 16);
  {
    const cuuint64_t dims[3] = {64, 448, 28}, str[2] = {3584, 128}; const cuuint32_t box[3] = {64, 32, 3};
    enc(&mW1, CU_TENSOR_MAP_DATA_TYPE_BFLOAT16, 3, d_in[5], dims, str, box, es, CU_TENSOR_MAP_INTERLEAVE_NONE, CU_TENSOR_MAP_SWIZZLE_128B,
        CU_TENSOR_MAP_L2_PROMOTION_L2_128B, CU_TENSOR_MAP_FLOAT_OOB_FILL_NONE);
  }
  typedef const __nv_bfloat16* BP;
  fused_kernel<<<128, 384, SMEM_BYTES>>>(mQKV, mWO, mW1, mW1b, mW2, mW2b, mX, (BP)d_in[1], (BP)d_in[2], (BP)d_in[3], (BP)d_in[5], (BP)d_in[6], (BP)d_in[7], (BP)d_in[8],
                                         (__nv_bfloat16*)d_out);
}
```

```cpp
#include <cuda_runtime.h>
#include <cuda_bf16.h>
#include <cuda.h>
#include <stdint.h>

constexpr int NST = 6, STAGE = 28672;
constexpr int OFF_PHIK = NST * STAGE;
constexpr int OFF_V = OFF_PHIK + 32768;
constexpr int OFF_WPHI = OFF_V + 16384;
constexpr int OFF_CB = OFF_WPHI + 7168;
constexpr int OFF_BAR = OFF_CB + 3584;
constexpr int OFF_X = OFF_V - 114688;
constexpr int SMEM_BYTES = OFF_BAR + 16 * NST + 8;
constexpr int FR = 16 * 8 * 28 * 32;
constexpr int SPIN = 1 << 18;

__device__ uint4 g_F[3 * FR];
constexpr int XR = 0, OO = FR, X1 = 2 * FR;
__device__ uint4 g_P[8 * FR];
__device__ uint4 g_ST[16 * 8 * 8 * 8];
__device__ uint4 g_KVP[8 * 16 * 1024];
__device__ uint2 g_KVR[8 * 1024];
__device__ uint4 g_CS[784];
__device__ uint4 g_S2[16 * 8 * 8];
__device__ uint4 g_WQ[8 * 6 * (STAGE / 16)];
__device__ uint32_t g_WQF[8];
__device__ uint32_t g_H[16 * 8 * 8];
#define MARK(i)
#define GT(i)

__device__ __forceinline__ uint32_t s2u(const void* p) { return (uint32_t)__cvta_generic_to_shared(p); }
__device__ __forceinline__ void mbar_init(uint32_t b, uint32_t c) { asm volatile("mbarrier.init.shared::cta.b64 [%0], %1;" ::"r"(b), "r"(c)); }
__device__ __forceinline__ void mbar_expect(uint32_t b, uint32_t tx) { asm volatile("mbarrier.arrive.expect_tx.shared::cta.b64 _, [%0], %1;" ::"r"(b), "r"(tx) : "memory"); }
__device__ __forceinline__ void mbar_arrive(uint32_t b) { asm volatile("mbarrier.arrive.shared::cta.b64 _, [%0];" ::"r"(b) : "memory"); }
__device__ __forceinline__ void mbar_wait(uint32_t b, uint32_t ph) {
  uint32_t ok = 0;
#pragma unroll 1
  for (int it = 0; it < SPIN && !ok; it++)
    asm volatile("{.reg .pred p; mbarrier.try_wait.parity.shared::cta.b64 p,[%1],%2; selp.u32 %0,1,0,p;}" : "=r"(ok) : "r"(b), "r"(ph) : "memory");
}
__device__ __forceinline__ void tma2d(uint32_t dst, const CUtensorMap* m, int c0, int c1, uint32_t bar) {
  asm volatile("cp.async.bulk.tensor.2d.shared::cluster.global.mbarrier::complete_tx::bytes [%0], [%1, {%3, %4}], [%2];"
               ::"r"(dst), "l"(m), "r"(bar), "r"(c0), "r"(c1) : "memory");
}
__device__ __forceinline__ void tma3d(uint32_t dst, const CUtensorMap* m, int c0, int c1, int c2, uint32_t bar) {
  asm volatile("cp.async.bulk.tensor.3d.shared::cluster.global.mbarrier::complete_tx::bytes [%0], [%1, {%3, %4, %5}], [%2];"
               ::"r"(dst), "l"(m), "r"(bar), "r"(c0), "r"(c1), "r"(c2) : "memory");
}
__device__ __forceinline__ void l2pf(const void* p, uint32_t bytes) { asm volatile("cp.async.bulk.prefetch.L2.global [%0], %1;" ::"l"(p), "r"(bytes) : "memory"); }
__device__ __forceinline__ void wg_fence() { asm volatile("wgmma.fence.sync.aligned;" ::: "memory"); }
__device__ __forceinline__ void wg_commit() { asm volatile("wgmma.commit_group.sync.aligned;" ::: "memory"); }
template <int N> __device__ __forceinline__ void wg_wait() { asm volatile("wgmma.wait_group.sync.aligned %0;" ::"n"(N) : "memory"); }
template <int N> __device__ __forceinline__ void regfence(float (&d)[N]) {
#pragma unroll
  for (int i = 0; i < N; i++) asm volatile("" : "+f"(d[i])::"memory");
}
__device__ __forceinline__ void bar_cons() { asm volatile("bar.sync 1, 256;" ::: "memory"); }
__device__ __forceinline__ void fence_async() { asm volatile("fence.proxy.async.shared::cta;" ::: "memory"); }
struct Desc { uint32_t lo, hi; };
__device__ __forceinline__ Desc mkdesc(uint32_t base16, uint32_t off, uint32_t lbo, uint32_t sbo, uint32_t swz) {
  return Desc{base16 + ((off >> 4) | ((lbo >> 4) << 16)), (sbo >> 4) | (swz << 30)};
}
__device__ __forceinline__ uint4 ldll(const uint4* p) {
  uint4 v; asm volatile("ld.relaxed.gpu.global.v4.u32 {%0,%1,%2,%3}, [%4];" : "=r"(v.x), "=r"(v.y), "=r"(v.z), "=r"(v.w) : "l"(p) : "memory"); return v;
}
__device__ __forceinline__ uint2 ldll2(const uint2* p) {
  uint2 v; asm volatile("ld.relaxed.gpu.global.v2.u32 {%0,%1}, [%2];" : "=r"(v.x), "=r"(v.y) : "l"(p) : "memory"); return v;
}
__device__ __forceinline__ void stll(uint4* p, uint32_t x, uint32_t y, uint32_t z, uint32_t w) {
  asm volatile("st.relaxed.gpu.global.v4.u32 [%0], {%1,%2,%3,%4};" ::"l"(p), "r"(x), "r"(y), "r"(z), "r"(w) : "memory");
}
__device__ __forceinline__ void stll2(void* p, uint32_t x, uint32_t y) {
  asm volatile("st.relaxed.gpu.global.v2.u32 [%0], {%1,%2};" ::"l"(p), "r"(x), "r"(y) : "memory");
}
__device__ __forceinline__ int laneid() { int l; asm volatile("mov.u32 %0, %%laneid;" : "=r"(l)); return l; }
__device__ __forceinline__ uint32_t tg(uint32_t w, uint32_t tag) { return (w & ~1u) | tag; }
__device__ __forceinline__ uint32_t pack(float lo, float hi) {
  uint32_t r; asm("cvt.rn.bf16x2.f32 %0, %1, %2;" : "=r"(r) : "f"(hi), "f"(lo)); return r;
}
__device__ __forceinline__ float blo(uint32_t w) { return __uint_as_float(w << 16); }
__device__ __forceinline__ float bhi(uint32_t w) { return __uint_as_float(w & 0xffff0000u); }
__device__ __forceinline__ float ex2(float x) { float r; asm("ex2.approx.ftz.f32 %0, %1;" : "=f"(r) : "f"(x)); return r; }
__device__ __forceinline__ float rcp(float x) { float r; asm("rcp.approx.ftz.f32 %0, %1;" : "=f"(r) : "f"(x)); return r; }
__device__ __forceinline__ float qsum(float v) { v += __shfl_xor_sync(~0u, v, 1); v += __shfl_xor_sync(~0u, v, 2); return v; }
__device__ __forceinline__ void sts32(uint32_t a, uint32_t v) { asm volatile("st.shared.u32 [%0], %1;" ::"r"(a), "r"(v) : "memory"); }
__device__ __forceinline__ void sts16(uint32_t a, uint32_t v) { asm volatile("st.shared.u16 [%0], %1;" ::"r"(a), "h"((uint16_t)v) : "memory"); }
__device__ __forceinline__ void sts128(uint32_t a, uint32_t x, uint32_t y, uint32_t z, uint32_t w) {
  asm volatile("st.shared.v4.u32 [%0], {%1,%2,%3,%4};" ::"r"(a), "r"(x), "r"(y), "r"(z), "r"(w) : "memory");
}
__device__ __forceinline__ uint32_t sw128(int row, int col) { return row * 128 + ((((col >> 3) ^ row) & 7) << 4) + (col & 7) * 2; }

__device__ __forceinline__ void wgmma_rs56(float (&d)[28], const uint32_t a0, const uint32_t a1, const uint32_t a2, const uint32_t a3, Desc db, int sd) {
  asm volatile("{.reg .pred p; .reg .b64 da, db; setp.ne.b32 p, %33, 0; mov.b64 db, {%32, %34};\n wgmma.mma_async.sync.aligned.m64n56k16.f32.bf16.bf16 {%0,%1,%2,%3,%4,%5,%6,%7,%8,%9,%10,%11,%12,%13,%14,%15,%16,%17,%18,%19,%20,%21,%22,%23,%24,%25,%26,%27}, {%28,%29,%30,%31}, db, p, 1, 1, 1;}"
   : "+f"(d[0]),"+f"(d[1]),"+f"(d[2]),"+f"(d[3]),"+f"(d[4]),"+f"(d[5]),"+f"(d[6]),"+f"(d[7]),"+f"(d[8]),"+f"(d[9]),"+f"(d[10]),"+f"(d[11]),"+f"(d[12]),"+f"(d[13]),"+f"(d[14]),"+f"(d[15]),"+f"(d[16]),"+f"(d[17]),"+f"(d[18]),"+f"(d[19]),"+f"(d[20]),"+f"(d[21]),"+f"(d[22]),"+f"(d[23]),"+f"(d[24]),"+f"(d[25]),"+f"(d[26]),"+f"(d[27])
   : "r"(a0),"r"(a1),"r"(a2),"r"(a3),"r"(db.lo),"r"(sd),"r"(db.hi));
}
__device__ __forceinline__ void wgmma_rs64(float (&d)[32], const uint32_t a0, const uint32_t a1, const uint32_t a2, const uint32_t a3, Desc db, int sd) {
  asm volatile("{.reg .pred p; .reg .b64 da, db; setp.ne.b32 p, %37, 0; mov.b64 db, {%36, %38};\n wgmma.mma_async.sync.aligned.m64n64k16.f32.bf16.bf16 {%0,%1,%2,%3,%4,%5,%6,%7,%8,%9,%10,%11,%12,%13,%14,%15,%16,%17,%18,%19,%20,%21,%22,%23,%24,%25,%26,%27,%28,%29,%30,%31}, {%32,%33,%34,%35}, db, p, 1, 1, 1;}"
   : "+f"(d[0]),"+f"(d[1]),"+f"(d[2]),"+f"(d[3]),"+f"(d[4]),"+f"(d[5]),"+f"(d[6]),"+f"(d[7]),"+f"(d[8]),"+f"(d[9]),"+f"(d[10]),"+f"(d[11]),"+f"(d[12]),"+f"(d[13]),"+f"(d[14]),"+f"(d[15]),"+f"(d[16]),"+f"(d[17]),"+f"(d[18]),"+f"(d[19]),"+f"(d[20]),"+f"(d[21]),"+f"(d[22]),"+f"(d[23]),"+f"(d[24]),"+f"(d[25]),"+f"(d[26]),"+f"(d[27]),"+f"(d[28]),"+f"(d[29]),"+f"(d[30]),"+f"(d[31])
   : "r"(a0),"r"(a1),"r"(a2),"r"(a3),"r"(db.lo),"r"(sd),"r"(db.hi));
}
__device__ __forceinline__ void wgmma_rs192(float (&d)[96], const uint32_t a0, const uint32_t a1, const uint32_t a2, const uint32_t a3, Desc db, int sd) {
  asm volatile("{.reg .pred p; .reg .b64 db; setp.ne.b32 p, %101, 0; mov.b64 db, {%100, %102};\n wgmma.mma_async.sync.aligned.m64n192k16.f32.bf16.bf16 {%0,%1,%2,%3,%4,%5,%6,%7,%8,%9,%10,%11,%12,%13,%14,%15,%16,%17,%18,%19,%20,%21,%22,%23,%24,%25,%26,%27,%28,%29,%30,%31,%32,%33,%34,%35,%36,%37,%38,%39,%40,%41,%42,%43,%44,%45,%46,%47,%48,%49,%50,%51,%52,%53,%54,%55,%56,%57,%58,%59,%60,%61,%62,%63,%64,%65,%66,%67,%68,%69,%70,%71,%72,%73,%74,%75,%76,%77,%78,%79,%80,%81,%82,%83,%84,%85,%86,%87,%88,%89,%90,%91,%92,%93,%94,%95}, {%96,%97,%98,%99}, db, p, 1, 1, 1;}"
   : "+f"(d[0]),"+f"(d[1]),"+f"(d[2]),"+f"(d[3]),"+f"(d[4]),"+f"(d[5]),"+f"(d[6]),"+f"(d[7]),"+f"(d[8]),"+f"(d[9]),"+f"(d[10]),"+f"(d[11]),"+f"(d[12]),"+f"(d[13]),"+f"(d[14]),"+f"(d[15]),"+f"(d[16]),"+f"(d[17]),"+f"(d[18]),"+f"(d[19]),"+f"(d[20]),"+f"(d[21]),"+f"(d[22]),"+f"(d[23]),"+f"(d[24]),"+f"(d[25]),"+f"(d[26]),"+f"(d[27]),"+f"(d[28]),"+f"(d[29]),"+f"(d[30]),"+f"(d[31]),"+f"(d[32]),"+f"(d[33]),"+f"(d[34]),"+f"(d[35]),"+f"(d[36]),"+f"(d[37]),"+f"(d[38]),"+f"(d[39]),"+f"(d[40]),"+f"(d[41]),"+f"(d[42]),"+f"(d[43]),"+f"(d[44]),"+f"(d[45]),"+f"(d[46]),"+f"(d[47]),"+f"(d[48]),"+f"(d[49]),"+f"(d[50]),"+f"(d[51]),"+f"(d[52]),"+f"(d[53]),"+f"(d[54]),"+f"(d[55]),"+f"(d[56]),"+f"(d[57]),"+f"(d[58]),"+f"(d[59]),"+f"(d[60]),"+f"(d[61]),"+f"(d[62]),"+f"(d[63]),"+f"(d[64]),"+f"(d[65]),"+f"(d[66]),"+f"(d[67]),"+f"(d[68]),"+f"(d[69]),"+f"(d[70]),"+f"(d[71]),"+f"(d[72]),"+f"(d[73]),"+f"(d[74]),"+f"(d[75]),"+f"(d[76]),"+f"(d[77]),"+f"(d[78]),"+f"(d[79]),"+f"(d[80]),"+f"(d[81]),"+f"(d[82]),"+f"(d[83]),"+f"(d[84]),"+f"(d[85]),"+f"(d[86]),"+f"(d[87]),"+f"(d[88]),"+f"(d[89]),"+f"(d[90]),"+f"(d[91]),"+f"(d[92]),"+f"(d[93]),"+f"(d[94]),"+f"(d[95])
   : "r"(a0),"r"(a1),"r"(a2),"r"(a3),"r"(db.lo),"r"(sd),"r"(db.hi));
}
__device__ __forceinline__ void wgmma_rs32(float (&d)[16], const uint32_t a0, const uint32_t a1, const uint32_t a2, const uint32_t a3, Desc db, int sd) {
  asm volatile("{.reg .pred p; .reg .b64 db; setp.ne.b32 p, %21, 0; mov.b64 db, {%20, %22};\n wgmma.mma_async.sync.aligned.m64n32k16.f32.bf16.bf16 {%0,%1,%2,%3,%4,%5,%6,%7,%8,%9,%10,%11,%12,%13,%14,%15}, {%16,%17,%18,%19}, db, p, 1, 1, 1;}"
   : "+f"(d[0]),"+f"(d[1]),"+f"(d[2]),"+f"(d[3]),"+f"(d[4]),"+f"(d[5]),"+f"(d[6]),"+f"(d[7]),"+f"(d[8]),"+f"(d[9]),"+f"(d[10]),"+f"(d[11]),"+f"(d[12]),"+f"(d[13]),"+f"(d[14]),"+f"(d[15])
   : "r"(a0),"r"(a1),"r"(a2),"r"(a3),"r"(db.lo),"r"(sd),"r"(db.hi));
}
__device__ __forceinline__ void wgmma_ss32(float (&d)[16], Desc da, Desc db, int sd) {
  asm volatile("{.reg .pred p; .reg .b64 da, db; setp.ne.b32 p, %18, 0; mov.b64 da, {%16, %19}; mov.b64 db, {%17, %19};\n wgmma.mma_async.sync.aligned.m64n32k16.f32.bf16.bf16 {%0,%1,%2,%3,%4,%5,%6,%7,%8,%9,%10,%11,%12,%13,%14,%15}, da, db, p, 1, 1, 1, 1;}"
   : "+f"(d[0]),"+f"(d[1]),"+f"(d[2]),"+f"(d[3]),"+f"(d[4]),"+f"(d[5]),"+f"(d[6]),"+f"(d[7]),"+f"(d[8]),"+f"(d[9]),"+f"(d[10]),"+f"(d[11]),"+f"(d[12]),"+f"(d[13]),"+f"(d[14]),"+f"(d[15])
   : "r"(da.lo),"r"(db.lo),"r"(sd),"r"(db.hi));
}

__device__ __forceinline__ uint4 ldsm4(uint32_t a) {
  uint4 v; asm volatile("ldmatrix.sync.aligned.m8n8.x4.shared.b16 {%0,%1,%2,%3}, [%4];" : "=r"(v.x), "=r"(v.y), "=r"(v.z), "=r"(v.w) : "r"(a) : "memory"); return v;
}
__device__ __forceinline__ void mma16816(float (&d)[4], const uint4& a, uint32_t b0, uint32_t b1) {
  asm("mma.sync.aligned.m16n8k16.row.col.f32.bf16.bf16.f32 {%0,%1,%2,%3}, {%4,%5,%6,%7}, {%8,%9}, {%0,%1,%2,%3};"
      : "+f"(d[0]), "+f"(d[1]), "+f"(d[2]), "+f"(d[3]) : "r"(a.x), "r"(a.y), "r"(a.z), "r"(a.w), "r"(b0), "r"(b1));
}
__device__ __forceinline__ uint32_t bsub(uint32_t a, uint32_t b) { uint32_t r; asm("sub.bf16x2 %0, %1, %2;" : "=r"(r) : "r"(a), "r"(b)); return r; }
__device__ __forceinline__ uint32_t bsq(uint32_t a) { uint32_t r; asm("mul.bf16x2 %0, %1, %1;" : "=r"(r) : "r"(a)); return r; }
__device__ __forceinline__ uint32_t hint_ld(const uint32_t* p) { uint32_t v; asm volatile("ld.relaxed.gpu.global.u32 %0, [%1];" : "=r"(v) : "l"(p) : "memory"); return v; }
template <int S, int N, bool SPL = false, int T> __device__ __forceinline__ void ll_issue(uint4 (&v)[T], const uint4* p, int stride, const uint2* p2 = nullptr) {
#pragma unroll
  for (int i = S; i < S + N; i++) {
    if (SPL && i % 7 == 3) { const uint2 lo = ldll2(p2 + i * 64), hi = ldll2(p2 + i * 64 + 32); v[i] = make_uint4(lo.x, lo.y, hi.x, hi.y); }
    else v[i] = ldll(p + i * stride);
  }
}
template <int S, int N, bool SPL, int T> __device__ __forceinline__ void ll_check(uint4 (&v)[T], const uint4* p, int stride, uint32_t tag, const uint2* p2 = nullptr) {
#pragma unroll 1
  for (int it = 0; it < SPIN; it++) {
    uint32_t bad = 0;
#pragma unroll
    for (int i = S; i < S + N; i++) bad |= (v[i].x ^ tag) | ((SPL && i % 7 == 3) ? (v[i].z ^ tag) : 0u);
    if (!__any_sync(~0u, bad & 1)) break;
    ll_issue<S, N, SPL>(v, p, stride, p2);
  }
}
__device__ __forceinline__ void hint_post(uint32_t* p, uint32_t v, int lane) {
  if (lane == 0) asm volatile("st.relaxed.gpu.global.u32 [%0], %1;" ::"l"(p), "r"(v) : "memory");
}
__device__ __forceinline__ void hint_wait(const uint32_t* p, uint32_t s, uint32_t v = 0xffffu) {
#pragma unroll 1
  for (int it = 0; it < SPIN; it++) {
    if (__all_sync(~0u, v - s < 10u)) break;
    v = hint_ld(p);
  }
}
__device__ __forceinline__ void p_issue(uint4 (&v)[8], const uint4* p, uint32_t own) {
  ll_issue<1, 7>(v, p, 896);
  asm volatile("ld.volatile.shared.v4.u32 {%0,%1,%2,%3}, [%4];" : "=r"(v[0].x), "=r"(v[0].y), "=r"(v[0].z), "=r"(v[0].w) : "r"(own) : "memory");
}
__device__ __forceinline__ void p_check(uint4 (&v)[8], const uint4* p, uint32_t own, uint32_t tag) {
#pragma unroll 1
  for (int it = 0; it < SPIN; it++) {
    uint32_t bad = 0;
#pragma unroll
    for (int i = 0; i < 8; i++) bad |= v[i].x ^ tag;
    if (!__any_sync(~0u, bad & 1)) break;
    p_issue(v, p, own);
  }
}
__device__ __forceinline__ void slice_store(uint4* pf, uint2* ph, const uint32_t (&w)[14], bool odd) {
#pragma unroll
  for (int u = 0; u < 3; u++)
    stll(pf + u * 32, odd ? w[4 * u + 2] : w[4 * u], odd ? w[4 * u + 3] : w[4 * u + 1], odd ? w[4 * u + 4] : w[4 * u + 2], odd ? w[4 * u + 5] : w[4 * u + 3]);
  stll2(ph, odd ? w[0] : w[12], odd ? w[1] : w[13]);
}
template <class F, class M> __device__ __forceinline__ void hedgehog(const float (&d)[28], F sink, M mid) {
  const float L2E = 1.4426950408889634f;
#define HX(G, p) ((p) < 6 ? d[((G) & 1) * 16 + ((p) >> 1) * 4 + ((p) & 1) + ((G) & 2)] : d[12 + (G)])
  float mx[4], mn[4], sp[4], sn[4], ep[4][7], en[4][7];
#pragma unroll
  for (int G = 0; G < 4; G++) {
    mx[G] = mn[G] = HX(G, 0);
#pragma unroll
    for (int p = 1; p < 7; p++) { mx[G] = fmaxf(mx[G], HX(G, p)); mn[G] = fminf(mn[G], HX(G, p)); }
  }
#pragma unroll
  for (int o = 1; o < 4; o <<= 1)
#pragma unroll
    for (int G = 0; G < 4; G++) { mx[G] = fmaxf(mx[G], __shfl_xor_sync(~0u, mx[G], o)); mn[G] = fminf(mn[G], __shfl_xor_sync(~0u, mn[G], o)); }
#pragma unroll
  for (int G = 0; G < 4; G++) {
    const float a = -mx[G] * L2E, b = mn[G] * L2E;
#pragma unroll
    for (int p = 0; p < 7; p++) { ep[G][p] = ex2(fmaf(HX(G, p), L2E, a)); en[G][p] = ex2(fmaf(HX(G, p), -L2E, b)); }
    sp[G] = ((ep[G][0] + ep[G][1]) + (ep[G][2] + ep[G][3])) + ((ep[G][4] + ep[G][5]) + ep[G][6]);
    sn[G] = ((en[G][0] + en[G][1]) + (en[G][2] + en[G][3])) + ((en[G][4] + en[G][5]) + en[G][6]);
    if (G == 1) mid();
  }
#pragma unroll
  for (int o = 1; o < 4; o <<= 1)
#pragma unroll
    for (int G = 0; G < 4; G++) { sp[G] += __shfl_xor_sync(~0u, sp[G], o); sn[G] += __shfl_xor_sync(~0u, sn[G], o); }
#pragma unroll
  for (int G = 0; G < 4; G++) {
    const float a = rcp(sp[G]), b = rcp(sn[G]);
#pragma unroll
    for (int p = 0; p < 7; p++) sink(G >> 1, G & 1, p, pack(ep[G][p] * a, en[G][p] * b));
  }
}
__device__ __forceinline__ void phi_gemm(const float (&x)[28], float (&y)[28], uint32_t wphi, float r0, float r1) {
  uint32_t f[14];
#pragma unroll
  for (int j = 0; j < 14; j++) f[j] = pack(x[2 * j] * (j & 1 ? r1 : r0), x[2 * j + 1] * (j & 1 ? r1 : r0));
  wg_fence();
#pragma unroll
  for (int ks = 0; ks < 3; ks++) wgmma_rs56(y, f[4 * ks], f[4 * ks + 1], f[4 * ks + 2], f[4 * ks + 3], mkdesc(wphi, ks * 2048, 1024, 1024, 1), ks);
  wgmma_rs56(y, f[12], f[13], 0u, 0u, mkdesc(wphi, 3 * 2048, 1024, 1024, 1), 1);
  wg_commit();
}
__device__ __forceinline__ void ln_stats(uint32_t (&xw)[4][4], float* sLN, int warp, int lane, uint4* dst) {
  const int g = lane >> 2; const bool full = warp < 4;
  float s0 = 0.f, s1 = 0.f;
#pragma unroll
  for (int u = 0; u < 4; u++) {
    s0 += (blo(xw[u][0]) + bhi(xw[u][0])) + (blo(xw[u][2]) + bhi(xw[u][2]));
    s1 += (blo(xw[u][1]) + bhi(xw[u][1])) + (blo(xw[u][3]) + bhi(xw[u][3]));
  }
  const float rc = full ? 1.f / 64 : 1.f / 48;
  s0 = qsum(s0); s1 = qsum(s1);
  const float a0 = s0 * rc, a1 = s1 * rc;
  float v0 = 0.f, v1 = 0.f;
#pragma unroll
  for (int u = 0; u < 4; u++)
    if (u < 3 || full) {
#pragma unroll
      for (int k = 0; k < 4; k += 2) {
        float a = blo(xw[u][k]) - a0, b = bhi(xw[u][k]) - a0, c2 = blo(xw[u][k + 1]) - a1, d2 = bhi(xw[u][k + 1]) - a1;
        v0 += a * a + b * b; v1 += c2 * c2 + d2 * d2;
      }
    }
  v0 = qsum(v0); v1 = qsum(v1);
  if ((lane & 3) == 0) *(float4*)(sLN + (g * 8 + warp) * 4) = make_float4(s0, v0, s1, v1);
  if (warp < 4) asm volatile("bar.arrive 10, 256;" ::: "memory");
  if (warp) { asm volatile("bar.arrive 7, 256;" ::: "memory"); return; }
  asm volatile("bar.sync 7, 256;" ::: "memory");
  const float4 ea = *(const float4*)(sLN + (g * 8 + (lane & 3)) * 4), eb = *(const float4*)(sLN + (g * 8 + 4 + (lane & 3)) * 4);
  const float m0 = qsum(ea.x + eb.x) * (1.f / 448), m1 = qsum(ea.z + eb.z) * (1.f / 448);
  const float d0 = ea.x * (1.f / 64) - m0, d1 = eb.x * (1.f / 48) - m0, d2 = ea.z * (1.f / 64) - m1, d3 = eb.z * (1.f / 48) - m1;
  v0 = qsum(ea.y + eb.y + 64.f * d0 * d0 + 48.f * d1 * d1); v1 = qsum(ea.w + eb.w + 64.f * d2 * d2 + 48.f * d3 * d3);
  if ((lane & 3) == 0) stll(dst + g, tg(__float_as_uint(m0), 1), __float_as_uint(rsqrtf(v0 * (1.f / 448) + 1e-5f)), __float_as_uint(m1), __float_as_uint(rsqrtf(v1 * (1.f / 448) + 1e-5f)));
}

__global__ void __launch_bounds__(384, 1)
fused_kernel(const __grid_constant__ CUtensorMap mQKV, const __grid_constant__ CUtensorMap mWO, const __grid_constant__ CUtensorMap mW1,
             const __grid_constant__ CUtensorMap mW1b, const __grid_constant__ CUtensorMap mW2, const __grid_constant__ CUtensorMap mW2b,
             const __grid_constant__ CUtensorMap mX, const __nv_bfloat16* __restrict__ wqkv, const __nv_bfloat16* __restrict__ wphi,
             const __nv_bfloat16* __restrict__ wo, const __nv_bfloat16* __restrict__ w1, const __nv_bfloat16* __restrict__ b1,
             const __nv_bfloat16* __restrict__ w2, const __nv_bfloat16* __restrict__ b2, __nv_bfloat16* __restrict__ out) {
  extern __shared__ __align__(1024) uint8_t sm[];
  constexpr uint32_t sb = 1024;
  if (s2u(sm) != sb) __trap();
  const int tid = threadIdx.x, warp = __shfl_sync(~0u, tid >> 5, 0), lane = tid & 31,
            t = blockIdx.x >> 3, c = blockIdx.x & 7;
  const uint32_t bfull = sb + OFF_BAR, bempty = bfull + 8 * NST;

#define XOFF(l) ((t * 128 + c * 16 + ((l) >> 2)) * 448 + warp * 16 + 2 * ((l) & 3))
  if (warp < 8) { MARK(0); GT(19); }
  if (tid == 256) {
    for (int s = 0; s < NST; s++) { mbar_init(bfull + 8 * s, 1); mbar_init(bempty + 8 * s, 8); }
    mbar_init(bempty + 8 * NST, 1);
    asm volatile("fence.mbarrier_init.release.cluster;" ::: "memory");
    fence_async();
    mbar_expect(bempty + 8 * NST, 114688);
    for (int i = 0; i < 7; i++)
      asm volatile("cp.async.bulk.tensor.2d.shared::cluster.global.mbarrier::complete_tx::bytes [%0], [%1, {%3, %4}], [%2];"
                   ::"r"(sb + OFF_X + i * 16384), "l"(&mX), "r"(bempty + 8 * NST), "r"(64 * i), "r"(128 * t) : "memory");
  }
  __syncthreads();
  if (warp >= 8) {
    asm volatile("setmaxnreg.dec.sync.aligned.u32 24;");
    auto issue = [&](int i, int s) {
      const uint32_t dst = sb + s * STAGE, bar = bfull + 8 * s;
      mbar_expect(bar, STAGE);
#pragma unroll 1
      for (int rk = 0; rk < 2; rk++)
      if (i < 4) tma2d(dst + rk * 14336, &mQKV, 448 + 448 * rk + 56 * c, 112 * i, bar);
      else if (i < 8) tma2d(dst + rk * 14336, i < 6 ? &mQKV : &mWO, (i < 6 ? 56 : 64) * c, 224 * (i & 1) + 112 * rk, bar);
      else if (i < 15) { const int k0 = 64 * ((i - 8 + c) % 7) + 32 * rk;
        tma3d(dst + rk * 12288, &mW1, 0, k0, 3 * c, bar); tma2d(dst + 24576 + rk * 2048, &mW1b, 1536 + 32 * c, k0, bar); }
      else { tma2d(dst + rk * 12288, &mW2, 64 * (i - 15), 192 * c + 96 * rk, bar); tma2d(dst + 24576 + rk * 2048, &mW2b, 64 * (i - 15), 1536 + 32 * c + 16 * rk, bar); }
    };
    auto colsum = [&](int job) {
        const int ld4 = job < 112 ? 448 : 336;
        const uint2* wp = (job < 112 ? (const uint2*)w1 + job * 4 : (const uint2*)wqkv + (job - 112) * 4) + (lane >> 2) * ld4 + (lane & 3);
        float s0 = 0.f, s1 = 0.f, s2 = 0.f, s3 = 0.f;
#pragma unroll 8
        for (int i = 0; i < 56; i++) { const uint2 v = __ldg(wp + i * 8 * ld4); s0 += blo(v.x); s1 += bhi(v.x); s2 += blo(v.y); s3 += bhi(v.y); }
#pragma unroll 1
        for (int o = 4; o < 32; o <<= 1) { s0 += __shfl_xor_sync(~0u, s0, o); s1 += __shfl_xor_sync(~0u, s1, o); s2 += __shfl_xor_sync(~0u, s2, o); s3 += __shfl_xor_sync(~0u, s3, o); }
        if (lane < 4) stll(g_CS + job * 4 + lane, tg(__float_as_uint(s0), 1), __float_as_uint(s1), __float_as_uint(s2), __float_as_uint(s3));
      };
    if (warp == 8) {
#pragma unroll 1
      for (int n = 0; n < 44; n++) {
        const int L = n >= 22, i = L ? (n < 28 ? (n - 18) % 6 : n - 22) : n, s = i % 6;
        if (n == 3) asm volatile("bar.sync 2, 288;" ::: "memory");
        mbar_wait(bempty + 8 * s, (i / 6 + (s >= 4 ? L : 0) + 1) & 1);
        if (n == 22) {
          uint32_t v = 0;
#pragma unroll 1
          for (int it = 0; it < SPIN && v < 32; it++) asm volatile("ld.acquire.gpu.global.u32 %0, [%1];" : "=r"(v) : "l"(g_WQF + c) : "memory");
          asm volatile("fence.proxy.async.global;" ::: "memory");
        }
        if (lane == 0) {
          if (n >= 22 && n < 28) {
            mbar_expect(bfull + 8 * s, STAGE);
            asm volatile("cp.async.bulk.shared::cluster.global.mbarrier::complete_tx::bytes [%0], [%1], %2, [%3];"
                         ::"r"(sb + s * STAGE), "l"(g_WQ + c * 10752 + i * (STAGE / 16)), "r"(STAGE), "r"(bfull + 8 * s) : "memory");
          } else issue(i, s);
        }
        __syncwarp();
      }
    } else if (warp == 9) {
      mbar_wait(bfull + 8 * 3, 0);
      if (lane == 0) {
        l2pf((const uint8_t*)wo + blockIdx.x * 3136, 3136);
        l2pf((const uint8_t*)w1 + blockIdx.x * 12544, 12544);
        l2pf((const uint8_t*)w2 + blockIdx.x * 12544, 12544);
      }
      if (blockIdx.x < 112) colsum(blockIdx.x);
      asm volatile("bar.sync 6, 96;" ::: "memory");
#pragma unroll 1
      for (int i = 0; i < 4; i++) {
        const int e = lane < 28 ? lane + 28 * (i & 1) : 0;
        const bool ok = i < 2 || (e < 48 && (e & 15) < 14);
        const int e4 = i < 2 ? (e < 48 ? 48 * c + e : 336 + 8 * c + e) : ok ? 448 + 112 * (e >> 4) + 14 * c + (e & 15) : 448;
        uint4 cv[1];
        ll_issue<0, 1>(cv, g_CS + e4, 0); ll_check<0, 1, false>(cv, g_CS + e4, 0, 1u);
        const uint2 bb = __ldg((const uint2*)b1 + (i < 2 ? e4 : 0));
        const uint32_t h0 = pack(__uint_as_float(cv[0].x), __uint_as_float(cv[0].y)), h1 = pack(__uint_as_float(cv[0].z), __uint_as_float(cv[0].w));
        const uint32_t l0 = pack(__uint_as_float(cv[0].x) - blo(h0), __uint_as_float(cv[0].y) - bhi(h0)), l1 = pack(__uint_as_float(cv[0].z) - blo(h1), __uint_as_float(cv[0].w) - bhi(h1));
#pragma unroll 1
        for (int j = 0; j < (i < 2 ? 5 : 3); j++) {
          const int r = i < 2 ? j : j + 5;
          const uint32_t ad = sb + OFF_CB + (e >> 3) * 512 + r * 64 + ((((e >> 1) ^ (r >> 1)) & 3) << 4) + (e & 1) * 8;
          sts32(ad, j < 2 ? h0 : j == 2 ? l0 : bb.x); sts32(ad + 4, j < 2 ? h1 : j == 2 ? l1 : bb.y);
        }
        if (i & 1) { fence_async(); if (i == 1) asm volatile("bar.arrive 4, 288;" ::: "memory"); else asm volatile("bar.arrive 8, 160; bar.arrive 9, 160;" ::: "memory"); }
      }
    } else if (warp >= 10) {
      const int h = warp - 10;
      uint4 wv[4];
#pragma unroll
      for (int i = 0; i < 4; i++) wv[i] = __ldg((const uint4*)wphi + (2 * c + h) * 98 + min(lane + 32 * i, 97));
#pragma unroll 1
      for (int e = h * 32 + lane; e < 672; e += 64) sts128(sb + OFF_WPHI + e * 16, 0, 0, 0, 0);
      asm volatile("bar.arrive 6, 96;" ::: "memory");
      asm volatile("bar.sync 5, 64;" ::: "memory");
#pragma unroll
      for (int i = 0; i < 4; i++) sts128(sb + OFF_V + h * 2048 + (lane + 32 * i) * 16, wv[i].x, wv[i].y, wv[i].z, wv[i].w);
      __syncwarp();
#pragma unroll 1
      for (int e = lane; e < 392; e += 32) {
        const int d = e / 14, f2 = 2 * (e - 14 * d), k = 28 * h + d;
        const uint32_t v = *(volatile uint32_t*)(sm + OFF_V + h * 2048 + e * 4);
        if (f2 < 24) sts32(sb + OFF_WPHI + sw128(k, 32 * h + f2), v);
        else { sts16(sb + OFF_WPHI + sw128(k, 2 * f2 - 24 + h), v); sts16(sb + OFF_WPHI + sw128(k, 2 * f2 - 22 + h), v >> 16); }
      }
      fence_async();
      asm volatile("bar.arrive 3, 320;" ::: "memory");
      mbar_wait(bfull + 8 * 5, 0);
#pragma unroll 2
      for (int e = t * 672 + h * 32 + lane; e < t * 672 + 672; e += 64) {
        const int r = e >> 3, st = r / 224, rr = r - st * 224, ch = (e & 7) ^ (rr & 7);
        const int k = st < 4 ? 112 * st + (rr >= 112 ? rr - 112 : rr) : 224 * (st - 4) + rr, col = (st < 4 ? (rr >= 112 ? 896 : 448) : 0) + 56 * c + 8 * ch;
        g_WQ[c * 10752 + e] = ch < 7 ? __ldg((const uint4*)(wqkv + k * 1344 + col)) : make_uint4(0, 0, 0, 0);
      }
      __syncwarp();
      if (lane == 0) asm volatile("red.release.gpu.global.add.u32 [%0], 1;" ::"l"(g_WQF + c) : "memory");
      if (h == 0 && blockIdx.x < 84) colsum(112 + blockIdx.x);
    }
  } else {
  asm volatile("setmaxnreg.inc.sync.aligned.u32 240;");

  const int wg = warp >> 2, g = lane >> 2, q = lane & 3;
  const int row0 = warp * 16 + g;
#define PTRS const int ln_ = laneid(); \
  uint4* const fm = g_F + ((t * 8 + warp) * 28) * 32 + ln_;            \
  uint4* const fr = g_F + ((t * 8 + c) * 28 + warp) * 32 + ln_;        \
  uint4* const sf = fm + (7 * (c >> 1) + 4 * (c & 1)) * 32;             \
  uint2* const f2 = (uint2*)(fm - ln_) + ln_;                           \
  uint2* const sh = f2 + (7 * (c >> 1) + 3) * 64 + 32 * (c & 1);        \
  uint32_t* const hme = g_H + (t * 8 + warp) * 8 + c; \
  const uint32_t* const hrow = g_H + (t * 8 + warp) * 8 + (ln_ & 7); \
  (void)fm; (void)fr; (void)sf; (void)f2; (void)sh; (void)hme; (void)hrow;
  float* sLN = (float*)(sm + OFF_V);
  const uint32_t sPK = sb + OFF_PHIK, sV = sb + OFF_V, d16 = (sb & 0x3FFFF) >> 4;
    uint32_t xw[4][4];
#pragma unroll
  for (int i = 0; i < 16; i++) xw[i >> 2][i & 3] = 0;
#define ACQ(I) (mbar_wait(bfull + 8 * ((I) % 6), ((I) / 6 + ((I) % 6 >= 4 ? L : 0)) & 1), d16 + ((I) % 6) * (STAGE >> 4))
#define REL(I) { if (lane == 0) mbar_arrive(bempty + 8 * ((I) % 6)); }
#define RISSUE(m, P, XA, XB, BA, BB) { p_issue(P, pr + (m) * 256, sPK + (8 * (m) + warp) * 512 + ln_ * 16); \
      { const uint4 v_ = ldll(fr + X1 + (m) * 256); XA = make_uint2(v_.x, v_.y); XB = make_uint2(v_.z, v_.w); } \
      const uint32_t* bp = (const uint32_t*)(b2 + 128 * (m) + 16 * warp) + (ln_ & 3); BA = __ldg(bp); BB = __ldg(bp + 4); }
#define REDU(m, P, XA, XB, BA, BB) { p_check(P, pr + (m) * 256, sPK + (8 * (m) + warp) * 512 + ln_ * 16, ptag); \
      float e[8] = {blo(XA.x) + blo(BA), bhi(XA.x) + bhi(BA), blo(XA.y) + blo(BA), bhi(XA.y) + bhi(BA), blo(XB.x) + blo(BB), bhi(XB.x) + bhi(BB), blo(XB.y) + blo(BB), bhi(XB.y) + bhi(BB)}; \
      _Pragma("unroll") for (int i = 0; i < 8; i++) { e[0] += blo(P[i].x); e[1] += bhi(P[i].x); e[2] += blo(P[i].y); e[3] += bhi(P[i].y); \
        e[4] += blo(P[i].z); e[5] += bhi(P[i].z); e[6] += blo(P[i].w); e[7] += bhi(P[i].w); } \
      xw[m][0] = pack(e[0], e[1]); xw[m][1] = pack(e[2], e[3]); xw[m][2] = pack(e[4], e[5]); xw[m][3] = pack(e[6], e[7]); }
#define RPUB(m) stll(fr + XR + (m) * 256, tg(xw[m][0], 0), xw[m][1], xw[m][2], xw[m][3]);
#define RLAST(ptag_, hv) { const uint32_t ptag = ptag_; const uint4* pr = g_P + ((t * 8 + c) * 8 * 28 + warp) * 32 + ln_; uint4 p[8]; uint2 xa, xb; uint32_t ba, bb; \
      if (ptag_) hint_wait(g_H + (t * 8 + c) * 8 + (ln_ & 7), hv); RISSUE(3, p, xa, xb, ba, bb) REDU(3, p, xa, xb, ba, bb) }
#pragma unroll 1
  for (int L = 0; L < 2; L++) {
    const uint32_t tag = 1 - L;
    uint32_t phq[2][2][7];
    const uint32_t hs = 10 * L;
    {
      PTRS
      uint4 a[28];
      const uint4* pa = fm + XR;
      uint32_t fa = 0, fb = 0;
      float r0 = 1.f, r1 = 1.f;
      if (L == 0) {
        hint_post(hme, 1, lane);
        mbar_wait(bempty + 8 * NST, 0);
        MARK(1);
        const int row = warp * 16 + (ln_ & 15);
        const uint32_t xb = sb + OFF_X + row * 128;
        float cs_[4][4] = {};
#pragma unroll
        for (int ks = 0; ks < 28; ks++) { a[ks] = ldsm4(xb + (ks >> 2) * 16384 + (((2 * (ks & 3) + (ln_ >> 4)) ^ (row & 7)) << 4)); mma16816(cs_[ks & 3], a[ks], 0x3F803F80u, 0x3F803F80u); }
        if (c < 7) {
#pragma unroll
          for (int u = 0; u < 4; u++) { const uint4 v = ldsm4(xb + c * 16384 + (((2 * u + (ln_ >> 4)) ^ (row & 7)) << 4)); stll(fm + XR + 128 * c + u * 32, tg(v.x, tag), v.y, v.z, v.w); }
        }
        const float m0 = ((cs_[0][0] + cs_[1][0]) + (cs_[2][0] + cs_[3][0])) * (1.f / 448), m1 = ((cs_[0][2] + cs_[1][2]) + (cs_[2][2] + cs_[3][2])) * (1.f / 448);
        const uint32_t mb0 = pack(m0, m0), mb1 = pack(m1, m1);
        asm volatile("bar.arrive 2, 288;" ::"r"(mb0) : "memory");
#pragma unroll
        for (int ks = 0; ks < 28; ks++) {
          a[ks].x = bsub(a[ks].x, mb0); a[ks].y = bsub(a[ks].y, mb1); a[ks].z = bsub(a[ks].z, mb0); a[ks].w = bsub(a[ks].w, mb1);
        }
        r0 = m0 - blo(mb0); r1 = m1 - blo(mb1);
      } else {
        ll_issue<0, 14>(a, pa, 32);
        if (wg == 0) { RLAST(1u, 10u) xw[3][0] = tg(xw[3][0], 0); RPUB(3) } else { xw[3][0] = xw[3][1] = xw[3][2] = xw[3][3] = 0; }
        MARK(20);
        ll_issue<14, 7>(a, pa, 32);
        REL(20) REL(21)
        ln_stats(xw, sLN, warp, lane, g_S2 + (t * 8 + c) * 8);
      }
      MARK(2 + L * 19);
      float ak[28], av[28], aq[28], pp[28];
#define KVSTAGE(i) { if (L) ll_check<7 * i, 7, false>(a, pa, 32, tag); const uint32_t st = ACQ(i); wg_fence(); \
      _Pragma("unroll") for (int ks = 0; ks < 7; ks++) { const uint4 f = a[7 * i + ks]; \
        wgmma_rs56(ak, f.x, f.y, f.z, f.w, mkdesc(st, ks * 2048, 1024, 1024, 1), i | ks); \
        wgmma_rs56(av, f.x, f.y, f.z, f.w, mkdesc(st, 14336 + ks * 2048, 1024, 1024, 1), i | ks); } \
      wg_commit(); if (i > 0) { wg_wait<1>(); REL(i + 5) } }
      KVSTAGE(0) KVSTAGE(1)
      uint4 sv[1] = {make_uint4(0, 0, 0, 0)};
      const uint4* ps = g_S2 + (t * 8 + warp) * 8 + (ln_ >> 2);
      if (L) { ll_issue<21, 7>(a, pa, 32); ll_issue<0, 1>(sv, ps, 0); }
      else {
        float c0[2][4] = {};
#pragma unroll
        for (int ks = 0; ks < 28; ks++) mma16816(c0[ks & 1], make_uint4(bsq(a[ks].x), bsq(a[ks].y), bsq(a[ks].z), bsq(a[ks].w)), 0x3F803F80u, 0x3F803F80u);
        const float q0 = c0[0][0] + c0[1][0], q1 = c0[0][2] + c0[1][2];
        r0 = rsqrtf(fmaxf(q0 * (1.f / 448) - r0 * r0, 0.f) + 1e-5f); r1 = rsqrtf(fmaxf(q1 * (1.f / 448) - r1 * r1, 0.f) + 1e-5f);
      }
      KVSTAGE(2) KVSTAGE(3)
      if (L) {
        if (wg) asm volatile("bar.sync 9, 160; bar.sync 10, 256;" ::: "memory"); else asm volatile("bar.sync 8, 160;" ::: "memory");
        ll_check<0, 1, false>(sv, ps, 0, 1u);
        const float m0 = -__uint_as_float(sv[0].x), m1 = -__uint_as_float(sv[0].z), h0 = blo(pack(m0, 0.f)), h1 = blo(pack(m1, 0.f));
        r0 = __uint_as_float(sv[0].y); r1 = __uint_as_float(sv[0].w);
        fa = q == 2 ? pack(0.f, h0) : q == 3 ? pack(m0 - h0, h0) : 0u; fb = q == 2 ? pack(0.f, h1) : q == 3 ? pack(m1 - h1, h1) : 0u;
      } else {
        asm volatile("bar.sync 3, 320;" ::: "memory");
      }
      wg_fence();
      wgmma_rs56(ak, fa, fb, 0u, 0u, mkdesc(d16, OFF_CB + 1024, 512, 0, 2), 1);
      wgmma_rs56(av, fa, fb, 0u, 0u, mkdesc(d16, OFF_CB + 2048, 512, 0, 2), 1);
      wg_commit();
      wg_wait<0>(); REL(3) regfence(ak); regfence(av);
      MARK(3 + L * 19);
      phi_gemm(ak, pp, d16 + (OFF_WPHI >> 4), r0, r1);
#pragma unroll
      for (int j = 0; j < 7; j++) {
        const int n = 8 * j + 2 * q, n2 = n < 28 ? n : n + 4;
        sts32(sV + sw128(row0, n2), pack(av[4 * j] * r0, av[4 * j + 1] * r0)); sts32(sV + sw128(row0 + 8, n2), pack(av[4 * j + 2] * r1, av[4 * j + 3] * r1));
      }
      { const int n2 = 28 + 2 * (q & 1) + 32 * (q >> 1); const uint32_t v = (q & 1) ? 0u : 0x3F80u; sts32(sV + sw128(row0, n2), v); sts32(sV + sw128(row0 + 8, n2), v); }
      wg_wait<0>(); regfence(pp);
      hedgehog(pp, [&](int r, int h, int p, uint32_t v) { sts32(sPK + h * 16384 + sw128(row0 + 8 * r, 8 * p + 2 * q), v); }, [] {});
#pragma unroll
      for (int i = 0; i < 4; i++) sts32(sPK + (i & 1) * 16384 + sw128(row0 + 8 * (i >> 1), 56 + 2 * q), 0u);
      fence_async();
      bar_cons();
      MARK(4 + L * 19);
      float kv[16];
      wg_fence();
#pragma unroll
      for (int ks = 0; ks < 8; ks++) wgmma_ss32(kv, mkdesc(d16 + wg * 1024, OFF_PHIK + ks * 2048, 1024, 1024, 1), mkdesc(d16 + wg * 4, OFF_V + ks * 2048, 1024, 1024, 1), ks);
      wg_commit(); wg_wait<0>(); regfence(kv);
      const int ln2 = laneid();
#pragma unroll
      for (int u = 0; u < 4; u++) {
        float e[4];
#pragma unroll
        for (int i = 0; i < 4; i++) e[i] = kv[4 * u + i];
        stll(g_KVP + (c * 16 + t) * 1024 + wg * 512 + u * 128 + (warp & 3) * 32 + ln2, tg(__float_as_uint(e[0]), tag), __float_as_uint(e[1]), __float_as_uint(e[2]), __float_as_uint(e[3]));
      }
      MARK(5 + L * 19);
      uint4 k4[4];
      const uint4* pk = g_KVP + (c * 16 + 4 * (ln2 & 3)) * 1024 + 64 * t + warp * 8 + (ln2 >> 2);
#pragma unroll
      for (int i = 0; i < 2; i++) {
        const uint32_t st = ACQ(4 + i); wg_fence();
#pragma unroll
        for (int ks = 0; ks < 14; ks++) { const uint4 f = a[14 * i + ks]; wgmma_rs56(aq, f.x, f.y, f.z, f.w, mkdesc(st, ks * 2048, 1024, 1024, 1), i | ks); }
        if (i == 1) wgmma_rs56(aq, fa, fb, 0u, 0u, mkdesc(d16, OFF_CB, 512, 0, 2), 1);
        wg_commit();
        if (i == 1) ll_issue<0, 4>(k4, pk, 1024);
      }
      wg_wait<0>(); REL(4) REL(5) regfence(aq);
      phi_gemm(aq, pp, d16 + (OFF_WPHI >> 4), r0, r1);
      bar_cons();
#pragma unroll
      for (int i = 0; i < 4; i++) { sts128(sV + warp * 2048 + (lane + i * 32) * 16, 0, 0, 0, 0); sts128(sPK + warp * 2048 + (lane + i * 32) * 16, L, 0, 0, 0); }
      ll_check<0, 4, false>(k4, pk, 1024, tag);
      float s0 = 0, s1 = 0, s2 = 0, s3 = 0;
#pragma unroll
      for (int i = 0; i < 4; i++) { s0 += __uint_as_float(k4[i].x); s1 += __uint_as_float(k4[i].y); s2 += __uint_as_float(k4[i].z); s3 += __uint_as_float(k4[i].w); }
      s0 = qsum(s0); s1 = qsum(s1); s2 = qsum(s2); s3 = qsum(s3);
      if (q == 0) stll2(g_KVR + c * 1024 + 64 * t + warp * 8 + (ln2 >> 2), tg(pack(s0, s1), tag), pack(s2, s3));
      MARK(6 + L * 19);
      wg_wait<0>(); regfence(pp);
      uint2 r[4];
      const uint2* pr = g_KVR + c * 1024 + wg * 512 + (warp & 3) * 32 + ln2;
      hedgehog(pp, [&](int r, int h, int p, uint32_t v) { phq[r][h][p] = v; }, [&] {
#pragma unroll
        for (int u = 0; u < 4; u++) r[u] = ldll2(pr + u * 128); });
      MARK(7 + L * 19);
#pragma unroll 1
      for (int it = 0; it < SPIN; it++) {
        if (!__any_sync(~0u, ((r[0].x ^ tag) | (r[1].x ^ tag) | (r[2].x ^ tag) | (r[3].x ^ tag)) & 1)) break;
#pragma unroll
        for (int u = 0; u < 4; u++) r[u] = ldll2(pr + u * 128);
      }
#pragma unroll
      for (int u = 0; u < 4; u++) {
        const int d = 8 * u + 2 * q;
        if (d < 28) { sts32(sV + sw128(row0, 28 * wg + d), r[u].x); sts32(sV + sw128(row0 + 8, 28 * wg + d), r[u].y); }
        else if (d == 28) {
#pragma unroll
          for (int j = 0; j < 4; j++) { sts16(sV + sw128(row0, 56 + 2 * j + wg), r[u].x); sts16(sV + sw128(row0 + 8, 56 + 2 * j + wg), r[u].y); }
        }
      }
      fence_async();
      bar_cons();
      MARK(8 + L * 19);
      float o[32];
      wg_fence();
#pragma unroll
      for (int ks = 0; ks < 8; ks++) {
        const int h = ks >> 2, p = 2 * (ks & 3);
        wgmma_rs64(o, phq[0][h][p], phq[1][h][p], p < 6 ? phq[0][h][p < 6 ? p + 1 : 0] : 0u, p < 6 ? phq[1][h][p < 6 ? p + 1 : 0] : 0u, mkdesc(d16, OFF_V + ks * 2048, 1024, 1024, 1), ks);
      }
      wg_commit(); wg_wait<0>(); regfence(o);
      const float iA0 = rcp(o[28] + 1e-6f), iB0 = rcp(o[29] + 1e-6f), iA1 = rcp(o[30] + 1e-6f), iB1 = rcp(o[31] + 1e-6f);
      uint32_t w[14];
      { PTRS
#pragma unroll
      for (int j = 0; j < 7; j++) {
        const bool hb = 8 * j + 2 * q >= 28; const float i0 = hb ? iB0 : iA0, i1 = hb ? iB1 : iA1;
        w[2 * j] = pack(o[4 * j] * i0, o[4 * j + 1] * i0); w[2 * j + 1] = pack(o[4 * j + 2] * i1, o[4 * j + 3] * i1);
        if (j == 0 || ((j ^ c) & 1) == 0) w[2 * j] = tg(w[2 * j], tag);
      }
      slice_store(sf + OO, sh + 2 * OO, w, c & 1);
      hint_post(hme, hs + 2, lane); }
    }
    MARK(9 + L * 19);
    uint4 xr[4];
    if (c < 7) {
      PTRS
      ll_issue<0, 4>(xr, fm + XR + 128 * c, 32);
      uint4 a[28];
      const uint4* pa = fm + OO;
      hint_wait(hrow, hs + 2);
      MARK(10 + L * 19);
      ll_issue<0, 28, true>(a, pa, 32, f2 + 2 * OO);
      float y[32];
      uint32_t st;
#define WOSTEP(i) { ll_check<7 * i, 7, true>(a, pa, 32, tag, f2 + 2 * OO); if (!(i & 1)) st = ACQ(6 + i / 2); wg_fence(); \
      _Pragma("unroll") for (int ks = 0; ks < 7; ks++) { const uint4 f = a[7 * i + ks]; \
        wgmma_rs64(y, f.x, f.y, f.z, f.w, mkdesc(st, ((i & 1) * 7 + ks) * 2048, 1024, 1024, 1), i | ks); } wg_commit(); }
      WOSTEP(0) WOSTEP(1) WOSTEP(2) WOSTEP(3)
      ll_check<0, 4, false>(xr, fm + XR + 128 * c, 32, tag);
      wg_wait<0>(); regfence(y);
      MARK(11 + L * 19);
#pragma unroll
      for (int u = 0; u < 4; u++) {
        xr[u].x = tg(pack(blo(xr[u].x) + y[8 * u], bhi(xr[u].x) + y[8 * u + 1]), tag); xr[u].y = pack(blo(xr[u].y) + y[8 * u + 2], bhi(xr[u].y) + y[8 * u + 3]);
        xr[u].z = pack(blo(xr[u].z) + y[8 * u + 4], bhi(xr[u].z) + y[8 * u + 5]); xr[u].w = pack(blo(xr[u].w) + y[8 * u + 6], bhi(xr[u].w) + y[8 * u + 7]);
        stll(fm + X1 + 128 * c + u * 32, xr[u].x, xr[u].y, xr[u].z, xr[u].w);
      }
      hint_post(hme, hs + 3, lane);
    } else {
      PTRS
      hint_post(hme, hs + 3, lane);
      (void)ACQ(6); (void)ACQ(7);
      hint_wait(hrow, hs + 3);
      ll_issue<0, 4>(xr, fm + X1, 32);
      MARK(10 + L * 19); MARK(11 + L * 19);
    }
    uint32_t hf[56];
    float rr0, rr1;
    {
      PTRS
      uint4 a[28];
      const uint4* pa = fm + X1;
      auto grp = [&](int i) -> const uint4* { const int k = i + c; return pa + ((k >= 7 ? k - 7 : k) - i) * 128; };
      if (c == 7) { ll_issue<4, 12>(a, pa, 32); ll_check<0, 4, false>(xr, pa, 32, tag); }
      else {
#pragma unroll
        for (int u = 4; u < 16; u++) a[u] = make_uint4(0, 0, 0, 0);
      }
#pragma unroll
      for (int u = 0; u < 4; u++) a[u] = xr[u];
      float y[96], z[16];
#define F1STAGE(i) { if (i > 0) ll_check<4 * i, 4, false>(a, grp(i), 32, tag); const uint32_t st = ACQ(8 + i); wg_fence(); \
      _Pragma("unroll") for (int ks = 0; ks < 4; ks++) { const uint4 f = a[4 * i + ks]; \
        wgmma_rs192(y, f.x, f.y, f.z, f.w, mkdesc(st, (ks >> 1) * 12288 + (ks & 1) * 2048, 4096, 1024, 1), i | ks); \
        wgmma_rs32(z, f.x, f.y, f.z, f.w, mkdesc(st, 24576 + ks * 1024, 512, 512, 2), i | ks); } \
      wg_commit(); if (i > 0) { wg_wait<1>(); REL(6 + i) if (i < 4) ll_issue<(i < 4 ? 4 * i + 12 : 0), 4>(a, grp(i + 3), 32); } }
      F1STAGE(0)
      MARK(12 + L * 19);
      if (c < 7) {
        if (L == 0) hint_wait(hrow, hs + 3);
        ll_issue<4, 4>(a, grp(1), 32); ll_issue<8, 4>(a, grp(2), 32); ll_issue<12, 4>(a, grp(3), 32);
        float s0 = 0.f, s1 = 0.f, v0 = 0.f, v1 = 0.f;
#pragma unroll
        for (int u = 0; u < 4; u++) { s0 += (blo(xr[u].x) + bhi(xr[u].x)) + (blo(xr[u].z) + bhi(xr[u].z)); s1 += (blo(xr[u].y) + bhi(xr[u].y)) + (blo(xr[u].w) + bhi(xr[u].w)); }
        s0 = qsum(s0) * (1.f / 64); s1 = qsum(s1) * (1.f / 64);
#pragma unroll
        for (int u = 0; u < 4; u++) {
          const float d0 = blo(xr[u].x) - s0, d1 = bhi(xr[u].x) - s0, d2 = blo(xr[u].z) - s0, d3 = bhi(xr[u].z) - s0;
          const float d4 = blo(xr[u].y) - s1, d5 = bhi(xr[u].y) - s1, d6 = blo(xr[u].w) - s1, d7 = bhi(xr[u].w) - s1;
          v0 += (d0 * d0 + d1 * d1) + (d2 * d2 + d3 * d3); v1 += (d4 * d4 + d5 * d5) + (d6 * d6 + d7 * d7);
        }
        v0 = qsum(v0); v1 = qsum(v1);
        if (q == 0) stll(g_ST + ((t * 8 + warp) * 8 + c) * 8 + (ln_ >> 2), tg(__float_as_uint(s0), tag), __float_as_uint(v0), __float_as_uint(s1), __float_as_uint(v1));
      }
      REL(6)
      F1STAGE(1) MARK(13 + L * 19); F1STAGE(2) F1STAGE(3)
      uint4 sv[2];
      const uint4* ps = g_ST + ((t * 8 + warp) * 8 + 2 * (laneid() & 3)) * 8 + (laneid() >> 2);
      ll_issue<0, 2>(sv, ps, q < 3 ? 8 : 0);
      F1STAGE(4)
      ll_check<0, 2, false>(sv, ps, q < 3 ? 8 : 0, tag);
      const float wb = q < 3 ? 1.f : 0.f;
      const float ma = __uint_as_float(sv[0].x), mb = __uint_as_float(sv[1].x), mc = __uint_as_float(sv[0].z), md = __uint_as_float(sv[1].z);
      const float m0 = qsum(ma + wb * mb) * (1.f / 7), m1 = qsum(mc + wb * md) * (1.f / 7);
      const float v0 = qsum(__uint_as_float(sv[0].y) + 64.f * (ma - m0) * (ma - m0) + wb * (__uint_as_float(sv[1].y) + 64.f * (mb - m0) * (mb - m0)));
      const float v1 = qsum(__uint_as_float(sv[0].w) + 64.f * (mc - m1) * (mc - m1) + wb * (__uint_as_float(sv[1].w) + 64.f * (md - m1) * (md - m1)));
      const float e0 = v0 * (1.f / 448) + 1e-5f, e1 = v1 * (1.f / 448) + 1e-5f;
      rr0 = 1.f / e0; rr1 = 1.f / e1;
      auto fold = [&](float m, float sd) -> uint32_t {
        const float mh = blo(pack(-m, 0.f)), sh_ = blo(pack(sd, 0.f));
        return q == 0 ? pack(mh, -m - mh) : q == 1 ? pack(mh, sh_) : q == 2 ? pack(sd - sh_, 0.f) : 0u;
      };
      const uint32_t fa = fold(m0, sqrtf(e0)), fb = fold(m1, sqrtf(e1));
      if (L == 0) asm volatile("bar.sync 4, 288;" ::: "memory");
      wg_fence();
      wgmma_rs192(y, fa, fb, 0u, 0u, mkdesc(d16, OFF_CB, 512, 0, 2), 1);
      wgmma_rs32(z, fa, fb, 0u, 0u, mkdesc(d16, OFF_CB + 3072, 512, 0, 2), 1);
      F1STAGE(5) F1STAGE(6)
      wg_wait<0>(); REL(13) REL(14) regfence(y); regfence(z);
      MARK(14 + L * 19);
#pragma unroll
      for (int j = 0; j < 56; j++) {
        uint32_t r; asm("cvt.rn.relu.bf16x2.f32 %0, %1, %2;" : "=r"(r) : "f"(j < 48 ? y[j < 48 ? 2 * j + 1 : 0] : z[j < 48 ? 0 : 2 * j - 95]), "f"(j < 48 ? y[j < 48 ? 2 * j : 0] : z[j < 48 ? 0 : 2 * j - 96]));
        asm("mul.bf16x2 %0, %1, %1;" : "=r"(hf[j]) : "r"(r));
      }
    }
    MARK(15 + L * 19);
    {
      PTRS
      float ya[32], yb[32];
      uint4* pp = g_P + ((t * 8 + warp) * 8 + ((c - warp) & 7)) * 28 * 32 + ln_;
#define F2STORE(j, Y) { regfence(Y); _Pragma("unroll") for (int u = 0; u < 4; u++) { \
      const uint32_t w0 = tg(pack(Y[8 * u] * rr0, Y[8 * u + 1] * rr0), tag), w1_ = pack(Y[8 * u + 2] * rr1, Y[8 * u + 3] * rr1), \
                     w2_ = pack(Y[8 * u + 4] * rr0, Y[8 * u + 5] * rr0), w3 = pack(Y[8 * u + 6] * rr1, Y[8 * u + 7] * rr1); \
      if (warp == c) sts128(sPK + (4 * (j) + u) * 512 + ln_ * 16, w0, w1_, w2_, w3); else stll(pp + (4 * (j) + u) * 32, w0, w1_, w2_, w3); } \
      if ((j) >= 5) hint_post(hme, hs + (4 + (j)), lane); }
#define F2PASS(j, Y, Z) { const uint32_t st = ACQ(15 + j); wg_fence(); \
      _Pragma("unroll") for (int ks = 0; ks < 14; ks++) wgmma_rs64(Y, hf[4 * ks], hf[4 * ks + 1], hf[4 * ks + 2], hf[4 * ks + 3], mkdesc(st, ks * 2048, 1024, 1024, 1), ks); \
      wg_commit(); if (j > 0) { wg_wait<1>(); if (j < 6) REL(14 + j) F2STORE(j - 1, Z) } }
      const uint4* pr = g_P + ((t * 8 + c) * 8 * 28 + warp) * 32 + ln_;
      uint4 p[8], p2[8]; uint2 xa, xb, xc, xd; uint32_t ba, bb, bc, bd;
      const uint32_t ptag = tag;
      const uint32_t* hred = g_H + (t * 8 + c) * 8 + (ln_ & 7);
      F2PASS(0, ya, yb) F2PASS(1, yb, ya) F2PASS(2, ya, yb) F2PASS(3, yb, ya)
      F2PASS(4, ya, yb)
      RISSUE(0, p, xa, xb, ba, bb)
      F2PASS(5, yb, ya)
      REDU(0, p, xa, xb, ba, bb)
      if (L == 0) { xw[0][0] = tg(xw[0][0], 0); RPUB(0) }
      F2PASS(6, ya, yb)
      RISSUE(1, p, xa, xb, ba, bb)
      wg_wait<0>(); F2STORE(6, ya)
      MARK(16 + L * 19);
      if (wg) hint_wait(hred, hs + 9);
      RISSUE(2, p2, xc, xd, bc, bd)
      REDU(1, p, xa, xb, ba, bb)
      if (L == 0) { xw[1][0] = tg(xw[1][0], 0); RPUB(1) }
      MARK(17 + L * 19);
      REDU(2, p2, xc, xd, bc, bd)
      if (L == 0) { xw[2][0] = tg(xw[2][0], 0); RPUB(2) }
    }
    MARK(18 + L * 19);
  }
  {
    PTRS
    uint32_t* op = (uint32_t*)(out + XOFF(ln_));
#define OUT(u) { op[u * 64] = xw[u][0]; op[u * 64 + 1792] = xw[u][1]; op[u * 64 + 4] = xw[u][2]; op[u * 64 + 1796] = xw[u][3]; }
    OUT(0) OUT(1) OUT(2)
    if (wg == 0) { RLAST(0u, 20u) OUT(3) }
    else if (warp == 7) {
      if (t == 0 && lane == 0) g_WQF[c] = 0;
      if (lane < 8) stll(g_S2 + (t * 8 + c) * 8 + lane, 0, 0, 0, 0);
      if (lane < 4) { stll(g_CS + blockIdx.x * 4 + lane, 0, 0, 0, 0); if (blockIdx.x < 68) stll(g_CS + 512 + blockIdx.x * 4 + lane, 0, 0, 0, 0); }
    }
  }
  MARK(38); GT(39);
  }
}

typedef CUresult (*EncFn)(CUtensorMap*, CUtensorMapDataType, cuuint32_t, void*, const cuuint64_t*, const cuuint64_t*, const cuuint32_t*, const cuuint32_t*,
                          CUtensorMapInterleave, CUtensorMapSwizzle, CUtensorMapL2promotion, CUtensorMapFloatOOBfill);

extern "C" void kernel_launch(void* const* d_in, const int* in_sizes, int n_in, void* d_out, int out_size) {
  static EncFn enc = nullptr;
  if (!enc) {
    void* fn = nullptr; cudaDriverEntryPointQueryResult qr;
    cudaGetDriverEntryPoint("cuTensorMapEncodeTiled", &fn, cudaEnableDefault, &qr);
    enc = (EncFn)fn;
    cudaFuncSetAttribute(fused_kernel, cudaFuncAttributeMaxDynamicSharedMemorySize, SMEM_BYTES);
  }
  CUtensorMap mQKV, mWO, mW1, mW1b, mW2, mW2b, mX;
  const cuuint32_t es[3] = {1, 1, 1};
  auto enc2 = [&](CUtensorMap* m, void* p, cuuint64_t cols, cuuint64_t rows, cuuint32_t bc, cuuint32_t br) {
    const cuuint64_t dims[2] = {cols, rows}, str[1] = {cols * 2}; const cuuint32_t box[2] = {bc, br};
    enc(m, CU_TENSOR_MAP_DATA_TYPE_BFLOAT16, 2, p, dims, str, box, es, CU_TENSOR_MAP_INTERLEAVE_NONE,
        bc == 64 ? CU_TENSOR_MAP_SWIZZLE_128B : CU_TENSOR_MAP_SWIZZLE_64B, CU_TENSOR_MAP_L2_PROMOTION_L2_128B, CU_TENSOR_MAP_FLOAT_OOB_FILL_NONE);
  };
  enc2(&mQKV, d_in[1], 1344, 448, 64, 112); enc2(&mWO, d_in[3], 448, 448, 64, 112); enc2(&mW1b, d_in[5], 1792, 448, 32, 32);
  enc2(&mX, d_in[0], 448, 2048, 64, 128);
  enc2(&mW2, d_in[7], 448, 1792, 64, 96); enc2(&mW2b, d_in[7], 448, 1792, 64, 16);
  {
    const cuuint64_t dims[3] = {64, 448, 28}, str[2] = {3584, 128}; const cuuint32_t box[3] = {64, 32, 3};
    enc(&mW1, CU_TENSOR_MAP_DATA_TYPE_BFLOAT16, 3, d_in[5], dims, str, box, es, CU_TENSOR_MAP_INTERLEAVE_NONE, CU_TENSOR_MAP_SWIZZLE_128B,
        CU_TENSOR_MAP_L2_PROMOTION_L2_128B, CU_TENSOR_MAP_FLOAT_OOB_FILL_NONE);
  }
  typedef const __nv_bfloat16* BP;
  fused_kernel<<<128, 384, SMEM_BYTES>>>(mQKV, mWO, mW1, mW1b, mW2, mW2b, mX, (BP)d_in[1], (BP)d_in[2], (BP)d_in[3], (BP)d_in[5], (BP)d_in[6], (BP)d_in[7], (BP)d_in[8],
                                         (__nv_bfloat16*)d_out);
}
```
